```python
import torch

def _softmax(x, axis=-1):
    return torch.softmax(x, dim=axis)
def _gelu(x):
    return torch.nn.functional.gelu(x, approximate="tanh")
def _silu(x):
    return torch.nn.functional.silu(x)
def _sigmoid(x):
    return torch.sigmoid(x)
def _layernorm(x, axis=-1, eps=1e-5):
    m = x.mean(dim=axis, keepdim=True)
    v = x.var(dim=axis, keepdim=True, unbiased=False)
    return (x - m) / torch.sqrt(v + eps)
def _scatter_add(tgt, idx, src, axis=0):
    return tgt.clone().index_add_(axis, idx, src)
def _segment_sum(src, seg, n):
    out = torch.zeros((n,) + src.shape[1:], dtype=src.dtype)
    return out.index_add_(0, seg, src)
def _pad(x, pw):
    flat = tuple(v for pair in reversed(pw) for v in pair)
    return torch.nn.functional.pad(x, flat)

kernel_name = 'parallel_sum__sliding_local_dilated__mixer_token_mlp__prompt'

def setup_inputs():

    _w = (lambda a: (lambda t: t.to(torch.bfloat16) if t.is_floating_point() else t)(torch.as_tensor(a)))
    def _A_setup():
        B, S, D = 1, 2048, 448
        return {
            "x": _w((lambda *s: torch.randn(*s, dtype=torch.bfloat16) * 0.05)(B, S, D)),
            "wqkv": _w((lambda *s: torch.randn(*s, dtype=torch.bfloat16) * 0.05)(D, 3 * D)),
            "wo": _w((lambda *s: torch.randn(*s, dtype=torch.bfloat16) * 0.05)(D, D)),
        }
    _A_in = _A_setup()

    def _B_setup():
        B, S, D, F = 1, 2048, 448, 1792
        return {
            "x": _w((lambda *s: torch.randn(*s, dtype=torch.bfloat16) * 0.05)(B, S, D)),
            "w1": _w((lambda *s: torch.randn(*s, dtype=torch.bfloat16) * 1.6)(S, F) * (S ** -0.5)),
            "b1": _w((lambda *s: torch.randn(*s, dtype=torch.bfloat16) * 12.8)(F) * 0.02),
            "w2": _w((lambda *s: torch.randn(*s, dtype=torch.bfloat16) * 0.4)(F, S) * (F ** -0.5)),
            "b2": _w((lambda *s: torch.randn(*s, dtype=torch.bfloat16) * 6.4)(S) * 0.02),
        }
    _B_in = _B_setup()

    return {
        "A_x": _A_in["x"],
        "A_wqkv": _A_in["wqkv"],
        "A_wo": _A_in["wo"],
        "B_x": _B_in["x"],
        "B_w1": _B_in["w1"],
        "B_b1": _B_in["b1"],
        "B_w2": _B_in["w2"],
        "B_b2": _B_in["b2"],
    }

def reference(A_x, A_wqkv, A_wo, B_x, B_w1, B_b1, B_w2, B_b2):
    def _A_ref(x, wqkv, wo):
        B, S, D = x.shape
        H = 16; Dh = D // H
        W, dil = 8, 2
        qkv = (lambda x, *d: x.permute(*d))((x @ wqkv).reshape(B, S, 3, H, Dh), 2, 0, 3, 1, 4)
        q, k, v = qkv[0], qkv[1], qkv[2]
        scale = Dh ** -0.5
        pos = torch.arange(S)
        off = torch.arange(W) * dil
        idx = pos[:, None] - off[None, :]
        mask = idx >= 0
        idx_c = torch.where(mask, idx, 0).reshape(-1)
        kg = k[:, :, idx_c, :].reshape(B, H, S, W, Dh)
        vg = v[:, :, idx_c, :].reshape(B, H, S, W, Dh)
        logits = torch.einsum("bhsd,bhswd->bhsw", q, kg) * scale
        logits = torch.where(mask[None, None, :, :], logits, -1e9)
        attn = _softmax(logits, axis=-1)
        o = torch.einsum("bhsw,bhswd->bhsd", attn, vg)
        return (lambda x, *d: x.permute(*d))(o, 0, 2, 1, 3).reshape(B, S, D) @ wo

    def _B_ref(x, w1, b1, w2, b2):
        B, S, D = x.shape
        h = _layernorm(x, axis=-1)
        u = torch.einsum("bsd,sf->bdf", h, w1) + b1
        u = _gelu(u)
        y = torch.einsum("bdf,fs->bds", u, w2) + b2
        return (lambda x, *d: x.permute(*d))(y, 0, 2, 1)

    x = A_x
    xn = _layernorm(x, axis=-1)
    return x + _A_ref(xn, A_wqkv, A_wo) + _B_ref(xn, B_w1, B_b1, B_w2, B_b2)
```

```cpp
#include <cuda_runtime.h>
#include <cuda.h>
#include <cuda_bf16.h>
#include <stdint.h>

namespace {

constexpr int S_ = 2048, D_ = 448, F_ = 1792;
constexpr uint32_t BLK = 14336;

__device__ __align__(1024) uint8_t g_himg[32 * 4 * BLK];
__device__ __align__(1024) uint8_t g_bimg[35 * 4 * BLK];
__device__ __align__(1024) __nv_bfloat16 g_o[S_ * D_];
__device__ __align__(128) float2 g_stats[2 * 1024];
__device__ __align__(128) float g_cs[3 * D_];
__device__ __align__(128) uint8_t g_halo[128 * 2 * 896];
__device__ __align__(128) unsigned g_ctr[2048];

constexpr int C_LN = 0, C_CS = 32, C_WO = 64, C_O = 128, C_U = 512, C_HALO = 1024;

#define TS(id)

constexpr uint32_t OFF_A = 0;
constexpr uint32_t OFF_B = 98304;
constexpr uint32_t OFF_Q = 184320, OFF_K = 198656, OFF_V = 213888;
constexpr uint32_t OFF_STATS = 229120;
constexpr uint32_t OFF_CS = OFF_STATS + 1024;
constexpr uint32_t OFF_LNST = OFF_CS + 768;
constexpr uint32_t OFF_CSP = OFF_LNST + 128;
constexpr uint32_t OFF_EP = OFF_CSP + 256;
constexpr uint32_t OFF_BAR = OFF_EP + 16;
constexpr uint32_t SMEM_BYTES = OFF_BAR + 8 * 48;

enum : int {
    B_FULLQ = 0, B_EMPTYQ = 7, B_FULL = 14, B_EMPTY = 20, B_LNST = 26, B_LNFREE = 27, B_AUX = 28, B_QKV = 29,
    B_HALO = 30, B_FREE = 31, B_RECV1 = 32, B_RECV2 = 34, B_UST = 36, B_EP = 38, B_COUNT = 39
};

__device__ __forceinline__ uint32_t smem_u32(const void* p) { return (uint32_t)__cvta_generic_to_shared(p); }
__device__ __forceinline__ void mbar_init(uint32_t a, int c) { asm volatile("mbarrier.init.shared::cta.b64 [%0], %1;" ::"r"(a), "r"(c) : "memory"); }
__device__ __forceinline__ void mbar_expect(uint32_t a, uint32_t b) { asm volatile("mbarrier.arrive.expect_tx.shared::cta.b64 _, [%0], %1;" ::"r"(a), "r"(b) : "memory"); }
__device__ __forceinline__ void mbar_arrive(uint32_t a) { asm volatile("mbarrier.arrive.shared::cta.b64 _, [%0];" ::"r"(a) : "memory"); }
__device__ __forceinline__ void mbar_wait(uint32_t a, uint32_t parity) {
    asm volatile(
        "{\n.reg .pred p;\n.reg .u32 n;\nmov.u32 n, 0;\n"
        "W0:\nmbarrier.try_wait.parity.shared::cta.b64 p, [%0], %1;\n@p bra W1;\n"
        "add.u32 n, n, 1;\nsetp.lt.u32 p, n, 4194304;\n@p bra W0;\ntrap;\nW1:\n}\n" ::"r"(a), "r"(parity) : "memory");
}
__device__ __forceinline__ void mbar_wait_cluster(uint32_t a, uint32_t parity) {
    asm volatile(
        "{\n.reg .pred p;\n.reg .u32 n;\nmov.u32 n, 0;\n"
        "W0:\nmbarrier.try_wait.parity.acquire.cluster.shared::cta.b64 p, [%0], %1;\n@p bra W1;\n"
        "add.u32 n, n, 1;\nsetp.lt.u32 p, n, 4194304;\n@p bra W0;\ntrap;\nW1:\n}\n" ::"r"(a), "r"(parity) : "memory");
}
__device__ __forceinline__ uint32_t mapa(uint32_t a, uint32_t cta) { uint32_t r; asm("mapa.shared::cluster.u32 %0, %1, %2;" : "=r"(r) : "r"(a), "r"(cta)); return r; }
__device__ __forceinline__ void tma2d(uint32_t dst, const CUtensorMap* m, int c0, int c1, uint32_t bar) {
    asm volatile("cp.async.bulk.tensor.2d.shared::cluster.global.mbarrier::complete_tx::bytes [%0], [%1, {%3, %4}], [%2];" ::"r"(dst), "l"(m), "r"(bar), "r"(c0), "r"(c1) : "memory");
}
__device__ __forceinline__ void tma3d(uint32_t dst, const CUtensorMap* m, int c0, int c1, int c2, uint32_t bar) {
    asm volatile("cp.async.bulk.tensor.3d.shared::cluster.global.mbarrier::complete_tx::bytes [%0], [%1, {%3, %4, %5}], [%2];" ::"r"(dst), "l"(m), "r"(bar), "r"(c0), "r"(c1), "r"(c2) : "memory");
}
__device__ __forceinline__ void tma2d_store(const CUtensorMap* m, uint32_t src, int c0, int c1) {
    asm volatile("cp.async.bulk.tensor.2d.global.shared::cta.bulk_group [%0, {%2, %3}], [%1];" ::"l"(m), "r"(src), "r"(c0), "r"(c1) : "memory");
}
__device__ __forceinline__ void bulk_load(uint32_t dst, const void* src, uint32_t bytes, uint32_t bar) {
    asm volatile("cp.async.bulk.shared::cluster.global.mbarrier::complete_tx::bytes [%0], [%1], %2, [%3];" ::"r"(dst), "l"(src), "r"(bytes), "r"(bar) : "memory");
}
__device__ __forceinline__ void bulk_store(void* dst, uint32_t src, uint32_t bytes) {
    asm volatile("cp.async.bulk.global.shared::cta.bulk_group [%0], [%1], %2;" ::"l"(dst), "r"(src), "r"(bytes) : "memory");
}
__device__ __forceinline__ void bulk_commit() { asm volatile("cp.async.bulk.commit_group;" ::: "memory"); }
__device__ __forceinline__ void bulk_wait_all() { asm volatile("cp.async.bulk.wait_group 0;" ::: "memory"); }
__device__ __forceinline__ void bulk_wait_read() { asm volatile("cp.async.bulk.wait_group.read 0;" ::: "memory"); }
__device__ __forceinline__ void l2_prefetch(const void* p, uint32_t bytes) { asm volatile("cp.async.bulk.prefetch.L2.global [%0], %1;" ::"l"(p), "r"(bytes) : "memory"); }
__device__ __forceinline__ void fence_async_smem() { asm volatile("fence.proxy.async.shared::cta;" ::: "memory"); }
__device__ __forceinline__ void fence_async_global() { asm volatile("fence.proxy.async.global;" ::: "memory"); }
__device__ __forceinline__ void red_relaxed(unsigned* p) { asm volatile("red.relaxed.gpu.global.add.u32 [%0], 1;" ::"l"(p) : "memory"); }
__device__ __forceinline__ void red_release(unsigned* p) { asm volatile("red.release.gpu.global.add.u32 [%0], 1;" ::"l"(p) : "memory"); }
__device__ __forceinline__ unsigned ld_relaxed(const unsigned* p) { unsigned v; asm volatile("ld.relaxed.gpu.global.u32 %0, [%1];" : "=r"(v) : "l"(p) : "memory"); return v; }
__device__ __forceinline__ bool ctr_done(unsigned v, unsigned target) { return ((v - target) & 0x1FFFFFFu) == 0; }
__device__ __forceinline__ void poll(const unsigned* p, unsigned target) {
    int n = 0;
    while (!ctr_done(ld_relaxed(p), target)) { if (++n > (1 << 21)) __trap(); }
}
template <int ID, int N> __device__ __forceinline__ void bar_sync() { asm volatile("bar.sync %0, %1;" ::"n"(ID), "n"(N) : "memory"); }
__device__ __forceinline__ void bar_sync_id(int id, int n) { asm volatile("bar.sync %0, %1;" ::"r"(id), "r"(n) : "memory"); }
__device__ __forceinline__ void wg_fence() { asm volatile("wgmma.fence.sync.aligned;" ::: "memory"); }
__device__ __forceinline__ void wg_commit() { asm volatile("wgmma.commit_group.sync.aligned;" ::: "memory"); }
template <int N> __device__ __forceinline__ void wg_wait() { asm volatile("wgmma.wait_group.sync.aligned %0;" ::"n"(N) : "memory"); }
template <int N> __device__ __forceinline__ void pin(float (&a)[N]) {
#pragma unroll
    for (int i = 0; i < N; i++) asm volatile("" : "+f"(a[i])::"memory");
}
__device__ __forceinline__ uint4 ldg_nc(const uint4* p) {
    uint4 v;
    asm volatile("ld.global.nc.v4.u32 {%0,%1,%2,%3}, [%4];" : "=r"(v.x), "=r"(v.y), "=r"(v.z), "=r"(v.w) : "l"(p));
    return v;
}
__device__ __forceinline__ uint32_t pack2(float lo, float hi) { uint32_t r; asm("cvt.rn.bf16x2.f32 %0, %1, %2;" : "=r"(r) : "f"(hi), "f"(lo)); return r; }
__device__ __forceinline__ float bf_lo(uint32_t v) { return __uint_as_float(v << 16); }
__device__ __forceinline__ float bf_hi(uint32_t v) { return __uint_as_float(v & 0xFFFF0000u); }
__device__ __forceinline__ void stsm4(uint32_t a, uint32_t r0, uint32_t r1, uint32_t r2, uint32_t r3) {
    asm volatile("stmatrix.sync.aligned.m8n8.x4.shared.b16 [%0], {%1, %2, %3, %4};" ::"r"(a), "r"(r0), "r"(r1), "r"(r2), "r"(r3) : "memory");
}
__device__ __forceinline__ void stsm2(uint32_t a, uint32_t r0, uint32_t r1) {
    asm volatile("stmatrix.sync.aligned.m8n8.x2.shared.b16 [%0], {%1, %2};" ::"r"(a), "r"(r0), "r"(r1) : "memory");
}
__device__ __forceinline__ void ldsm4(uint32_t a, uint32_t (&r)[4]) {
    asm volatile("ldmatrix.sync.aligned.m8n8.x4.shared.b16 {%0, %1, %2, %3}, [%4];" : "=r"(r[0]), "=r"(r[1]), "=r"(r[2]), "=r"(r[3]) : "r"(a) : "memory");
}
__device__ __forceinline__ void ldsm4t(uint32_t a, uint32_t (&r)[4]) {
    asm volatile("ldmatrix.sync.aligned.m8n8.x4.trans.shared.b16 {%0, %1, %2, %3}, [%4];" : "=r"(r[0]), "=r"(r[1]), "=r"(r[2]), "=r"(r[3]) : "r"(a) : "memory");
}
__device__ __forceinline__ void mma16816(float (&c)[4], uint32_t a0, uint32_t a1, uint32_t a2, uint32_t a3, uint32_t b0, uint32_t b1) {
    asm volatile("mma.sync.aligned.m16n8k16.row.col.f32.bf16.bf16.f32 {%0,%1,%2,%3}, {%4,%5,%6,%7}, {%8,%9}, {%0,%1,%2,%3};"
                 : "+f"(c[0]), "+f"(c[1]), "+f"(c[2]), "+f"(c[3]) : "r"(a0), "r"(a1), "r"(a2), "r"(a3), "r"(b0), "r"(b1));
}
__device__ __forceinline__ void mma1688(float (&c)[4], uint32_t a0, uint32_t a1, uint32_t b0) {
    asm volatile("mma.sync.aligned.m16n8k8.row.col.f32.bf16.bf16.f32 {%0,%1,%2,%3}, {%4,%5}, {%6}, {%0,%1,%2,%3};"
                 : "+f"(c[0]), "+f"(c[1]), "+f"(c[2]), "+f"(c[3]) : "r"(a0), "r"(a1), "r"(b0));
}
__device__ __forceinline__ uint64_t mkdesc(uint32_t addr, uint32_t lbo, uint32_t sbo, uint32_t sw) {
    uint32_t lo = ((addr & 0x3FFFF) >> 4) | ((lbo >> 4) << 16), hi = (sbo >> 4) | (sw << 30);
    return ((uint64_t)hi << 32) | lo;
}
__device__ __forceinline__ float gelu_tanh(float x) {
    float y = x * fmaf(x * x, 0.0356774081363f, 0.7978845608029f), t;
    asm("tanh.approx.f32 %0, %1;" : "=f"(t) : "f"(y));
    float hx = 0.5f * x;
    return fmaf(hx, t, hx);
}

template <int TA, int TB>
__device__ __forceinline__ void wgmma_m64n56k16(float (&d)[28], uint64_t da, uint64_t db, int scale_d) {
    asm volatile("{\n.reg .pred p;\nsetp.ne.b32 p, %30, 0;\n"
        "wgmma.mma_async.sync.aligned.m64n56k16.f32.bf16.bf16 "
        "{%0, %1, %2, %3, %4, %5, %6, %7, %8, %9, %10, %11, %12, %13, %14, %15, %16, %17, %18, %19, %20, %21, %22, %23, %24, %25, %26, %27}, "
        "%28, %29, p, 1, 1, %31, %32;\n}\n"
        : "+f"(d[0]), "+f"(d[1]), "+f"(d[2]), "+f"(d[3]), "+f"(d[4]), "+f"(d[5]), "+f"(d[6]), "+f"(d[7]), "+f"(d[8]), "+f"(d[9]), "+f"(d[10]), "+f"(d[11]), "+f"(d[12]), "+f"(d[13]), "+f"(d[14]), "+f"(d[15]), "+f"(d[16]), "+f"(d[17]), "+f"(d[18]), "+f"(d[19]), "+f"(d[20]), "+f"(d[21]), "+f"(d[22]), "+f"(d[23]), "+f"(d[24]), "+f"(d[25]), "+f"(d[26]), "+f"(d[27])
        : "l"(da), "l"(db), "r"(scale_d), "n"(TA), "n"(TB));
}
template <int TA, int TB>
__device__ __forceinline__ void wgmma_m64n112k16(float (&d)[56], uint64_t da, uint64_t db, int scale_d) {
    asm volatile("{\n.reg .pred p;\nsetp.ne.b32 p, %58, 0;\n"
        "wgmma.mma_async.sync.aligned.m64n112k16.f32.bf16.bf16 "
        "{%0, %1, %2, %3, %4, %5, %6, %7, %8, %9, %10, %11, %12, %13, %14, %15, %16, %17, %18, %19, %20, %21, %22, %23, %24, %25, %26, %27, %28, %29, %30, %31, %32, %33, %34, %35, %36, %37, %38, %39, %40, %41, %42, %43, %44, %45, %46, %47, %48, %49, %50, %51, %52, %53, %54, %55}, "
        "%56, %57, p, 1, 1, %59, %60;\n}\n"
        : "+f"(d[0]), "+f"(d[1]), "+f"(d[2]), "+f"(d[3]), "+f"(d[4]), "+f"(d[5]), "+f"(d[6]), "+f"(d[7]), "+f"(d[8]), "+f"(d[9]), "+f"(d[10]), "+f"(d[11]), "+f"(d[12]), "+f"(d[13]), "+f"(d[14]), "+f"(d[15]), "+f"(d[16]), "+f"(d[17]), "+f"(d[18]), "+f"(d[19]), "+f"(d[20]), "+f"(d[21]), "+f"(d[22]), "+f"(d[23]), "+f"(d[24]), "+f"(d[25]), "+f"(d[26]), "+f"(d[27]), "+f"(d[28]), "+f"(d[29]), "+f"(d[30]), "+f"(d[31]), "+f"(d[32]), "+f"(d[33]), "+f"(d[34]), "+f"(d[35]), "+f"(d[36]), "+f"(d[37]), "+f"(d[38]), "+f"(d[39]), "+f"(d[40]), "+f"(d[41]), "+f"(d[42]), "+f"(d[43]), "+f"(d[44]), "+f"(d[45]), "+f"(d[46]), "+f"(d[47]), "+f"(d[48]), "+f"(d[49]), "+f"(d[50]), "+f"(d[51]), "+f"(d[52]), "+f"(d[53]), "+f"(d[54]), "+f"(d[55])
        : "l"(da), "l"(db), "r"(scale_d), "n"(TA), "n"(TB));
}

__device__ __forceinline__ void send_half(const float (&a)[56], uint32_t rbuf, uint32_t rbar, int t) {
    uint32_t p[14];
#pragma unroll
    for (int i = 0; i < 14; i++) p[i] = pack2(a[28 + 2 * i], a[29 + 2 * i]);
#pragma unroll
    for (int i = 0; i < 3; i++)
        asm volatile("st.async.weak.shared::cluster.mbarrier::complete_tx::bytes.v4.b32 [%0], {%1,%2,%3,%4}, [%5];" ::"r"(rbuf + i * 2048 + t * 16),
                     "r"(p[4 * i]), "r"(p[4 * i + 1]), "r"(p[4 * i + 2]), "r"(p[4 * i + 3]), "r"(rbar) : "memory");
    asm volatile("st.async.weak.shared::cluster.mbarrier::complete_tx::bytes.v2.b32 [%0], {%1,%2}, [%3];" ::"r"(rbuf + 6144 + t * 8), "r"(p[12]), "r"(p[13]), "r"(rbar) : "memory");
}
__device__ __forceinline__ void recv_half(uint32_t (&p)[14], uint32_t buf, int t) {
#pragma unroll
    for (int i = 0; i < 3; i++)
        asm volatile("ld.shared.v4.b32 {%0,%1,%2,%3}, [%4];" : "=r"(p[4 * i]), "=r"(p[4 * i + 1]), "=r"(p[4 * i + 2]), "=r"(p[4 * i + 3]) : "r"(buf + i * 2048 + t * 16) : "memory");
    asm volatile("ld.shared.v2.b32 {%0,%1}, [%2];" : "=r"(p[12]), "=r"(p[13]) : "r"(buf + 6144 + t * 8) : "memory");
}

struct Maps { CUtensorMap x, wqkv, w1, w2, old_, ost, out; };

__global__ void __cluster_dims__(2, 1, 1) __launch_bounds__(512, 1)
fused_kernel(const __grid_constant__ Maps mp, const __nv_bfloat16* __restrict__ x, const __nv_bfloat16* __restrict__ wqkv,
             const __nv_bfloat16* __restrict__ wo, const __nv_bfloat16* __restrict__ w1, const __nv_bfloat16* __restrict__ b1,
             const __nv_bfloat16* __restrict__ w2, const __nv_bfloat16* __restrict__ b2) {
    extern __shared__ __align__(1024) uint8_t smem[];
    const uint32_t sb = smem_u32(smem);
    const uint32_t bar = sb + OFF_BAR;
    const int tid = threadIdx.x, lane = tid & 31;
    const int warp = __shfl_sync(0xffffffffu, tid >> 5, 0);
    const int b = blockIdx.x, z = b & 1, c = b >> 1;
    int q, j;
    if (c < 4) { q = 15; j = c; } else if (c < 36) { q = (c - 4) & 7; j = (c - 4) >> 3; } else { q = 8 + (c - 36) % 7; j = (c - 36) / 7; }
    const bool g1 = q < 14;
    const int R = q >> 1, P = (q & 1) * 4 + j;

    TS(warp == 0 ? 0 : 63);
    auto cta_start = [&]() {
        bar_sync<0, 512>();
        asm volatile("barrier.cluster.arrive.relaxed.aligned;" ::: "memory");
    };

    if (warp < 8) {
        asm volatile("setmaxnreg.inc.sync.aligned.u32 176;");
        cta_start();
        const int wg = warp >> 2, w4 = warp & 3, t = tid & 127, g = lane >> 2, tq = lane & 3;
        float a1[56];
        {
            float bl = 0.f, bh = 0.f;
            if (g1) { bl = __bfloat162float(b1[q * 128 + wg * 64 + w4 * 16 + g]); bh = __bfloat162float(b1[q * 128 + wg * 64 + w4 * 16 + g + 8]); }
#pragma unroll
            for (int i = 0; i < 56; i++) a1[i] = i < 28 ? ((i & 2) ? bh : bl) : 0.f;
        }
        uint32_t st = 0, ph = 0;
        const uint64_t dA = mkdesc(sb + OFF_A + wg * 8192, 16, 1024, 1);
        const uint64_t dH = mkdesc(sb + OFF_B, 1792, 128, 0);
        const uint64_t dU = mkdesc(sb + OFF_B, 128, 1024, 0);
        auto release = [&](uint32_t a) { if (lane == 0) mbar_arrive(a); };
        auto advance = [&]() { if (++st == 6) { st = 0; ph ^= 1; } };
        auto prev_empty = [&](uint32_t back) { uint32_t s = st + 6 - back; if (s >= 6) s -= 6; return bar + 8 * (B_EMPTY + s); };
        auto g1_issue = [&]() {
            if (g1) mbar_wait(bar + 8 * (B_FULL + st), ph);
            wg_fence();
#pragma unroll
            for (int k = 0; k < 4; k++) wgmma_m64n112k16<1, 1>(a1, dA + st * 1024 + k * 128, dH + st * 896 + k * 224, 1);
            wg_commit();
            if (g1) advance();
        };
        {
            float aq0[28], aq1[28], aq2[28];
            const uint64_t dW = mkdesc(sb + OFF_B, 16, 1024, 1);
#pragma unroll 1
            for (int kb = 0; kb < 7; kb++) {
                const uint32_t xs = (0x5432154u >> (4 * kb)) & 7, ws = (0x3421034u >> (4 * kb)) & 7;
                mbar_wait(bar + 8 * (B_FULLQ + kb), 0);
                if (kb == 0) TS(warp == 0 ? 1 : 63);
                wg_fence();
#pragma unroll
                for (int k = 0; k < 4; k++) {
                    const int sc = (k > 0) | (kb > 0);
                    wgmma_m64n56k16<0, 1>(aq0, dA + xs * 1024 + k * 2, dW + ws * 1536 + k * 128, sc);
                    wgmma_m64n56k16<0, 1>(aq1, dA + xs * 1024 + k * 2, dW + ws * 1536 + 512 + k * 128, sc);
                    wgmma_m64n56k16<0, 1>(aq2, dA + xs * 1024 + k * 2, dW + ws * 1536 + 1024 + k * 128, sc);
                }
                wg_commit();
                wg_wait<1>();
                if (kb > 0) release(bar + 8 * (B_EMPTYQ + kb - 1));
            }
            TS(warp == 0 ? 2 : 63);
            g1_issue();
            wg_wait<1>();
            pin(aq0); pin(aq1); pin(aq2);
            release(bar + 8 * (B_EMPTYQ + 6));
            TS(warp == 0 ? 3 : 63);
            g1_issue();
            mbar_wait(bar + 8 * B_AUX, 0);
            bar_sync<1, 256>();
            const int row = wg * 64 + w4 * 16;
            const float2 sl = *reinterpret_cast<const float2*>(smem + OFF_STATS + (row + g) * 8);
            const float2 sh = *reinterpret_cast<const float2*>(smem + OFF_STATS + (row + g + 8) * 8);
            const uint32_t so = (row + (lane & 15)) * 112 + (lane >> 4) * 16;
            auto put = [&](const float (&a)[28], int sec, uint32_t dst) {
                uint32_t p[14];
#pragma unroll
                for (int n = 0; n < 7; n++) {
                    const float2 cs = *reinterpret_cast<const float2*>(smem + OFF_CS + sec * 224 + n * 32 + tq * 8);
                    p[2 * n] = pack2(fmaf(a[4 * n], sl.x, sl.y * cs.x), fmaf(a[4 * n + 1], sl.x, sl.y * cs.y));
                    p[2 * n + 1] = pack2(fmaf(a[4 * n + 2], sh.x, sh.y * cs.x), fmaf(a[4 * n + 3], sh.x, sh.y * cs.y));
                }
#pragma unroll
                for (int n = 0; n < 3; n++) stsm4(dst + so + n * 32, p[4 * n], p[4 * n + 1], p[4 * n + 2], p[4 * n + 3]);
                stsm2(dst + (row + (lane & 15)) * 112 + 96, p[12], p[13]);
            };
            put(aq1, 1, sb + OFF_K + 896);
            put(aq2, 2, sb + OFF_V + 896);
            put(aq0, 0, sb + OFF_Q);
            fence_async_smem();
            __syncwarp();
            release(bar + 8 * B_QKV);
            TS(warp == 0 ? 4 : 63);
        }
        uint32_t xv[14];
        const int orow = q * 128 + wg * 64 + w4 * 16 + g;
        {
            const uint32_t* px = reinterpret_cast<const uint32_t*>(x + (size_t)orow * D_ + j * 112 + z * 56) + tq;
#pragma unroll
            for (int n = 0; n < 7; n++) {
                asm volatile("ld.global.nc.u32 %0, [%1];" : "=r"(xv[2 * n]) : "l"(px + 4 * n));
                asm volatile("ld.global.nc.u32 %0, [%1];" : "=r"(xv[2 * n + 1]) : "l"(px + 4 * n + 8 * (D_ / 2)));
            }
        }
        unsigned short b2l, b2h;
        asm volatile("ld.global.nc.u16 %0, [%1];" : "=h"(b2l) : "l"(b2 + orow));
        asm volatile("ld.global.nc.u16 %0, [%1];" : "=h"(b2h) : "l"(b2 + orow + 8));
        wg_wait<1>();
        if (g1) release(prev_empty(2));
#pragma unroll 1
        for (int it = g1 ? 2 : 16; it < 16; it++) {
            g1_issue();
            wg_wait<1>();
            release(prev_empty(2));
        }
        if (!g1) {
            const int ic = (q - 14) * 8 + j * 2 + z;
#pragma unroll 1
            for (int i = tid >> 3; i < 196; i += 32) {
                const int cm = 196 * ic + i, kg = cm / 56, cg = cm % 56, kb = kg >> 3, sl = cg / 14;
                int pos = cg % 14 + (kb >= 4 ? 7 : 0);
                if (pos >= 14) pos -= 14;
                const uint4 v = __ldg(reinterpret_cast<const uint4*>(wo + (size_t)(kg * 8 + (tid & 7)) * D_ + cg * 8));
                *reinterpret_cast<uint4*>(g_bimg + (kb * 4 + sl) * BLK + pos * 1024 + (kg & 7) * 128 + (tid & 7) * 16) = v;
            }
            fence_async_global();
            bar_sync<1, 256>();
            if (tid == 0) red_release(g_ctr + C_WO);
        }
        TS(warp == 0 ? 5 : 63);
        float a2[56];
        {
            const float fl = __uint_as_float((uint32_t)b2l << 16), fh = __uint_as_float((uint32_t)b2h << 16);
#pragma unroll
            for (int n = 0; n < 7; n++) {
                a2[4 * n] = bf_lo(xv[2 * n]) + fl; a2[4 * n + 1] = bf_hi(xv[2 * n]) + fl;
                a2[4 * n + 2] = bf_lo(xv[2 * n + 1]) + fh; a2[4 * n + 3] = bf_hi(xv[2 * n + 1]) + fh;
            }
#pragma unroll
            for (int i = 28; i < 56; i++) a2[i] = 0.f;
        }
        auto o_issue = [&]() {
            mbar_wait(bar + 8 * (B_FULL + st), ph);
            wg_fence();
#pragma unroll
            for (int k = 0; k < 4; k++) wgmma_m64n112k16<0, 1>(a2, dA + st * 1024 + k * 2, dU + st * 896 + k * 16, 1);
            wg_commit();
            advance();
        };
        const uint32_t peer = z ^ 1;
        o_issue();
        wg_wait<1>();
        pin(a1);
        TS(warp == 0 ? 6 : 63);
        mbar_wait_cluster(bar + 8 * B_FREE, 0);
        if (g1) {
            release(prev_empty(2));
            send_half(a1, mapa(sb + OFF_K + wg * 7168, peer), mapa(bar + 8 * (B_RECV1 + wg), peer), t);
        }
        const int n_o = 4 - z;
#pragma unroll 1
        for (int it = 1; it < n_o; it++) o_issue();
        TS(warp == 0 ? 7 : 63);
        if (g1) {
            uint32_t p[14];
            mbar_wait_cluster(bar + 8 * (B_RECV1 + wg), 0);
            TS(warp == 0 ? 8 : 63);
            recv_half(p, sb + OFF_K + wg * 7168, t);
#pragma unroll
            for (int i = 0; i < 14; i++) p[i] = pack2(gelu_tanh(a1[2 * i] + bf_lo(p[i])), gelu_tanh(a1[2 * i + 1] + bf_hi(p[i])));
            const uint32_t dst = sb + OFF_V + wg * 7168 + w4 * 256 + (lane & 15) * 16;
#pragma unroll
            for (int n = 0; n < 3; n++) stsm4(dst + (2 * n + (lane >> 4)) * 1024, p[4 * n], p[4 * n + 1], p[4 * n + 2], p[4 * n + 3]);
            stsm2(dst + 6144, p[12], p[13]);
            fence_async_smem();
            __syncwarp();
            release(bar + 8 * (B_UST + wg));
        }
        TS(warp == 0 ? 9 : 63);
        wg_wait<1>();
#pragma unroll 1
        for (int it = n_o; it >= 2; it--) release(prev_empty(it));
#pragma unroll 1
        for (int it = 0; it < 14; it++) {
            mbar_wait(bar + 8 * (B_FULL + st), ph);
            if (it == 0) TS(warp == 0 ? 10 : 63);
            wg_fence();
#pragma unroll
            for (int k = 0; k < 4; k++) wgmma_m64n112k16<1, 1>(a2, dA + st * 1024 + k * 128, dU + st * 896 + k * 16, 1);
            wg_commit();
            advance();
            wg_wait<1>();
            release(prev_empty(2));
        }
        wg_wait<0>();
        pin(a2);
        TS(warp == 0 ? 11 : 63);
        send_half(a2, mapa(sb + OFF_Q + wg * 7168, peer), mapa(bar + 8 * (B_RECV2 + wg), peer), t);
        {
            uint32_t p[14];
            mbar_wait_cluster(bar + 8 * (B_RECV2 + wg), 0);
            TS(warp == 0 ? 12 : 63);
            recv_half(p, sb + OFF_Q + wg * 7168, t);
#pragma unroll
            for (int i = 0; i < 14; i++) p[i] = pack2(a2[2 * i] + bf_lo(p[i]), a2[2 * i + 1] + bf_hi(p[i]));
            const uint32_t dst = sb + OFF_K + wg * 7168 + (w4 * 16 + (lane & 15)) * 112;
#pragma unroll
            for (int n = 0; n < 3; n++) stsm4(dst + n * 32 + (lane >> 4) * 16, p[4 * n], p[4 * n + 1], p[4 * n + 2], p[4 * n + 3]);
            stsm2(dst + 96, p[12], p[13]);
            fence_async_smem();
            bar_sync_id(2 + wg, 128);
            if (t == 0) {
                tma2d_store(&mp.out, sb + OFF_K + wg * 7168, j * 112 + z * 56, q * 128 + wg * 64);
                bulk_commit();
                bulk_wait_read();
            }
        }
        TS(warp == 0 ? 13 : 63);
    } else if (warp < 12) {
        asm volatile("setmaxnreg.dec.sync.aligned.u32 120;");
        const int hw = warp - 8;
        uint4 xr[7], wr[7];
        {
            const uint4* px = reinterpret_cast<const uint4*>(x + (size_t)(16 * b + hw * 4 + (lane & 3)) * D_) + (lane >> 2);
            const uint4* pw = reinterpret_cast<const uint4*>(wqkv + (size_t)(hw * 112 + (lane >> 1)) * (3 * D_) + 16 * (b < 84 ? b : 0)) + (lane & 1);
#pragma unroll
            for (int i = 0; i < 7; i++) xr[i] = ldg_nc(px + 8 * i);
            if (b < 84) {
#pragma unroll
                for (int i = 0; i < 7; i++) wr[i] = ldg_nc(pw + (size_t)i * 16 * (3 * D_ / 8));
            }
        }
        cta_start();
        {
            float v[56];
            float s = 0.f;
#pragma unroll
            for (int i = 0; i < 7; i++) {
                const uint32_t u[4] = {xr[i].x, xr[i].y, xr[i].z, xr[i].w};
#pragma unroll
                for (int e = 0; e < 4; e++) { v[8 * i + 2 * e] = bf_lo(u[e]); v[8 * i + 2 * e + 1] = bf_hi(u[e]); }
                s += ((v[8 * i] + v[8 * i + 1]) + (v[8 * i + 2] + v[8 * i + 3])) + ((v[8 * i + 4] + v[8 * i + 5]) + (v[8 * i + 6] + v[8 * i + 7]));
            }
            TS(hw == 0 ? 16 : 63);
            s += __shfl_xor_sync(0xffffffffu, s, 4); s += __shfl_xor_sync(0xffffffffu, s, 8); s += __shfl_xor_sync(0xffffffffu, s, 16);
            const float mean = s * (1.f / D_);
            float s1[4] = {0.f, 0.f, 0.f, 0.f}, s2[4] = {0.f, 0.f, 0.f, 0.f};
#pragma unroll
            for (int i = 0; i < 56; i++) { v[i] -= mean; s1[i & 3] += v[i]; s2[i & 3] = fmaf(v[i], v[i], s2[i & 3]); }
            float d1 = (s1[0] + s1[1]) + (s1[2] + s1[3]), d2 = (s2[0] + s2[1]) + (s2[2] + s2[3]);
#pragma unroll
            for (int o = 4; o <= 16; o <<= 1) { d1 += __shfl_xor_sync(0xffffffffu, d1, o); d2 += __shfl_xor_sync(0xffffffffu, d2, o); }
            d1 *= (1.f / D_); d2 *= (1.f / D_);
            const float r1 = rsqrtf(d2 + 1e-5f);
            const float r2 = rsqrtf((d2 - d1 * d1) * r1 * r1 + 1e-5f);
            const float sc = r1 * r2, of = -d1 * sc;
            const int rl = hw * 4 + (lane & 3);
            const uint32_t rot = b >= 64 ? 7 : 0;
#pragma unroll
            for (int i = 0; i < 7; i++) {
                const uint32_t ch = (lane >> 2) + 8 * i, sl = ch / 14;
                uint32_t pos = ch % 14 + rot;
                if (pos >= 14) pos -= 14;
                uint4 o;
                o.x = pack2(fmaf(v[8 * i], sc, of), fmaf(v[8 * i + 1], sc, of));
                o.y = pack2(fmaf(v[8 * i + 2], sc, of), fmaf(v[8 * i + 3], sc, of));
                o.z = pack2(fmaf(v[8 * i + 4], sc, of), fmaf(v[8 * i + 5], sc, of));
                o.w = pack2(fmaf(v[8 * i + 6], sc, of), fmaf(v[8 * i + 7], sc, of));
                *reinterpret_cast<uint4*>(smem + OFF_A + sl * 3584 + (rl >> 3) * 1792 + pos * 128 + (rl & 7) * 16) = o;
            }
            if (lane < 4) *reinterpret_cast<float2*>(smem + OFF_LNST + (rl & 1) * 64 + (rl >> 1) * 8) = make_float2(r1, -mean * r1);
            fence_async_smem();
            __syncwarp();
            if (lane == 0) mbar_arrive(bar + 8 * B_LNST);
            TS(hw == 0 ? 17 : 63);
        }
        if (b < 84) {
            float cs[8] = {0.f, 0.f, 0.f, 0.f, 0.f, 0.f, 0.f, 0.f};
#pragma unroll
            for (int i = 0; i < 7; i++) {
                const uint32_t u[4] = {wr[i].x, wr[i].y, wr[i].z, wr[i].w};
#pragma unroll
                for (int e = 0; e < 4; e++) { cs[2 * e] += bf_lo(u[e]); cs[2 * e + 1] += bf_hi(u[e]); }
            }
#pragma unroll
            for (int o = 2; o <= 16; o <<= 1)
#pragma unroll
                for (int e = 0; e < 8; e++) cs[e] += __shfl_xor_sync(0xffffffffu, cs[e], o);
            float* part = reinterpret_cast<float*>(smem + OFF_CSP);
            if (lane < 2) {
#pragma unroll
                for (int e = 0; e < 8; e++) part[hw * 16 + lane * 8 + e] = cs[e];
            }
            bar_sync<4, 128>();
            if (hw == 0) {
                if (lane < 16) g_cs[16 * b + lane] = (part[lane] + part[16 + lane]) + (part[32 + lane] + part[48 + lane]);
                fence_async_global();
                __syncwarp();
                if (lane == 0) red_release(g_ctr + C_CS);
            }
        }
        asm volatile("barrier.cluster.wait.aligned;" ::: "memory");
        TS(hw == 0 ? 18 : 63);
        mbar_wait(bar + 8 * B_QKV, 0);
        TS(hw == 0 ? 19 : 63);
        if (R == 0 && hw == 0) {
            for (int i = lane; i < 56; i += 32) {
                *reinterpret_cast<uint4*>(smem + OFF_K + i * 16) = make_uint4(0, 0, 0, 0);
                *reinterpret_cast<uint4*>(smem + OFF_V + i * 16) = make_uint4(0, 0, 0, 0);
            }
        }
        const int g = lane >> 2, tq = lane & 3;
        const bool up0 = 2 * tq > g, up1 = 2 * tq + 1 > g;
        const float scl = 0.18898223650461362f * 1.4426950408889634f;
#pragma unroll 1
        for (int u = 0; u < 4; u++) {
            const int bi = (u < 2) ? hw + 4 : hw, hd = u & 1;
            if (u == 2 && hw == 0) mbar_wait(bar + 8 * B_HALO, 0);
            __syncwarp();
            uint32_t q0[4], q1[4], k0[4], k1[4], k2[4];
            const uint32_t qa = sb + OFF_Q + (bi * 16 + (lane & 15)) * 112 + hd * 48 + (lane >> 4) * 16;
            const uint32_t ka = (bi * 16 + (lane & 7)) * 112 + hd * 48 + (lane >> 3) * 16;
            ldsm4(qa, q0); ldsm4(qa + 32, q1);
            ldsm4(sb + OFF_K + ka, k0); ldsm4(sb + OFF_K + ka + 896, k1); ldsm4(sb + OFF_K + ka + 1792, k2);
            if (hd == 0 && tq >= 2) { q1[2] = 0; q1[3] = 0; }
            if (hd == 1 && tq < 2) { q0[0] = 0; q0[1] = 0; }
            float s0[4] = {0.f, 0.f, 0.f, 0.f}, s1[4] = {0.f, 0.f, 0.f, 0.f}, s2[4] = {0.f, 0.f, 0.f, 0.f};
            mma16816(s0, q0[0], q0[1], q0[2], q0[3], k0[0], k0[1]);
            mma16816(s1, q0[0], q0[1], q0[2], q0[3], k1[0], k1[1]);
            mma16816(s2, q0[0], q0[1], q0[2], q0[3], k2[0], k2[1]);
            mma16816(s0, q1[0], q1[1], q1[2], q1[3], k0[2], k0[3]);
            mma16816(s1, q1[0], q1[1], q1[2], q1[3], k1[2], k1[3]);
            mma16816(s2, q1[0], q1[1], q1[2], q1[3], k2[2], k2[3]);
            ldsm4t(sb + OFF_V + ka, k0); ldsm4t(sb + OFF_V + ka + 896, k1); ldsm4t(sb + OFF_V + ka + 1792, k2);
            if (R == 0 && bi == 0) { s0[0] = -1e30f; s0[1] = -1e30f; }
            float l0 = up0 ? s0[0] : s1[0], l1 = up1 ? s0[1] : s1[1];
            float h0 = up0 ? s1[2] : s2[2], h1 = up1 ? s1[3] : s2[3];
            float ml = fmaxf(l0, l1), mh = fmaxf(h0, h1);
            ml = fmaxf(ml, __shfl_xor_sync(0xffffffffu, ml, 1)); mh = fmaxf(mh, __shfl_xor_sync(0xffffffffu, mh, 1));
            ml = fmaxf(ml, __shfl_xor_sync(0xffffffffu, ml, 2)); mh = fmaxf(mh, __shfl_xor_sync(0xffffffffu, mh, 2));
            l0 = exp2f((l0 - ml) * scl); l1 = exp2f((l1 - ml) * scl);
            h0 = exp2f((h0 - mh) * scl); h1 = exp2f((h1 - mh) * scl);
            float sl = l0 + l1, sh = h0 + h1;
            sl += __shfl_xor_sync(0xffffffffu, sl, 1); sh += __shfl_xor_sync(0xffffffffu, sh, 1);
            sl += __shfl_xor_sync(0xffffffffu, sl, 2); sh += __shfl_xor_sync(0xffffffffu, sh, 2);
            sl = __fdividef(1.f, sl); sh = __fdividef(1.f, sh);
            const uint32_t pl = pack2(l0 * sl, l1 * sl), phh = pack2(h0 * sh, h1 * sh);
            const uint32_t mk = (up0 ? 0xFFFFu : 0u) | (up1 ? 0xFFFF0000u : 0u);
            const uint32_t oa = sb + OFF_Q + (bi * 16 + g) * 112 + hd * 48 + tq * 4;
#pragma unroll
            for (int n = 0; n < 4; n++) {
                float o[4] = {0.f, 0.f, 0.f, 0.f};
                mma16816(o, pl & mk, 0u, pl & ~mk, phh & mk, k0[n], k1[n]);
                mma1688(o, 0u, phh & ~mk, k2[n]);
                const bool skip = (n == 3 && hd == 0 && tq >= 2) || (n == 0 && hd == 1 && tq < 2);
                if (!skip) {
                    asm volatile("st.shared.b32 [%0], %1;" ::"r"(oa + n * 16), "r"(pack2(o[0], o[1])) : "memory");
                    asm volatile("st.shared.b32 [%0], %1;" ::"r"(oa + n * 16 + 896), "r"(pack2(o[2], o[3])) : "memory");
                }
            }
        }
        fence_async_smem();
        bar_sync<4, 128>();
        TS(hw == 0 ? 20 : 63);
        if (hw == 2 && lane == 0) {
            tma2d_store(&mp.ost, sb + OFF_Q, z * D_ + P * 56, R * 128);
            bulk_commit();
            bulk_wait_all();
            red_release(g_ctr + C_O + R * 32);
            mbar_arrive(bar + 8 * B_FREE);
            asm volatile("mbarrier.arrive.release.cluster.shared::cluster.b64 _, [%0];" ::"r"(mapa(bar + 8 * B_FREE, z ^ 1)) : "memory");
            TS(21);
        } else if (hw < 2 && lane == 0 && g1) {
            const int ub = 2 * q + hw, zz = ub >= 14 ? 1 : 0;
            mbar_wait(bar + 8 * (B_UST + hw), 0);
            bulk_store(g_bimg + ((7 + ub) * 4 + j) * BLK + (z ^ zz) * 7168, sb + OFF_V + hw * 7168, 7168);
            bulk_commit();
            bulk_wait_all();
            red_relaxed(g_ctr + C_U + (j * 2 + zz) * 32 + (ub - 14 * zz));
            TS(22 + hw);
        }
    } else {
        asm volatile("setmaxnreg.dec.sync.aligned.u32 40;");
        if (warp == 12) {
            if (sb & 1023) __trap();
            for (int i = lane; i < B_COUNT; i += 32) {
                int cnt = 1;
                if (i < B_EMPTYQ || (i >= B_FULL && i < B_EMPTY) || i == B_FREE) cnt = 2;
                else if (i < B_LNST || i == B_QKV) cnt = 8;
                else if (i == B_LNST || i == B_UST || i == B_UST + 1) cnt = 4;
                mbar_init(bar + 8 * i, cnt);
                if (i >= B_RECV1 && i < B_UST) mbar_expect(bar + 8 * i, 7168);
            }
            asm volatile("fence.mbarrier_init.release.cluster;" ::: "memory");
        } else if (warp == 13) {
            if (lane < 7) asm volatile("prefetch.tensormap [%0];" ::"l"(reinterpret_cast<const CUtensorMap*>(&mp) + lane) : "memory");
        }
        __syncwarp();
        cta_start();
        const int n_g1 = g1 ? 16 : 0, n_o = 4 - z, n_all = n_g1 + n_o + 14;
        if (warp == 12) {
            if (lane == 0) {
#pragma unroll 1
                for (int kb = 0; kb < 7; kb++) {
                    if (kb >= 5) mbar_wait(bar + 8 * (B_EMPTYQ + kb - 5), 0);
                    const uint32_t xs = (0x5432154u >> (4 * kb)) & 7;
                    mbar_expect(bar + 8 * (B_FULLQ + kb), 16384);
                    tma2d(sb + OFF_A + xs * 16384, &mp.x, z * D_ + kb * 64, R * 128, bar + 8 * (B_FULLQ + kb));
                }
                mbar_wait(bar + 8 * B_EP, 0);
                const unsigned e1 = *reinterpret_cast<volatile unsigned*>(smem + OFF_EP);
                uint32_t st = 0, ph = 1;
#pragma unroll 1
                for (int r = 0; r < n_all; r++) {
                    if (r == n_g1) { poll(g_ctr + C_O + R * 32, e1 * 16); asm volatile("fence.acq_rel.gpu;" ::: "memory"); fence_async_global(); TS(32); }
                    if (r < 6) mbar_wait(bar + 8 * (r == 0 ? B_LNFREE : B_EMPTYQ + r + 1), 0);
                    else mbar_wait(bar + 8 * (B_EMPTY + st), ph);
                    const uint32_t fb = bar + 8 * (B_FULL + st), dst = sb + OFF_A + st * 16384;
                    mbar_expect(fb, 16384);
                    if (r < n_g1) tma3d(dst, &mp.w1, 0, z * 1024 + r * 64, 2 * q, fb);
                    else if (r < n_g1 + n_o) tma2d(dst, &mp.old_, (4 * z + r - n_g1) * 64, q * 128, fb);
                    else tma3d(dst, &mp.w2, 0, (14 * z + r - n_g1 - n_o) * 64, 2 * q, fb);
                    if (++st == 6) { st = 0; ph ^= 1; }
                }
            }
        } else if (warp == 13) {
            if (lane == 0) {
#pragma unroll 1
                for (int kb = 0; kb < 7; kb++) {
                    if (kb >= 5) mbar_wait(bar + 8 * (B_EMPTYQ + kb - 5), 0);
                    const uint32_t ws = (0x3421034u >> (4 * kb)) & 7;
                    mbar_expect(bar + 8 * (B_FULLQ + kb), 21504);
                    tma3d(sb + OFF_B + ws * 24576, &mp.wqkv, P * 56, kb * 64, 0, bar + 8 * (B_FULLQ + kb));
                }
            }
            mbar_wait(bar + 8 * B_EP, 0);
            const unsigned e1 = *reinterpret_cast<volatile unsigned*>(smem + OFF_EP);
            uint32_t st = 0, ph = 1, ready = 0;
            const unsigned* uf = g_ctr + C_U + (j * 2 + z) * 32 + (lane < 14 ? lane : 0);
#pragma unroll 1
            for (int r = 0; r < n_all; r++) {
                const int ui = r - n_g1 - n_o;
                if (r == 0 && g1) { poll(g_ctr + C_LN, e1 * 128); fence_async_global(); TS(33); }
                if (r == n_g1) { poll(g_ctr + C_WO, e1 * 16); asm volatile("fence.acq_rel.gpu;" ::: "memory"); fence_async_global(); }
                if (r < 6) mbar_wait(bar + 8 * (B_EMPTYQ + ((0x644332u >> (4 * r)) & 7)), 0);
                else mbar_wait(bar + 8 * (B_EMPTY + st), ph);
                if (ui >= 0) {
                    int n = 0;
                    while (!((ready >> ui) & 1)) {
                        ready = __ballot_sync(0xffffffffu, ctr_done(ld_relaxed(uf), e1 * 2));
                        if (++n > (1 << 21)) __trap();
                    }
                    if (n) fence_async_global();
                    if (ui == 0) TS(34);
                }
                if (lane == 0) {
                    const uint8_t* src = r < n_g1 ? g_himg + ((16 * z + r) * 4 + j) * BLK
                                       : (ui < 0 ? g_bimg + ((4 * z + r - n_g1) * 4 + j) * BLK : g_bimg + ((7 + 14 * z + ui) * 4 + j) * BLK);
                    const uint32_t fb = bar + 8 * (B_FULL + st);
                    mbar_expect(fb, BLK);
                    bulk_load(sb + OFF_B + st * BLK, src, BLK, fb);
                }
                __syncwarp();
                if (++st == 6) { st = 0; ph ^= 1; }
            }
        } else if (warp == 14) {
            if (lane == 0) {
                const unsigned v0 = ld_relaxed(g_ctr + C_LN);
                const int r1 = (b >> 6) * 1024 + (b & 63), r2 = (b >> 6) * 896 + (b & 63);
#pragma unroll 1
                for (int i = 0; i < 16; i++) l2_prefetch(w1 + (size_t)(r1 + 64 * i) * F_, F_ * 2);
                const unsigned e1 = (v0 >> 7) + 1;
                *reinterpret_cast<volatile unsigned*>(smem + OFF_EP) = e1;
                mbar_arrive(bar + 8 * B_EP);
                TS(36);
                mbar_wait(bar + 8 * B_LNST, 0);
#pragma unroll 1
                for (int s = 0; s < 4; s++) bulk_store(g_himg + ((b >> 2) * 4 + s) * BLK + (b & 3) * 3584, sb + OFF_A + s * 3584, 3584);
                bulk_store(g_stats + 8 * b, sb + OFF_LNST, 64);
                bulk_store(g_stats + 1024 + 8 * b, sb + OFF_LNST + 64, 64);
                bulk_commit();
                bulk_wait_all();
                red_relaxed(g_ctr + C_LN);
                mbar_arrive(bar + 8 * B_LNFREE);
                TS(37);
                l2_prefetch(reinterpret_cast<const uint8_t*>(wo) + b * 3136, 3136);
#pragma unroll 1
                for (int i = 0; i < 14; i++) l2_prefetch(w2 + (size_t)(r2 + 64 * i) * S_, S_ * 2);
                poll(g_ctr + C_LN, e1 * 128);
                poll(g_ctr + C_CS, e1 * 84);
                asm volatile("fence.acq_rel.gpu;" ::: "memory");
                fence_async_global();
                mbar_expect(bar + 8 * B_AUX, 1024 + 672);
                bulk_load(sb + OFF_STATS, g_stats + z * 1024 + R * 128, 1024, bar + 8 * B_AUX);
#pragma unroll 1
                for (int s = 0; s < 3; s++) bulk_load(sb + OFF_CS + s * 224, g_cs + s * D_ + P * 56, 224, bar + 8 * B_AUX);
                TS(38);
            }
        } else {
            if (lane == 0) {
                mbar_wait(bar + 8 * B_EP, 0);
                const unsigned e1 = *reinterpret_cast<volatile unsigned*>(smem + OFF_EP);
                const int me = (R * 8 + P) * 2 + z;
                mbar_wait(bar + 8 * B_QKV, 0);
                if (R < 7) {
                    bulk_store(g_halo + me * 1792, sb + OFF_K + 128 * 112, 896);
                    bulk_store(g_halo + me * 1792 + 896, sb + OFF_V + 128 * 112, 896);
                    bulk_commit();
                    bulk_wait_all();
                    red_relaxed(g_ctr + C_HALO + me * 8);
                }
                if (R > 0) {
                    poll(g_ctr + C_HALO + (me - 16) * 8, e1);
                    fence_async_global();
                    mbar_expect(bar + 8 * B_HALO, 1792);
                    bulk_load(sb + OFF_K, g_halo + (me - 16) * 1792, 896, bar + 8 * B_HALO);
                    bulk_load(sb + OFF_V, g_halo + (me - 16) * 1792 + 896, 896, bar + 8 * B_HALO);
                } else {
                    mbar_arrive(bar + 8 * B_HALO);
                }
                TS(40);
            }
        }
    }
}

typedef CUresult (*EncodeFn)(CUtensorMap*, CUtensorMapDataType, cuuint32_t, void*, const cuuint64_t*, const cuuint64_t*, const cuuint32_t*,
                             const cuuint32_t*, CUtensorMapInterleave, CUtensorMapSwizzle, CUtensorMapL2promotion, CUtensorMapFloatOOBfill);

void encode(EncodeFn fn, CUtensorMap* m, const void* p, int rank, const cuuint64_t* dims, const cuuint64_t* strides, const cuuint32_t* box, bool swz) {
    const cuuint32_t es[3] = {1, 1, 1};
    fn(m, CU_TENSOR_MAP_DATA_TYPE_BFLOAT16, rank, const_cast<void*>(p), dims, strides, box, es, CU_TENSOR_MAP_INTERLEAVE_NONE,
       swz ? CU_TENSOR_MAP_SWIZZLE_128B : CU_TENSOR_MAP_SWIZZLE_NONE, CU_TENSOR_MAP_L2_PROMOTION_L2_128B, CU_TENSOR_MAP_FLOAT_OOB_FILL_NONE);
}

}

extern "C" void kernel_launch(void* const* d_in, const int* in_sizes, int n_in, void* d_out, int out_size) {
    const __nv_bfloat16* x = (const __nv_bfloat16*)d_in[0];
    const __nv_bfloat16* wqkv = (const __nv_bfloat16*)d_in[1];
    const __nv_bfloat16* wo = (const __nv_bfloat16*)d_in[2];
    const __nv_bfloat16* w1 = (const __nv_bfloat16*)d_in[4];
    const __nv_bfloat16* b1 = (const __nv_bfloat16*)d_in[5];
    const __nv_bfloat16* w2 = (const __nv_bfloat16*)d_in[6];
    const __nv_bfloat16* b2 = (const __nv_bfloat16*)d_in[7];

    void* fp = nullptr;
    cudaDriverEntryPointQueryResult qr;
    cudaGetDriverEntryPoint("cuTensorMapEncodeTiled", &fp, cudaEnableDefault, &qr);
    EncodeFn fn = (EncodeFn)fp;
    void* o = nullptr;
    cudaGetSymbolAddress(&o, g_o);

    Maps mp;
    { cuuint64_t d[2] = {896, 1024}, s[1] = {1792}; cuuint32_t bx[2] = {64, 128}; encode(fn, &mp.x, x, 2, d, s, bx, true); }
    { cuuint64_t d[3] = {448, 448, 3}, s[2] = {2688, 896}; cuuint32_t bx[3] = {56, 64, 3}; encode(fn, &mp.wqkv, wqkv, 3, d, s, bx, true); }
    { cuuint64_t d[3] = {64, 2048, 28}, s[2] = {3584, 128}; cuuint32_t bx[3] = {64, 64, 2}; encode(fn, &mp.w1, w1, 3, d, s, bx, true); }
    { cuuint64_t d[3] = {64, 1792, 32}, s[2] = {4096, 128}; cuuint32_t bx[3] = {64, 64, 2}; encode(fn, &mp.w2, w2, 3, d, s, bx, true); }
    { cuuint64_t d[2] = {448, 2048}, s[1] = {896}; cuuint32_t bx[2] = {64, 128}; encode(fn, &mp.old_, o, 2, d, s, bx, true); }
    { cuuint64_t d[2] = {896, 1024}, s[1] = {1792}; cuuint32_t bx[2] = {56, 128}; encode(fn, &mp.ost, o, 2, d, s, bx, false); }
    { cuuint64_t d[2] = {448, 2048}, s[1] = {896}; cuuint32_t bx[2] = {56, 64}; encode(fn, &mp.out, d_out, 2, d, s, bx, false); }

    cudaFuncSetAttribute(fused_kernel, cudaFuncAttributeMaxDynamicSharedMemorySize, SMEM_BYTES);
    fused_kernel<<<128, 512, SMEM_BYTES>>>(mp, x, wqkv, wo, w1, b1, w2, b2);
}
```

```cpp
#include <cuda_runtime.h>
#include <cuda.h>
#include <cuda_bf16.h>
#include <stdint.h>

namespace {

constexpr int S_ = 2048, D_ = 448, F_ = 1792;
constexpr uint32_t BLK = 14336;

__device__ __align__(1024) uint8_t g_himg[32 * 4 * BLK];
__device__ __align__(1024) uint8_t g_bimg[36 * 4 * BLK];
__device__ __align__(1024) uint8_t g_ident[2 * BLK];
__device__ __align__(1024) __nv_bfloat16 g_o[8 * S_ * 64];
__device__ __align__(128) float2 g_stats[S_];
__device__ __align__(128) float g_cs[8 * 4 * 168];
__device__ __align__(128) uint8_t g_halo[128 * 2 * 896];
__device__ __align__(128) unsigned g_ctr[2336];

constexpr int C_LN = 0, C_WO = 256, C_O = 288, C_U = 800, C_HALO = 1312;

#define TSX(sel, id)
#define TS(id)
#define TS0(id)
#define TSH(id)
#define TG(id)

#define POLL_NS 200
#define QDEPTH 3
#define MC0 1
#define PF1 16
#define PF2 14
constexpr uint32_t OFF_A = 0;
constexpr uint32_t OFF_B = 98304;
constexpr uint32_t OFF_Q = 184320, OFF_K = 198656, OFF_V = 213888;
constexpr uint32_t OFF_OST = OFF_Q, OFF_RECV2 = OFF_Q, OFF_RECV1 = OFF_Q + 16384, OFF_UST = OFF_Q + 30720, OFF_OUT = OFF_Q + 16384;
constexpr uint32_t OFF_STATS = 221184, OFF_CSIN = OFF_STATS + 2048, OFF_CSP = OFF_CSIN + 2688, OFF_LNST = OFF_CSP + 1792, OFF_CSOUT = OFF_LNST + 128;
constexpr uint32_t OFF_CS = 229376;
constexpr uint32_t OFF_EP = OFF_CS + 672;
constexpr uint32_t OFF_BAR = OFF_EP + 16;
constexpr uint32_t OFF_TS = OFF_BAR + 8 * 48;
constexpr uint32_t SMEM_BYTES = OFF_TS;

enum : int {
    B_FULLQ = 0, B_EMPTYQ = 7, B_FULL = 14, B_EMPTY = 20, B_AUX = 26, B_QKV = 27, B_HALO = 28, B_FREE = 29,
    B_RECV1 = 30, B_RECV2 = 32, B_UST = 34, B_EP = 36, B_OST = 37, B_LNST = 38, B_CSP = 39, B_LNFREE = 40, B_LN = 41,
    B_AUXL = 42, B_UDONE = 43, B_COUNT = 44
};
constexpr uint32_t XSLOT = 0x5432154u;
constexpr uint32_t WSLOT = 0x3421034u;
#define ATT_STEP 8

__device__ __forceinline__ uint32_t smem_u32(const void* p) { return (uint32_t)__cvta_generic_to_shared(p); }
__device__ __forceinline__ void mbar_init(uint32_t a, int c) { asm volatile("mbarrier.init.shared::cta.b64 [%0], %1;" ::"r"(a), "r"(c) : "memory"); }
__device__ __forceinline__ void mbar_expect(uint32_t a, uint32_t b) { asm volatile("mbarrier.arrive.expect_tx.shared::cta.b64 _, [%0], %1;" ::"r"(a), "r"(b) : "memory"); }
__device__ __forceinline__ void mbar_arrive(uint32_t a) { asm volatile("mbarrier.arrive.shared::cta.b64 _, [%0];" ::"r"(a) : "memory"); }
__device__ __forceinline__ void mbar_arrive_if0(uint32_t a, uint32_t sel) {
    asm volatile("{\n.reg .pred p;\nsetp.eq.u32 p, %1, 0;\n@p mbarrier.arrive.shared::cta.b64 _, [%0];\n}" ::"r"(a), "r"(sel) : "memory");
}
__device__ __forceinline__ void mbar_wait(uint32_t a, uint32_t parity) {
    asm volatile(
        "{\n.reg .pred p;\n.reg .u32 n;\nmov.u32 n, 0;\n"
        "W0:\nmbarrier.try_wait.parity.shared::cta.b64 p, [%0], %1;\n@p bra W1;\n"
        "add.u32 n, n, 1;\nsetp.lt.u32 p, n, 4194304;\n@p bra W0;\ntrap;\nW1:\n}\n" ::"r"(a), "r"(parity) : "memory");
}
__device__ __forceinline__ void mbar_wait_cluster(uint32_t a, uint32_t parity) {
    asm volatile(
        "{\n.reg .pred p;\n.reg .u32 n;\nmov.u32 n, 0;\n"
        "W0:\nmbarrier.try_wait.parity.acquire.cluster.shared::cta.b64 p, [%0], %1;\n@p bra W1;\n"
        "add.u32 n, n, 1;\nsetp.lt.u32 p, n, 4194304;\n@p bra W0;\ntrap;\nW1:\n}\n" ::"r"(a), "r"(parity) : "memory");
}
__device__ __forceinline__ uint32_t mapa(uint32_t a, uint32_t cta) { uint32_t r; asm("mapa.shared::cluster.u32 %0, %1, %2;" : "=r"(r) : "r"(a), "r"(cta)); return r; }
__device__ __forceinline__ void tma2d(uint32_t dst, const CUtensorMap* m, int c0, int c1, uint32_t bar) {
    asm volatile("cp.async.bulk.tensor.2d.shared::cluster.global.mbarrier::complete_tx::bytes [%0], [%1, {%3, %4}], [%2];" ::"r"(dst), "l"(m), "r"(bar), "r"(c0), "r"(c1) : "memory");
}
__device__ __forceinline__ void tma3d(uint32_t dst, const CUtensorMap* m, int c0, int c1, int c2, uint32_t bar) {
    asm volatile("cp.async.bulk.tensor.3d.shared::cluster.global.mbarrier::complete_tx::bytes [%0], [%1, {%3, %4, %5}], [%2];" ::"r"(dst), "l"(m), "r"(bar), "r"(c0), "r"(c1), "r"(c2) : "memory");
}
__device__ __forceinline__ void tma3d_mc(uint32_t dst, const CUtensorMap* m, int c0, int c1, int c2, uint32_t bar) {
    asm volatile("cp.async.bulk.tensor.3d.shared::cluster.global.mbarrier::complete_tx::bytes.multicast::cluster [%0], [%1, {%3, %4, %5}], [%2], %6;"
                 ::"r"(dst), "l"(m), "r"(bar), "r"(c0), "r"(c1), "r"(c2), "h"((uint16_t)3) : "memory");
}
__device__ __forceinline__ void tma2d_store(const CUtensorMap* m, uint32_t src, int c0, int c1) {
    asm volatile("cp.async.bulk.tensor.2d.global.shared::cta.bulk_group [%0, {%2, %3}], [%1];" ::"l"(m), "r"(src), "r"(c0), "r"(c1) : "memory");
}
__device__ __forceinline__ void tma4d_store(const CUtensorMap* m, uint32_t src, int c0, int c1, int c2, int c3) {
    asm volatile("cp.async.bulk.tensor.4d.global.shared::cta.bulk_group [%0, {%2, %3, %4, %5}], [%1];" ::"l"(m), "r"(src), "r"(c0), "r"(c1), "r"(c2), "r"(c3) : "memory");
}
__device__ __forceinline__ void bulk_load(uint32_t dst, const void* src, uint32_t bytes, uint32_t bar) {
    asm volatile("cp.async.bulk.shared::cluster.global.mbarrier::complete_tx::bytes [%0], [%1], %2, [%3];" ::"r"(dst), "l"(src), "r"(bytes), "r"(bar) : "memory");
}
__device__ __forceinline__ void bulk_store(void* dst, uint32_t src, uint32_t bytes) {
    asm volatile("cp.async.bulk.global.shared::cta.bulk_group [%0], [%1], %2;" ::"l"(dst), "r"(src), "r"(bytes) : "memory");
}
__device__ __forceinline__ void bulk_commit() { asm volatile("cp.async.bulk.commit_group;" ::: "memory"); }
__device__ __forceinline__ void bulk_wait_all() { asm volatile("cp.async.bulk.wait_group 0;" ::: "memory"); }
__device__ __forceinline__ void bulk_wait_read() { asm volatile("cp.async.bulk.wait_group.read 0;" ::: "memory"); }
__device__ __forceinline__ void l2_prefetch(const void* p) { asm volatile("prefetch.global.L2 [%0];" ::"l"(p)); }
__device__ __forceinline__ void fence_async_smem() { asm volatile("fence.proxy.async.shared::cta;" ::: "memory"); }
__device__ __forceinline__ void fence_async_global() { asm volatile("fence.proxy.async.global;" ::: "memory"); }
__device__ __forceinline__ void red_relaxed(unsigned* p) { asm volatile("red.relaxed.gpu.global.add.u32 [%0], 1;" ::"l"(p) : "memory"); }
__device__ __forceinline__ void red_release(unsigned* p) { asm volatile("red.release.gpu.global.add.u32 [%0], 1;" ::"l"(p) : "memory"); }
__device__ __forceinline__ unsigned ld_relaxed(const unsigned* p) { unsigned v; asm volatile("ld.relaxed.gpu.global.u32 %0, [%1];" : "=r"(v) : "l"(p) : "memory"); return v; }
__device__ __forceinline__ bool ctr_done(unsigned v, unsigned target) { return ((v - target) & 0x1FFFFFFu) == 0; }
__device__ __forceinline__ void poll(const unsigned* p, unsigned target) {
    int n = 0;
    while (!ctr_done(ld_relaxed(p), target)) { if (++n > (1 << 21)) __trap(); }
}
__device__ __forceinline__ void poll_slow(const unsigned* p, unsigned target) {
    int n = 0;
    while (!ctr_done(ld_relaxed(p), target)) { __nanosleep(POLL_NS); if (++n > (1 << 21)) __trap(); }
}
template <int ID, int N> __device__ __forceinline__ void bar_sync() { asm volatile("bar.sync %0, %1;" ::"n"(ID), "n"(N) : "memory"); }
__device__ __forceinline__ void bar_sync_id(int id, int n) { asm volatile("bar.sync %0, %1;" ::"r"(id), "r"(n) : "memory"); }
__device__ __forceinline__ void sched_fence(uint32_t never_zero) {
    asm volatile("{\n.reg .pred p;\nF0:\nsetp.eq.u32 p, %0, 0;\n@p bra F0;\n}\n" ::"r"(never_zero) : "memory");
}
__device__ __forceinline__ void wg_fence() { asm volatile("wgmma.fence.sync.aligned;" ::: "memory"); }
__device__ __forceinline__ void wg_commit() { asm volatile("wgmma.commit_group.sync.aligned;" ::: "memory"); }
template <int N> __device__ __forceinline__ void wg_wait() { asm volatile("wgmma.wait_group.sync.aligned %0;" ::"n"(N) : "memory"); }
template <int N> __device__ __forceinline__ void pin(float (&a)[N]) {
#pragma unroll
    for (int i = 0; i < N; i++) asm volatile("" : "+f"(a[i])::"memory");
}
__device__ __forceinline__ uint4 ldg_nc(const uint4* p) {
    uint4 v;
    asm volatile("ld.volatile.global.v4.u32 {%0,%1,%2,%3}, [%4];" : "=r"(v.x), "=r"(v.y), "=r"(v.z), "=r"(v.w) : "l"(p) : "memory");
    return v;
}
__device__ __forceinline__ uint32_t pack2(float lo, float hi) { uint32_t r; asm("cvt.rn.bf16x2.f32 %0, %1, %2;" : "=r"(r) : "f"(hi), "f"(lo)); return r; }
__device__ __forceinline__ float bf_lo(uint32_t v) { return __uint_as_float(v << 16); }
__device__ __forceinline__ float bf_hi(uint32_t v) { return __uint_as_float(v & 0xFFFF0000u); }
__device__ __forceinline__ void stsm4(uint32_t a, uint32_t r0, uint32_t r1, uint32_t r2, uint32_t r3) {
    asm volatile("stmatrix.sync.aligned.m8n8.x4.shared.b16 [%0], {%1, %2, %3, %4};" ::"r"(a), "r"(r0), "r"(r1), "r"(r2), "r"(r3) : "memory");
}
__device__ __forceinline__ void stsm2(uint32_t a, uint32_t r0, uint32_t r1) {
    asm volatile("stmatrix.sync.aligned.m8n8.x2.shared.b16 [%0], {%1, %2};" ::"r"(a), "r"(r0), "r"(r1) : "memory");
}
__device__ __forceinline__ void ldsm4(uint32_t a, uint32_t (&r)[4]) {
    asm volatile("ldmatrix.sync.aligned.m8n8.x4.shared.b16 {%0, %1, %2, %3}, [%4];" : "=r"(r[0]), "=r"(r[1]), "=r"(r[2]), "=r"(r[3]) : "r"(a) : "memory");
}
__device__ __forceinline__ void ldsm4t(uint32_t a, uint32_t (&r)[4]) {
    asm volatile("ldmatrix.sync.aligned.m8n8.x4.trans.shared.b16 {%0, %1, %2, %3}, [%4];" : "=r"(r[0]), "=r"(r[1]), "=r"(r[2]), "=r"(r[3]) : "r"(a) : "memory");
}
__device__ __forceinline__ void mma16816(float (&c)[4], uint32_t a0, uint32_t a1, uint32_t a2, uint32_t a3, uint32_t b0, uint32_t b1) {
    asm volatile("mma.sync.aligned.m16n8k16.row.col.f32.bf16.bf16.f32 {%0,%1,%2,%3}, {%4,%5,%6,%7}, {%8,%9}, {%0,%1,%2,%3};"
                 : "+f"(c[0]), "+f"(c[1]), "+f"(c[2]), "+f"(c[3]) : "r"(a0), "r"(a1), "r"(a2), "r"(a3), "r"(b0), "r"(b1));
}
__device__ __forceinline__ void mma1688(float (&c)[4], uint32_t a0, uint32_t a1, uint32_t b0) {
    asm volatile("mma.sync.aligned.m16n8k8.row.col.f32.bf16.bf16.f32 {%0,%1,%2,%3}, {%4,%5}, {%6}, {%0,%1,%2,%3};"
                 : "+f"(c[0]), "+f"(c[1]), "+f"(c[2]), "+f"(c[3]) : "r"(a0), "r"(a1), "r"(b0));
}
__device__ __forceinline__ uint64_t mkdesc(uint32_t addr, uint32_t lbo, uint32_t sbo, uint32_t sw) {
    uint32_t lo = ((addr & 0x3FFFF) >> 4) | ((lbo >> 4) << 16), hi = (sbo >> 4) | (sw << 30);
    return ((uint64_t)hi << 32) | lo;
}
__device__ __forceinline__ float ex2(float x) { float r; asm("ex2.approx.ftz.f32 %0, %1;" : "=f"(r) : "f"(x)); return r; }
__device__ __forceinline__ float rcp(float x) { float r; asm("rcp.approx.ftz.f32 %0, %1;" : "=f"(r) : "f"(x)); return r; }
__device__ __forceinline__ float gelu_tanh(float x) {
    float y = x * fmaf(x * x, 0.0356774081363f, 0.7978845608029f), t;
    asm("tanh.approx.f32 %0, %1;" : "=f"(t) : "f"(y));
    float hx = 0.5f * x;
    return fmaf(hx, t, hx);
}

template <int TB>
__device__ __forceinline__ void wgmma_m64n56k16_rs(float (&d)[28], uint32_t a0, uint32_t a1, uint32_t a2, uint32_t a3, uint64_t db, int scale_d) {
    asm volatile("{\n.reg .pred p;\nsetp.ne.b32 p, %33, 0;\n"
        "wgmma.mma_async.sync.aligned.m64n56k16.f32.bf16.bf16 "
        "{%0, %1, %2, %3, %4, %5, %6, %7, %8, %9, %10, %11, %12, %13, %14, %15, %16, %17, %18, %19, %20, %21, %22, %23, %24, %25, %26, %27}, "
        "{%28, %29, %30, %31}, %32, p, 1, 1, %34;\n}\n"
        : "+f"(d[0]), "+f"(d[1]), "+f"(d[2]), "+f"(d[3]), "+f"(d[4]), "+f"(d[5]), "+f"(d[6]), "+f"(d[7]), "+f"(d[8]), "+f"(d[9]), "+f"(d[10]), "+f"(d[11]), "+f"(d[12]), "+f"(d[13]), "+f"(d[14]), "+f"(d[15]), "+f"(d[16]), "+f"(d[17]), "+f"(d[18]), "+f"(d[19]), "+f"(d[20]), "+f"(d[21]), "+f"(d[22]), "+f"(d[23]), "+f"(d[24]), "+f"(d[25]), "+f"(d[26]), "+f"(d[27])
        : "r"(a0), "r"(a1), "r"(a2), "r"(a3), "l"(db), "r"(scale_d), "n"(TB));
}
template <int TA, int TB>
__device__ __forceinline__ void wgmma_m64n112k16(float (&d)[56], uint64_t da, uint64_t db, int scale_d) {
    asm volatile("{\n.reg .pred p;\nsetp.ne.b32 p, %58, 0;\n"
        "wgmma.mma_async.sync.aligned.m64n112k16.f32.bf16.bf16 "
        "{%0, %1, %2, %3, %4, %5, %6, %7, %8, %9, %10, %11, %12, %13, %14, %15, %16, %17, %18, %19, %20, %21, %22, %23, %24, %25, %26, %27, %28, %29, %30, %31, %32, %33, %34, %35, %36, %37, %38, %39, %40, %41, %42, %43, %44, %45, %46, %47, %48, %49, %50, %51, %52, %53, %54, %55}, "
        "%56, %57, p, 1, 1, %59, %60;\n}\n"
        : "+f"(d[0]), "+f"(d[1]), "+f"(d[2]), "+f"(d[3]), "+f"(d[4]), "+f"(d[5]), "+f"(d[6]), "+f"(d[7]), "+f"(d[8]), "+f"(d[9]), "+f"(d[10]), "+f"(d[11]), "+f"(d[12]), "+f"(d[13]), "+f"(d[14]), "+f"(d[15]), "+f"(d[16]), "+f"(d[17]), "+f"(d[18]), "+f"(d[19]), "+f"(d[20]), "+f"(d[21]), "+f"(d[22]), "+f"(d[23]), "+f"(d[24]), "+f"(d[25]), "+f"(d[26]), "+f"(d[27]), "+f"(d[28]), "+f"(d[29]), "+f"(d[30]), "+f"(d[31]), "+f"(d[32]), "+f"(d[33]), "+f"(d[34]), "+f"(d[35]), "+f"(d[36]), "+f"(d[37]), "+f"(d[38]), "+f"(d[39]), "+f"(d[40]), "+f"(d[41]), "+f"(d[42]), "+f"(d[43]), "+f"(d[44]), "+f"(d[45]), "+f"(d[46]), "+f"(d[47]), "+f"(d[48]), "+f"(d[49]), "+f"(d[50]), "+f"(d[51]), "+f"(d[52]), "+f"(d[53]), "+f"(d[54]), "+f"(d[55])
        : "l"(da), "l"(db), "r"(scale_d), "n"(TA), "n"(TB));
}

__device__ __forceinline__ void send_half(const float (&a)[56], uint32_t rbuf, uint32_t rbar, int t) {
    uint32_t p[14];
#pragma unroll
    for (int i = 0; i < 14; i++) p[i] = pack2(a[28 + 2 * i], a[29 + 2 * i]);
#pragma unroll
    for (int i = 0; i < 3; i++)
        asm volatile("st.async.weak.shared::cluster.mbarrier::complete_tx::bytes.v4.b32 [%0], {%1,%2,%3,%4}, [%5];" ::"r"(rbuf + i * 2048 + t * 16),
                     "r"(p[4 * i]), "r"(p[4 * i + 1]), "r"(p[4 * i + 2]), "r"(p[4 * i + 3]), "r"(rbar) : "memory");
    asm volatile("st.async.weak.shared::cluster.mbarrier::complete_tx::bytes.v2.b32 [%0], {%1,%2}, [%3];" ::"r"(rbuf + 6144 + t * 8), "r"(p[12]), "r"(p[13]), "r"(rbar) : "memory");
}
__device__ __forceinline__ void recv_half(uint32_t (&p)[14], uint32_t buf, int t) {
#pragma unroll
    for (int i = 0; i < 3; i++)
        asm volatile("ld.shared.v4.b32 {%0,%1,%2,%3}, [%4];" : "=r"(p[4 * i]), "=r"(p[4 * i + 1]), "=r"(p[4 * i + 2]), "=r"(p[4 * i + 3]) : "r"(buf + i * 2048 + t * 16) : "memory");
    asm volatile("ld.shared.v2.b32 {%0,%1}, [%2];" : "=r"(p[12]), "=r"(p[13]) : "r"(buf + 6144 + t * 8) : "memory");
}

struct Maps { CUtensorMap x, wqkv, hst, w1, w2, xn, old_, ost, out[2]; };

__global__ void __cluster_dims__(2, 1, 1) __launch_bounds__(512, 1)
fused_kernel(const __grid_constant__ Maps mp, const __nv_bfloat16* __restrict__ x, const __nv_bfloat16* __restrict__ wqkv,
             const __nv_bfloat16* __restrict__ wo, const __nv_bfloat16* __restrict__ w1, const __nv_bfloat16* __restrict__ b1,
             const __nv_bfloat16* __restrict__ w2, const __nv_bfloat16* __restrict__ b2) {
    extern __shared__ __align__(1024) uint8_t smem[];
    const uint32_t sb = smem_u32(smem);
    const uint32_t bar = sb + OFF_BAR;
    const int tid = threadIdx.x, lane = tid & 31;
    const int b = blockIdx.x, z = b & 1, c = b >> 1;
    if (tid < 112) l2_prefetch(reinterpret_cast<const uint8_t*>(x) + (b * 112 + tid) * 128);
    else if (tid < 112 + 74) l2_prefetch(reinterpret_cast<const uint8_t*>(wqkv) + min(b + (tid - 112) * 128, 9407) * 128);
    const int warp = __shfl_sync(0xffffffffu, tid >> 5, 0);
    int q, j;
    if (c < 4) { q = 15; j = c; } else if (c < 36) { q = (c - 4) & 7; j = (c - 4) >> 3; } else { q = 8 + (c - 36) % 7; j = (c - 36) / 7; }
    const bool g1 = q < 14;
    const int R = q >> 1, P = (q & 1) * 4 + j;

    TS0(0);
    TG(60);
    auto qkv_load = [&](int kb) {
        mbar_expect(bar + 8 * (B_FULLQ + kb), 40960);
        const uint32_t wd = sb + OFF_B + ((WSLOT >> (4 * kb)) & 7) * 24576;
        if (kb < MC0) tma3d(wd, &mp.wqkv, (P * 56) & ~15, kb * 64, 0, bar + 8 * (B_FULLQ + kb));
        else if ((kb & 1) == z) tma3d_mc(wd, &mp.wqkv, (P * 56) & ~15, kb * 64, 0, bar + 8 * (B_FULLQ + kb));
        tma2d(sb + OFF_A + ((XSLOT >> (4 * kb)) & 7) * 16384, &mp.x, z * D_ + kb * 64, R * 128, bar + 8 * (B_FULLQ + kb));
    };
    if (tid == 384) {
        mbar_init(bar + 8 * B_FULLQ, 1);
        qkv_load(0);
        TS(49);
    }
    auto slot = [](uint32_t r) { return r - 6 * ((r * 43) >> 8); };
    auto phase = [](uint32_t r) { return ((r * 43) >> 8) & 1; };
    const uint32_t r_o = g1 ? 16 : 0, r_u = r_o + 5;

    if (warp < 8) {
        const int wg = warp >> 2, w4 = warp & 3, t = tid & 127, g = lane >> 2, tq = lane & 3;
        asm volatile("barrier.cluster.arrive.relaxed.aligned;" ::: "memory");
        if (wg == 1) bar_sync<10, 256>();
        if (b < 96 && wg == 1) {
            const uint4* pw = reinterpret_cast<const uint4*>(wqkv + (size_t)((b / 24) * 112 + w4 * 28 + (lane >> 3)) * (3 * D_) + (b % 24) * 56) + min(lane & 7, 6);
            uint4 wr[7];
#pragma unroll
            for (int i = 0; i < 7; i++) wr[i] = ldg_nc(pw + (size_t)i * 4 * (3 * D_ / 8));
            float cs[8] = {0.f, 0.f, 0.f, 0.f, 0.f, 0.f, 0.f, 0.f};
#pragma unroll
            for (int i = 0; i < 7; i++) {
                const uint32_t u[4] = {wr[i].x, wr[i].y, wr[i].z, wr[i].w};
#pragma unroll
                for (int e = 0; e < 4; e++) { cs[2 * e] += bf_lo(u[e]); cs[2 * e + 1] += bf_hi(u[e]); }
            }
#pragma unroll
            for (int o = 8; o <= 16; o <<= 1)
#pragma unroll
                for (int e = 0; e < 8; e++) cs[e] += __shfl_xor_sync(0xffffffffu, cs[e], o);
            if (lane < 7) {
                float4* part = reinterpret_cast<float4*>(smem + OFF_CSP + w4 * 224 + lane * 32);
                part[0] = make_float4(cs[0], cs[1], cs[2], cs[3]);
                part[1] = make_float4(cs[4], cs[5], cs[6], cs[7]);
            }
        }
        __syncwarp();
        asm volatile("setmaxnreg.inc.sync.aligned.u32 192;");
        TS0(44);
        bar_sync_id(8 + wg, 256);
        mbar_arrive_if0(bar + 8 * B_CSP, lane | (wg ^ 1));
        TSX(tid - 128, 45);
        float a1[56];
        const int frow = (g1 ? q : 0) * 128 + wg * 64 + w4 * 16 + g;
        const int orow = q * 128 + wg * 64 + w4 * 16 + g;
        const unsigned short* b1u = reinterpret_cast<const unsigned short*>(b1);
        const unsigned short* b2u = reinterpret_cast<const unsigned short*>(b2);
        uint32_t b1p = b1u[frow] | ((uint32_t)b1u[frow + 8] << 16);
        uint32_t b2p = z ? 0u : (b2u[orow] | ((uint32_t)b2u[orow + 8] << 16));
        const uint64_t dA = mkdesc(sb + OFF_A + wg * 8192, 16, 1024, 1);
        const uint64_t dH = mkdesc(sb + OFF_B, 1792, 128, 0);
        const uint64_t dU = mkdesc(sb + OFF_B, 128, 1024, 0);
        auto release = [&](uint32_t a) { mbar_arrive_if0(a, lane); };
        auto g1_wait = [&](uint32_t r) { mbar_wait(bar + 8 * (B_FULL + r % 6), g1 ? (r / 6) & 1 : 1); TS0(64 + r); };
        auto g1_free = [&](uint32_t r) { mbar_arrive_if0(bar + 8 * (B_EMPTY + r % 6), lane | !g1); };
        auto g1_mma = [&](uint32_t s) {
            wg_fence();
#pragma unroll
            for (int k = 0; k < 4; k++) wgmma_m64n112k16<1, 1>(a1, dA + s * 1024 + k * 128, dH + s * 896 + k * 224, 1);
            wg_commit();
        };
        {
            float aq0[28], aq1[28], aq2[28];
            const uint64_t dW = mkdesc(sb + OFF_B + (P & 1) * 16, 16, 1024, 1);
            uint32_t xf[2][4][4];
            const uint32_t xa = sb + OFF_A + wg * 8192 + (w4 * 16 + (lane & 15)) * 128;
            auto wait_x = [&](int kb) { mbar_wait(bar + 8 * (B_FULLQ + kb), 0); TS0(170 + kb); };
            auto load_x = [&](int kb) {
#pragma unroll
                for (int k = 0; k < 4; k++)
                    ldsm4(xa + ((XSLOT >> (4 * kb)) & 7) * 16384 + (((2 * k + (lane >> 4)) ^ (lane & 7)) << 4), xf[kb & 1][k]);
            };
            auto qkv_mma = [&](int kb, int k) {
                const uint32_t (&f)[4] = xf[kb & 1][k];
                const uint64_t d = dW + ((WSLOT >> (4 * kb)) & 7) * 1536 + k * 128;
                const int sc = (k > 0) | (kb > 0);
                wgmma_m64n56k16_rs<1>(aq0, f[0], f[1], f[2], f[3], d, sc);
                wgmma_m64n56k16_rs<1>(aq1, f[0], f[1], f[2], f[3], d + 512, sc);
                wgmma_m64n56k16_rs<1>(aq2, f[0], f[1], f[2], f[3], d + 1024, sc);
            };
#pragma unroll
            for (int kb = 0; kb < 7; kb++) {
                wait_x(kb); load_x(kb);
                wg_fence();
#pragma unroll
                for (int k = 0; k < 4; k++) qkv_mma(kb, k);
                wg_commit();
                if (kb == 0) asm volatile("barrier.cluster.wait.aligned;" ::: "memory");
                if (kb > 0) { wg_wait<1>(); release(bar + 8 * (B_EMPTYQ + kb - 1)); }
                if (kb == 1 || kb == 2)
                    asm volatile("{\n.reg .pred p;\nsetp.eq.u32 p, %1, 0;\n@p mbarrier.arrive.shared::cluster.b64 _, [%0];\n}"
                                 ::"r"(mapa(bar + 8 * (B_EMPTYQ + kb - 1), z ^ 1)), "r"(lane) : "memory");
            }
            TS0(2);
            asm volatile("" : "+r"(b1p)::"memory");
#pragma unroll
            for (int i = 0; i < 56; i++) a1[i] = i < 28 ? ((i & 2) ? bf_hi(b1p) : bf_lo(b1p)) : 0.f;
            pin(a1);
            g1_wait(0);
            g1_mma(0);
            wg_wait<1>();
            pin(aq0); pin(aq1); pin(aq2);
            release(bar + 8 * (B_EMPTYQ + 6));
            TS0(3);
            g1_wait(1);
            g1_mma(1);
            mbar_wait(bar + 8 * B_AUX, 0);
            const int row = wg * 64 + w4 * 16;
            float2 sl, sh;
            asm volatile("ld.shared.v2.f32 {%0,%1}, [%2];" : "=f"(sl.x), "=f"(sl.y) : "r"(sb + OFF_STATS + (row + g) * 16 + z * 8) : "memory");
            asm volatile("ld.shared.v2.f32 {%0,%1}, [%2];" : "=f"(sh.x), "=f"(sh.y) : "r"(sb + OFF_STATS + (row + g + 8) * 16 + z * 8) : "memory");
            bar_sync<1, 256>();
            const uint32_t so = (row + (lane & 15)) * 112 + (lane >> 4) * 16;
            auto put = [&](const float (&a)[28], int sec, uint32_t dst) {
                uint32_t p[14];
#pragma unroll
                for (int n = 0; n < 7; n++) {
                    const float2 cs = *reinterpret_cast<const float2*>(smem + OFF_CS + sec * 224 + n * 32 + tq * 8);
                    p[2 * n] = pack2(fmaf(a[4 * n], sl.x, sl.y * cs.x), fmaf(a[4 * n + 1], sl.x, sl.y * cs.y));
                    p[2 * n + 1] = pack2(fmaf(a[4 * n + 2], sh.x, sh.y * cs.x), fmaf(a[4 * n + 3], sh.x, sh.y * cs.y));
                }
#pragma unroll
                for (int n = 0; n < 3; n++) stsm4(dst + so + n * 32, p[4 * n], p[4 * n + 1], p[4 * n + 2], p[4 * n + 3]);
                stsm2(dst + (row + (lane & 15)) * 112 + 96, p[12], p[13]);
            };
            put(aq1, 1, sb + OFF_K + 896);
            wg_wait<1>(); g1_free(0); g1_wait(2); g1_mma(2); sched_fence(sb);
            put(aq2, 2, sb + OFF_V + 896);
            wg_wait<1>(); g1_free(1); g1_wait(3); g1_mma(3); sched_fence(sb);
            fence_async_smem();
            __syncwarp();
            release(bar + 8 * B_QKV);
            put(aq0, 0, sb + OFF_Q);
            TS0(4);
        }
        if (!g1) {
            const int ic = (q - 14) * 8 + j * 2 + z, pp = ic >> 1, cg0 = (ic & 1) * 28 + (lane >> 3);
            uint4 v[7];
#pragma unroll
            for (int i = 0; i < 7; i++) {
                v[i] = make_uint4(0, 0, 0, 0);
                if (warp < 7) v[i] = ldg_nc(reinterpret_cast<const uint4*>(wo + (size_t)(pp * 56 + warp * 8 + (lane & 7)) * D_) + cg0 + 4 * i);
            }
#pragma unroll
            for (int i = 0; i < 7; i++) {
                const int cg = cg0 + 4 * i;
                int pos = cg % 14 + (pp >= 4 ? 6 : 0);
                if (pos >= 14) pos -= 14;
                *reinterpret_cast<uint4*>(g_bimg + (pp * 4 + cg / 14) * BLK + pos * 1024 + warp * 128 + (lane & 7) * 16) = v[i];
            }
            if (tid < 112) {
                const int id = ic * 112 + tid, rem = id % 896, kg = (rem >> 3) & 7, r = rem & 7;
                const uint32_t one = ((rem >> 6) == kg && (id < 896 || kg < 6)) ? (0x3F80u << (16 * (r & 1))) : 0u;
                reinterpret_cast<uint4*>(g_ident)[id] = make_uint4((r >> 1) == 0 ? one : 0, (r >> 1) == 1 ? one : 0, (r >> 1) == 2 ? one : 0, (r >> 1) == 3 ? one : 0);
            }
            fence_async_global();
            bar_sync<1, 256>();
            if (tid == 0) red_release(g_ctr + C_WO);
        }
        __syncwarp();
        wg_wait<1>();
        g1_free(2);
        auto g1_steps = [&](uint32_t r0, uint32_t r1) {
#pragma unroll 1
            for (uint32_t r = r0; r < r1; r++) {
                const uint32_t s = slot(r);
                mbar_wait(bar + 8 * (B_FULL + s), phase(r));
                TS0(64 + r);
                g1_mma(s);
                wg_wait<1>();
                release(bar + 8 * (B_EMPTY + slot(r - 1)));
            }
        };
        g1_steps(g1 ? 4 : ATT_STEP, ATT_STEP);
        {
            uint32_t qf[2][2][4], kf[2][3][4], vf[2][3][4];
            mbar_wait(bar + 8 * B_HALO, 0);
            {
                const uint32_t qa = sb + OFF_Q + (warp * 16 + (lane & 15)) * 112 + (lane >> 4) * 16;
                const uint32_t ka = sb + OFF_K + (warp * 16 + (lane & 7)) * 112 + (lane >> 3) * 16;
                const uint32_t va = sb + OFF_V + (warp * 16 + (lane & 15)) * 112 + (lane >> 4) * 16;
#pragma unroll
                for (int hd = 0; hd < 2; hd++) {
                    ldsm4(qa + hd * 48, qf[hd][0]); ldsm4(qa + hd * 48 + 32, qf[hd][1]);
#pragma unroll
                    for (int u = 0; u < 3; u++) ldsm4(ka + hd * 48 + u * 896, kf[hd][u]);
                    ldsm4t(va + hd * 48, vf[hd][0]); ldsm4t(va + hd * 48 + 32, vf[hd][1]);
                    ldsm4t(ka + (OFF_V - OFF_K) + hd * 48 + 1792, vf[hd][2]);
                }
            }
            if (tq >= 2) { qf[0][1][2] = 0; qf[0][1][3] = 0; } else { qf[1][0][0] = 0; qf[1][0][1] = 0; }
            const bool up0 = 2 * tq > g, up1 = 2 * tq + 1 > g, edge = (R | warp) == 0;
            const uint32_t mk = (up0 ? 0xFFFFu : 0u) | (up1 ? 0xFFFF0000u : 0u);
            const float scl = 0.18898223650461362f * 1.4426950408889634f;
            wg_wait<0>();
            g1_free(ATT_STEP - 1);
            bar_sync<1, 256>();
            sched_fence(sb);
            TS0(19);
            float sc[2][3][4];
#pragma unroll
            for (int hd = 0; hd < 2; hd++)
#pragma unroll
                for (int u = 0; u < 3; u++) {
                    sc[hd][u][0] = sc[hd][u][1] = sc[hd][u][2] = sc[hd][u][3] = 0.f;
                    mma16816(sc[hd][u], qf[hd][0][0], qf[hd][0][1], qf[hd][0][2], qf[hd][0][3], kf[hd][u][0], kf[hd][u][1]);
                }
#pragma unroll
            for (int hd = 0; hd < 2; hd++)
#pragma unroll
                for (int u = 0; u < 3; u++)
                    mma16816(sc[hd][u], qf[hd][1][0], qf[hd][1][1], qf[hd][1][2], qf[hd][1][3], kf[hd][u][2], kf[hd][u][3]);
            float e[2][2][2], mx[2][2], sm[2][2];
#pragma unroll
            for (int hd = 0; hd < 2; hd++) {
                e[hd][0][0] = up0 ? (edge ? -1e30f : sc[hd][0][0]) : sc[hd][1][0];
                e[hd][0][1] = up1 ? (edge ? -1e30f : sc[hd][0][1]) : sc[hd][1][1];
                e[hd][1][0] = up0 ? sc[hd][1][2] : sc[hd][2][2];
                e[hd][1][1] = up1 ? sc[hd][1][3] : sc[hd][2][3];
                mx[hd][0] = fmaxf(e[hd][0][0], e[hd][0][1]);
                mx[hd][1] = fmaxf(e[hd][1][0], e[hd][1][1]);
            }
#pragma unroll
            for (int o = 1; o <= 2; o <<= 1)
#pragma unroll
                for (int i = 0; i < 4; i++) mx[i >> 1][i & 1] = fmaxf(mx[i >> 1][i & 1], __shfl_xor_sync(0xffffffffu, mx[i >> 1][i & 1], o));
            uint32_t pp[2][2];
#pragma unroll
            for (int i = 0; i < 4; i++) {
                float* ee = e[i >> 1][i & 1];
                const float m = mx[i >> 1][i & 1] * scl;
                pp[i >> 1][i & 1] = pack2(ex2(fmaf(ee[0], scl, -m)), ex2(fmaf(ee[1], scl, -m)));
                sm[i >> 1][i & 1] = bf_lo(pp[i >> 1][i & 1]) + bf_hi(pp[i >> 1][i & 1]);
            }
            float ov[2][4][4];
#pragma unroll
            for (int hd = 0; hd < 2; hd++)
#pragma unroll
                for (int n = 0; n < 4; n++) {
                    ov[hd][n][0] = ov[hd][n][1] = ov[hd][n][2] = ov[hd][n][3] = 0.f;
                    mma16816(ov[hd][n], pp[hd][0] & mk, 0u, pp[hd][0] & ~mk, pp[hd][1] & mk, vf[hd][n >> 1][2 * (n & 1)], vf[hd][n >> 1][2 * (n & 1) + 1]);
                }
#pragma unroll
            for (int hd = 0; hd < 2; hd++)
#pragma unroll
                for (int n = 0; n < 4; n++) mma1688(ov[hd][n], 0u, pp[hd][1] & ~mk, vf[hd][2][n]);
            sched_fence(sb);
            bar_sync<1, 256>();
            TS0(53);
            g1_wait(ATT_STEP); g1_mma(ATT_STEP % 6);
            g1_wait(ATT_STEP + 1); g1_mma((ATT_STEP + 1) % 6);
            sched_fence(sb);
#pragma unroll
            for (int o = 1; o <= 2; o <<= 1)
#pragma unroll
                for (int i = 0; i < 4; i++) sm[i >> 1][i & 1] += __shfl_xor_sync(0xffffffffu, sm[i >> 1][i & 1], o);
            const uint32_t oa = sb + OFF_OST + (warp * 16 + (lane & 15)) * 128;
            uint32_t op[16];
            op[14] = op[15] = 0;
#pragma unroll
            for (int i = 0; i < 4; i++) sm[i >> 1][i & 1] = rcp(sm[i >> 1][i & 1]);
#pragma unroll
            for (int n = 0; n < 7; n++) {
                const bool hb = n > 3 || (n == 3 && tq >= 2);
#pragma unroll
                for (int h = 0; h < 2; h++) {
                    const float r = hb ? sm[1][h] : sm[0][h];
                    const float x0 = hb ? ov[1][n >= 3 ? n - 3 : 0][2 * h] : ov[0][n <= 3 ? n : 0][2 * h];
                    const float x1 = hb ? ov[1][n >= 3 ? n - 3 : 0][2 * h + 1] : ov[0][n <= 3 ? n : 0][2 * h + 1];
                    op[2 * n + h] = pack2(x0 * r, x1 * r);
                }
            }
#pragma unroll
            for (int n = 0; n < 4; n++) stsm4(oa + (((2 * n + (lane >> 4)) ^ (lane & 7)) << 4), op[4 * n], op[4 * n + 1], op[4 * n + 2], op[4 * n + 3]);
            fence_async_smem();
            __syncwarp();
            release(bar + 8 * B_OST);
            TS0(20);
            wg_wait<1>();
            g1_free(ATT_STEP);
        }
        g1_steps(g1 ? ATT_STEP + 2 : 16, 16);
        TS0(5);
        float a2[56];
        asm volatile("" : "+r"(b2p)::"memory");
#pragma unroll
        for (int i = 0; i < 56; i++) a2[i] = (i & 2) ? bf_hi(b2p) : bf_lo(b2p);
        auto o_issue = [&](uint32_t r) {
            const uint32_t s = slot(r);
            mbar_wait(bar + 8 * (B_FULL + s), phase(r));
            wg_fence();
#pragma unroll
            for (int k = 0; k < 4; k++) wgmma_m64n112k16<0, 1>(a2, dA + s * 1024 + k * 2, dU + s * 896 + k * 16, 1);
            wg_commit();
        };
        const uint32_t peer = z ^ 1;
        pin(a2);
        o_issue(r_o);
        wg_wait<1>();
        pin(a1);
        TS0(6);
        mbar_wait_cluster(bar + 8 * B_FREE, 0);
        if (g1) {
            release(bar + 8 * (B_EMPTY + 3));
            send_half(a1, mapa(sb + OFF_RECV1 + wg * 7168, peer), mapa(bar + 8 * (B_RECV1 + wg), peer), t);
        }
        o_issue(r_o + 1);
        TS0(7);
        if (g1) {
            uint32_t p[14];
            mbar_wait_cluster(bar + 8 * (B_RECV1 + wg), 0);
            TS0(8);
            recv_half(p, sb + OFF_RECV1 + wg * 7168, t);
#pragma unroll
            for (int i = 0; i < 14; i++) p[i] = pack2(gelu_tanh(a1[2 * i] + bf_lo(p[i])), gelu_tanh(a1[2 * i + 1] + bf_hi(p[i])));
            const uint32_t dst = sb + OFF_UST + wg * 7168 + w4 * 256 + (lane & 15) * 16;
#pragma unroll
            for (int n = 0; n < 3; n++) stsm4(dst + (2 * n + (lane >> 4)) * 1024, p[4 * n], p[4 * n + 1], p[4 * n + 2], p[4 * n + 3]);
            stsm2(dst + 6144, p[12], p[13]);
            fence_async_smem();
            __syncwarp();
            release(bar + 8 * (B_UST + wg));
        }
        TS0(9);
        __syncwarp();
        wg_wait<1>();
        release(bar + 8 * (B_EMPTY + slot(r_o)));
#pragma unroll 1
        for (uint32_t r = r_o + 2; r < r_u; r++) {
            o_issue(r);
            wg_wait<1>();
            release(bar + 8 * (B_EMPTY + slot(r - 1)));
        }
        wg_wait<0>();
        release(bar + 8 * (B_EMPTY + slot(r_u - 1)));
        TS0(10);
#pragma unroll 1
        for (uint32_t r = r_u; r < r_u + 14; r++) {
            const uint32_t s = slot(r);
            mbar_wait(bar + 8 * (B_FULL + s), phase(r));
            TS0(85 + r - r_u);
            wg_fence();
#pragma unroll
            for (int k = 0; k < 4; k++) wgmma_m64n112k16<1, 1>(a2, dA + s * 1024 + k * 128, dU + s * 896 + k * 16, 1);
            wg_commit();
            wg_wait<1>();
            mbar_arrive_if0(bar + 8 * (B_EMPTY + slot(r - 1)), lane | (r == r_u));
        }
        mbar_wait(bar + 8 * B_UDONE, g1 ? 0 : 1);
        wg_wait<0>();
        pin(a2);
        TS0(11);
        {
            const uint32_t rbuf = mapa(sb + OFF_RECV2 + wg * 8192 + t * 16, peer) - (z ? 0 : 2048), rbar = mapa(bar + 8 * (B_RECV2 + wg), peer);
#pragma unroll
            for (int i = 3; i >= 0; i--)
                if (i > 0 || z)
                    asm volatile("st.async.weak.shared::cluster.mbarrier::complete_tx::bytes.v4.b32 [%0], {%1,%2,%3,%4}, [%5];" ::"r"(rbuf + i * 2048),
                                 "r"(pack2(a2[24 + 8 * i], a2[25 + 8 * i])), "r"(pack2(a2[26 + 8 * i], a2[27 + 8 * i])),
                                 "r"(pack2(a2[28 + 8 * i], a2[29 + 8 * i])), "r"(pack2(a2[30 + 8 * i], a2[31 + 8 * i])), "r"(rbar) : "memory");
            mbar_wait_cluster(bar + 8 * (B_RECV2 + wg), 0);
            TS0(12);
            const uint32_t dst = sb + OFF_OUT + wg * 8192 + (w4 * 16 + (lane & 15)) * 128;
#pragma unroll
            for (int i = 0; i < 4; i++) {
                uint32_t p[4];
                asm volatile("ld.shared.v4.b32 {%0,%1,%2,%3}, [%4];" : "=r"(p[0]), "=r"(p[1]), "=r"(p[2]), "=r"(p[3]) : "r"(sb + OFF_RECV2 + wg * 8192 + i * 2048 + t * 16) : "memory");
#pragma unroll
                for (int e = 0; e < 4; e++) p[e] = pack2(a2[8 * i + 2 * e] + bf_lo(p[e]), a2[8 * i + 2 * e + 1] + bf_hi(p[e]));
                stsm4(dst + (((2 * i + (lane >> 4)) ^ (lane & 7)) << 4), p[0], p[1], p[2], p[3]);
            }
            fence_async_smem();
            bar_sync_id(2 + wg, 128);
            if (t == 0) {
                tma2d_store(&mp.out[z], sb + OFF_OUT + wg * 8192, j * 112 + z * 64, q * 128 + wg * 64);
                bulk_commit();
                bulk_wait_read();
            }
        }
        TS0(13);
        TG(61);
    } else if (warp < 12) {
        asm volatile("setmaxnreg.dec.sync.aligned.u32 96;");
        const int hw = warp - 8;
        TSH(46);
        uint4 xr[7];
        {
            const uint4* px = reinterpret_cast<const uint4*>(x + (size_t)(16 * b + hw * 4 + (lane & 3)) * D_) + (lane >> 2);
#pragma unroll
            for (int i = 0; i < 7; i++) xr[i] = ldg_nc(px + 8 * i);
        }
        TSH(47);
        asm volatile("barrier.cluster.arrive.relaxed.aligned;" ::: "memory");
        asm volatile("bar.arrive 10, 256;" ::: "memory");
        {
            float v[56];
            float s = 0.f;
#pragma unroll
            for (int i = 0; i < 7; i++) {
                const uint32_t u[4] = {xr[i].x, xr[i].y, xr[i].z, xr[i].w};
#pragma unroll
                for (int e = 0; e < 4; e++) { v[8 * i + 2 * e] = bf_lo(u[e]); v[8 * i + 2 * e + 1] = bf_hi(u[e]); }
                s += ((v[8 * i] + v[8 * i + 1]) + (v[8 * i + 2] + v[8 * i + 3])) + ((v[8 * i + 4] + v[8 * i + 5]) + (v[8 * i + 6] + v[8 * i + 7]));
            }
            TSH(16);
            s += __shfl_xor_sync(0xffffffffu, s, 4); s += __shfl_xor_sync(0xffffffffu, s, 8); s += __shfl_xor_sync(0xffffffffu, s, 16);
            const float mean = s * (1.f / D_);
            float s1[4] = {0.f, 0.f, 0.f, 0.f}, s2[4] = {0.f, 0.f, 0.f, 0.f};
#pragma unroll
            for (int i = 0; i < 56; i++) { v[i] -= mean; s1[i & 3] += v[i]; s2[i & 3] = fmaf(v[i], v[i], s2[i & 3]); }
            float d1 = (s1[0] + s1[1]) + (s1[2] + s1[3]), d2 = (s2[0] + s2[1]) + (s2[2] + s2[3]);
#pragma unroll
            for (int o = 4; o <= 16; o <<= 1) { d1 += __shfl_xor_sync(0xffffffffu, d1, o); d2 += __shfl_xor_sync(0xffffffffu, d2, o); }
            d1 *= (1.f / D_); d2 *= (1.f / D_);
            const float r1 = rsqrtf(d2 + 1e-5f);
            const float r2 = rsqrtf((d2 - d1 * d1) * r1 * r1 + 1e-5f);
            const float sc = r1 * r2, of = -d1 * sc;
            const int rl = hw * 4 + (lane & 3);
            const uint32_t rot = b >= 64 ? 7 : 0;
            uint8_t* hdst = smem + OFF_A + (rl >> 3) * 1792 + (rl & 7) * 16;
#pragma unroll
            for (int i = 0; i < 7; i++) {
                const uint32_t ch = (lane >> 2) + 8 * i, sl = ch / 14;
                uint32_t pos = ch % 14 + rot;
                if (pos >= 14) pos -= 14;
                uint4 o;
                o.x = pack2(fmaf(v[8 * i], sc, of), fmaf(v[8 * i + 1], sc, of));
                o.y = pack2(fmaf(v[8 * i + 2], sc, of), fmaf(v[8 * i + 3], sc, of));
                o.z = pack2(fmaf(v[8 * i + 4], sc, of), fmaf(v[8 * i + 5], sc, of));
                o.w = pack2(fmaf(v[8 * i + 6], sc, of), fmaf(v[8 * i + 7], sc, of));
                *reinterpret_cast<uint4*>(hdst + sl * 3584 + pos * 128) = o;
            }
            if (lane < 4) *reinterpret_cast<float2*>(smem + OFF_LNST + rl * 8) = make_float2(r1, -mean * r1);
            fence_async_smem();
            asm volatile("barrier.cluster.wait.aligned;" ::: "memory");
            mbar_arrive_if0(bar + 8 * B_LNST, lane);
            TSH(17);
        }
        if (hw == 2 && lane == 0) {
            mbar_wait(bar + 8 * B_OST, 0);
            tma2d_store(&mp.ost, sb + OFF_OST, z * 64, P * 1024 + R * 128);
            bulk_commit();
            bulk_wait_all();
            red_relaxed(g_ctr + C_O + q * 32);
            TS(21);
            mbar_arrive(bar + 8 * B_FREE);
            asm volatile("fence.release.sync_restrict::shared::cta.cluster;" ::: "memory");
            asm volatile("mbarrier.arrive.relaxed.cluster.shared::cluster.b64 _, [%0];" ::"r"(mapa(bar + 8 * B_FREE, z ^ 1)) : "memory");
        } else if (hw < 2 && lane == 0 && g1) {
            const int ub = 2 * q + hw, zz = ub >= 14 ? 1 : 0;
            uint8_t* ud = g_bimg + ((8 + ub) * 4 + j) * BLK;
            mbar_wait(bar + 8 * (B_UST + hw), 0);
            bulk_store(ud + ((7 * z + 1 + 6 * zz) % 14) * 1024, sb + OFF_UST + hw * 7168 + 1024, 6144);
            bulk_store(ud + (7 * z + 6 * zz) * 1024, sb + OFF_UST + hw * 7168, 1024);
            bulk_commit();
            bulk_wait_all();
            red_relaxed(g_ctr + C_U + ((j * 2 + zz) * 2 + hw) * 32);
            TS(22 + hw);
            mbar_arrive(bar + 8 * B_UDONE);
        }
    } else {
        asm volatile("setmaxnreg.dec.sync.aligned.u32 32;");
        auto epoch = [&]() { mbar_wait(bar + 8 * B_EP, 0); return *reinterpret_cast<volatile unsigned*>(smem + OFF_EP); };
        auto wait_free = [&](uint32_t r, uint32_t first) {
            const uint32_t a = r < 6 ? B_EMPTYQ + ((first >> (4 * r)) & 7) : B_EMPTY + slot(r);
            mbar_wait(bar + 8 * a, r < 6 ? 0 : phase(r) ^ 1);
        };
        if (warp == 12) {
            if (lane == 0) {
#pragma unroll
                for (int i = 1; i < 7; i++) mbar_init(bar + 8 * (B_FULLQ + i), 1);
                asm volatile("fence.mbarrier_init.release.cluster;" ::: "memory");
            }
            __syncwarp();
            asm volatile("bar.arrive 8, 256;\nbar.arrive 9, 256;" ::: "memory");
            asm volatile("barrier.cluster.arrive.relaxed.aligned;" ::: "memory");
            bar_sync<7, 128>();
            asm volatile("barrier.cluster.wait.aligned;" ::: "memory");
            TS(48);
            if (lane == 0) {
#pragma unroll 1
                for (int kb = 1; kb < QDEPTH; kb++) qkv_load(kb);
#pragma unroll 1
                for (int kb = QDEPTH; kb < 7; kb++) {
                    mbar_wait(bar + 8 * (B_FULLQ + kb - QDEPTH), 0);
                    if (kb >= 5) mbar_wait(bar + 8 * (B_EMPTYQ + kb - 5), 0);
                    qkv_load(kb);
                }
                TS(50);
                mbar_wait(bar + 8 * B_LNFREE, 0);
#pragma unroll 1
                for (uint32_t r = 0; r < r_o; r++) {
                    const uint32_t s = slot(r), fb = bar + 8 * (B_FULL + s);
                    wait_free(r, 0x654320u);
                    mbar_expect(fb, 16384);
                    tma3d(sb + OFF_A + s * 16384, &mp.w1, 0, z * 1024 + r * 64, 2 * q, fb);
                    TS(99 + r);
                }
#pragma unroll 1
                for (uint32_t r = r_o; r < r_u; r++) {
                    const uint32_t s = slot(r), fb = bar + 8 * (B_FULL + s);
                    if (r == r_o + 1) { poll_slow(g_ctr + C_O + (R * 2 + z) * 32, epoch() * 8); fence_async_global(); TS(32); }
                    wait_free(r, 0x654320u);
                    mbar_expect(fb, 16384);
                    if (r == r_o) tma2d(sb + OFF_A + s * 16384, &mp.xn, j * 112 + z * 64, q * 128, fb);
                    else tma2d(sb + OFF_A + s * 16384, &mp.old_, 0, (4 * z + r - r_o - 1) * S_ + q * 128, fb);
                    TS(99 + 16 + r - r_o);
                }
#pragma unroll 1
                for (uint32_t i = 0; i < 14; i++) {
                    const uint32_t r = r_u + i, s = slot(r), fb = bar + 8 * (B_FULL + s);
                    wait_free(r, 0x654320u);
                    mbar_expect(fb, 16384);
                    tma3d(sb + OFF_A + s * 16384, &mp.w2, 0, (14 * z + (i < 7 ? 2 * i : 2 * i - 13)) * 64, 2 * q, fb);
                    TS(99 + 21 + i);
                }
            }
        } else if (warp == 13) {
            if (lane == 0) {
#pragma unroll
                for (int i = B_EMPTYQ; i < B_EMPTY; i++) mbar_init(bar + 8 * i, i >= B_FULL ? 2 : i < B_EMPTYQ + 2 ? 16 : 8);
                asm volatile("fence.mbarrier_init.release.cluster;" ::: "memory");
            }
            __syncwarp();
            asm volatile("bar.arrive 8, 256;\nbar.arrive 9, 256;" ::: "memory");
            asm volatile("barrier.cluster.arrive.relaxed.aligned;" ::: "memory");
            bar_sync<7, 128>();
            if (lane == 0) {
                const unsigned e1 = epoch();
                auto run = [&](uint32_t r0, uint32_t n, const uint8_t* src, uint32_t stride, uint32_t ts) {
#pragma unroll 1
                    for (uint32_t r = r0; r < r0 + n; r++, src += stride) {
                        const uint32_t s = slot(r), fb = bar + 8 * (B_FULL + s);
                        wait_free(r, 0x644332u);
                        mbar_expect(fb, BLK);
                        bulk_load(sb + OFF_B + s * BLK, src, BLK, fb);
                        TS(ts + r - r0);
                    }
                };
#pragma unroll 1
                for (int ph = g1 ? 0 : 1; ph < 5; ph++) {
                    if (ph == 0) mbar_wait(bar + 8 * B_LN, 0);
                    else if (ph == 1) poll_slow(g_ctr + C_WO, e1 * 16);
                    else if (ph > 2) poll(g_ctr + C_U + ((j * 2 + z) * 2 + ph - 3) * 32, e1 * 14);
                    fence_async_global();
                    TS(ph == 0 ? 33 : ph == 3 ? 34 : ph == 4 ? 35 : 63);
                    const uint8_t* src = ph == 0 ? g_himg + (64 * z + j) * BLK : ph == 1 ? g_ident + z * BLK
                                                 : g_bimg + ((ph == 2 ? 4 * z : 5 + 14 * z + ph) * 4 + j) * BLK;
                    const uint32_t off = ph < 2 ? 0 : ph == 2 ? 1 : 5 + 7 * (ph - 3);
                    run(ph == 0 ? 0 : r_o + off, ph == 0 ? 16 : ph == 1 ? 1 : ph == 2 ? 4 : 7, src, ph < 3 ? 4 * BLK : 8 * BLK, 134 + (ph == 0 ? 0 : 16 + off));
                }
            }
        } else if (warp == 14) {
            if (lane == 0) {
#pragma unroll
                for (int i = B_EMPTY; i < B_AUX; i++) mbar_init(bar + 8 * i, 8);
            }
            __syncwarp();
            asm volatile("bar.arrive 8, 256;\nbar.arrive 9, 256;" ::: "memory");
            asm volatile("barrier.cluster.arrive.relaxed.aligned;" ::: "memory");
            unsigned* lnc = g_ctr + C_LN + 32 * (c & 7);
            const unsigned e1 = (ld_relaxed(lnc) >> 7) + 1;
            bar_sync<7, 128>();
            if (lane == 0) {
                *reinterpret_cast<volatile unsigned*>(smem + OFF_EP) = e1;
                mbar_arrive(bar + 8 * B_EP);
                TS(36);
            }
            mbar_wait(bar + 8 * B_CSP, 0);
            if (lane < 28) {
                const float2* p = reinterpret_cast<const float2*>(smem + OFF_CSP) + lane;
                float2 a = p[0];
#pragma unroll
                for (int i = 1; i < 4; i++) { const float2 v = p[28 * i]; a.x += v.x; a.y += v.y; }
                reinterpret_cast<float2*>(smem + OFF_CSOUT)[lane] = a;
            }
            fence_async_smem();
            __syncwarp();
            if (lane == 0) {
                if (b < 96) bulk_store(g_cs + ((b % 24) & 7) * 672 + (b / 24) * 168 + ((b % 24) >> 3) * 56, sb + OFF_CSOUT, 224);
                mbar_wait(bar + 8 * B_LNST, 0);
                tma4d_store(&mp.hst, sb + OFF_A, 0, 0, b & 3, b & ~3);
                bulk_store(g_stats + 16 * b, sb + OFF_LNST, 128);
                bulk_commit();
                bulk_wait_all();
            }
            __syncwarp();
            if (lane < 8) red_relaxed(g_ctr + C_LN + 32 * lane);
            if (lane == 0) {
                mbar_arrive(bar + 8 * B_LNFREE);
                TS(37);
                poll(lnc, e1 * 128);
                mbar_arrive(bar + 8 * B_LN);
                fence_async_global();
                mbar_expect(bar + 8 * B_AUXL, 2048 + 2688);
                bulk_load(sb + OFF_CSIN, g_cs + P * 672, 2688, bar + 8 * B_AUXL);
                bulk_load(sb + OFF_STATS, g_stats + R * 256, 2048, bar + 8 * B_AUXL);
                TS(38);
            }
            __syncwarp();
            mbar_wait(bar + 8 * B_AUXL, 0);
            if (lane < 28) {
#pragma unroll
                for (int s = 0; s < 3; s++) {
                    const float2* p = reinterpret_cast<const float2*>(smem + OFF_CSIN) + s * 28 + lane;
                    const float2 c0 = p[0], c1 = p[84], c2 = p[168], c3 = p[252];
                    reinterpret_cast<float2*>(smem + OFF_CS)[s * 28 + lane] = make_float2((c0.x + c1.x) + (c2.x + c3.x), (c0.y + c1.y) + (c2.y + c3.y));
                }
            }
            __syncwarp();
            if (lane == 0) mbar_arrive(bar + 8 * B_AUX);
            TS(39);
        } else {
            if (lane == 0) {
                if (sb & 1023) __trap();
#pragma unroll
                for (int i = B_AUX; i < B_COUNT; i++)
                    mbar_init(bar + 8 * i, (i == B_QKV || i == B_OST) ? 8 : (i == B_FREE || i == B_UDONE) ? 2
                                           : (i == B_UST || i == B_UST + 1 || i == B_LNST || i == B_CSP) ? 4 : 1);
#pragma unroll
                for (int i = B_RECV1; i < B_UST; i++) mbar_expect(bar + 8 * i, i < B_RECV2 ? 7168 : 8192 - 2048 * z);
                asm volatile("fence.mbarrier_init.release.cluster;" ::: "memory");
            }
            __syncwarp();
            asm volatile("bar.arrive 8, 256;\nbar.arrive 9, 256;" ::: "memory");
            asm volatile("barrier.cluster.arrive.relaxed.aligned;" ::: "memory");
            asm volatile("bar.arrive 7, 128;" ::: "memory");
            if (lane == 0) {
#pragma unroll
                for (int i = 2; i < 10; i++) asm volatile("prefetch.tensormap [%0];" ::"l"(reinterpret_cast<const CUtensorMap*>(&mp) + i) : "memory");
            }
            const int me = (R * 8 + P) * 2 + z;
            mbar_wait(bar + 8 * B_QKV, 0);
            if (R == 0) {
                for (int i = lane; i < 56; i += 32) {
                    *reinterpret_cast<uint4*>(smem + OFF_K + i * 16) = make_uint4(0, 0, 0, 0);
                    *reinterpret_cast<uint4*>(smem + OFF_V + i * 16) = make_uint4(0, 0, 0, 0);
                }
                __syncwarp();
            }
            if (lane == 0) {
                if (R < 7) {
                    bulk_store(g_halo + me * 1792, sb + OFF_K + 128 * 112, 896);
                    bulk_store(g_halo + me * 1792 + 896, sb + OFF_V + 128 * 112, 896);
                    bulk_commit();
                    bulk_wait_all();
                    red_relaxed(g_ctr + C_HALO + me * 8);
                }
                if (R > 0) {
                    poll(g_ctr + C_HALO + (me - 16) * 8, epoch());
                    fence_async_global();
                    mbar_expect(bar + 8 * B_HALO, 1792);
                    bulk_load(sb + OFF_K, g_halo + (me - 16) * 1792, 896, bar + 8 * B_HALO);
                    bulk_load(sb + OFF_V, g_halo + (me - 16) * 1792 + 896, 896, bar + 8 * B_HALO);
                } else {
                    mbar_arrive(bar + 8 * B_HALO);
                }
                TS(40);
            }
        }
    }
}

typedef CUresult (*EncodeFn)(CUtensorMap*, CUtensorMapDataType, cuuint32_t, void*, const cuuint64_t*, const cuuint64_t*, const cuuint32_t*,
                             const cuuint32_t*, CUtensorMapInterleave, CUtensorMapSwizzle, CUtensorMapL2promotion, CUtensorMapFloatOOBfill);

void encode(EncodeFn fn, CUtensorMap* m, const void* p, int rank, const cuuint64_t* dims, const cuuint64_t* strides, const cuuint32_t* box, bool swz) {
    const cuuint32_t es[4] = {1, 1, 1, 1};
    fn(m, CU_TENSOR_MAP_DATA_TYPE_BFLOAT16, rank, const_cast<void*>(p), dims, strides, box, es, CU_TENSOR_MAP_INTERLEAVE_NONE,
       swz ? CU_TENSOR_MAP_SWIZZLE_128B : CU_TENSOR_MAP_SWIZZLE_NONE, CU_TENSOR_MAP_L2_PROMOTION_L2_128B, CU_TENSOR_MAP_FLOAT_OOB_FILL_NONE);
}

}

extern "C" void kernel_launch(void* const* d_in, const int* in_sizes, int n_in, void* d_out, int out_size) {
    const __nv_bfloat16* x = (const __nv_bfloat16*)d_in[0];
    const __nv_bfloat16* wqkv = (const __nv_bfloat16*)d_in[1];
    const __nv_bfloat16* wo = (const __nv_bfloat16*)d_in[2];
    const __nv_bfloat16* w1 = (const __nv_bfloat16*)d_in[4];
    const __nv_bfloat16* b1 = (const __nv_bfloat16*)d_in[5];
    const __nv_bfloat16* w2 = (const __nv_bfloat16*)d_in[6];
    const __nv_bfloat16* b2 = (const __nv_bfloat16*)d_in[7];

    void* fp = nullptr;
    cudaDriverEntryPointQueryResult qr;
    cudaGetDriverEntryPoint("cuTensorMapEncodeTiled", &fp, cudaEnableDefault, &qr);
    EncodeFn fn = (EncodeFn)fp;
    void* o = nullptr;
    cudaGetSymbolAddress(&o, g_o);
    void* himg = nullptr;
    cudaGetSymbolAddress(&himg, g_himg);

    Maps mp;
    { cuuint64_t d[2] = {896, 1024}, s[1] = {1792}; cuuint32_t bx[2] = {64, 128}; encode(fn, &mp.x, x, 2, d, s, bx, true); }
    { cuuint64_t d[3] = {448, 448, 3}, s[2] = {2688, 896}; cuuint32_t bx[3] = {64, 64, 3}; encode(fn, &mp.wqkv, wqkv, 3, d, s, bx, true); }
    { cuuint64_t d[3] = {64, 2048, 28}, s[2] = {3584, 128}; cuuint32_t bx[3] = {64, 64, 2}; encode(fn, &mp.w1, w1, 3, d, s, bx, true); }
    { cuuint64_t d[3] = {64, 1792, 32}, s[2] = {4096, 128}; cuuint32_t bx[3] = {64, 64, 2}; encode(fn, &mp.w2, w2, 3, d, s, bx, true); }
    { cuuint64_t d[4] = {64, 28, 4, 128}, s[3] = {128, 3584, BLK}; cuuint32_t bx[4] = {64, 28, 1, 4}; encode(fn, &mp.hst, himg, 4, d, s, bx, false); }
    { cuuint64_t d[2] = {448, 2048}, s[1] = {896}; cuuint32_t bx[2] = {64, 128}; encode(fn, &mp.xn, x, 2, d, s, bx, true); }
    { cuuint64_t d[2] = {64, 8 * 2048}, s[1] = {128}; cuuint32_t bx[2] = {64, 128}; encode(fn, &mp.old_, o, 2, d, s, bx, true); }
    { cuuint64_t d[2] = {128, 8 * 1024}, s[1] = {256}; cuuint32_t bx[2] = {64, 128}; encode(fn, &mp.ost, o, 2, d, s, bx, true); }
    { cuuint64_t d[2] = {448, 2048}, s[1] = {896}; cuuint32_t bx[2] = {64, 64}; encode(fn, &mp.out[0], d_out, 2, d, s, bx, true); }
    { cuuint64_t d[2] = {448, 2048}, s[1] = {896}; cuuint32_t bx[2] = {48, 64}; encode(fn, &mp.out[1], d_out, 2, d, s, bx, true); }

    cudaFuncSetAttribute(fused_kernel, cudaFuncAttributeMaxDynamicSharedMemorySize, SMEM_BYTES);
    fused_kernel<<<128, 512, SMEM_BYTES>>>(mp, x, wqkv, wo, w1, b1, w2, b2);
}
```

```cpp
#include <cuda_runtime.h>
#include <cuda.h>
#include <cuda_bf16.h>
#include <stdint.h>

namespace {

constexpr int S_ = 2048, D_ = 448;
constexpr uint32_t BLK = 14336;

constexpr uint32_t G_HIMG = 0;
constexpr uint32_t G_BIMG = G_HIMG + 32 * 4 * BLK;
constexpr uint32_t G_IDENT = G_BIMG + 36 * 4 * BLK;
constexpr uint32_t G_O = G_IDENT + 2 * BLK;
constexpr uint32_t G_STATS = G_O + 8 * S_ * 128;
constexpr uint32_t G_CS = G_STATS + S_ * 8;
constexpr uint32_t G_HALO = G_CS + 8 * 4 * 168 * 4;
constexpr uint32_t G_CTR = G_HALO + 128 * 2 * 896;
constexpr uint32_t G_END = G_CTR + 2592 * 4;
__device__ __align__(1024) uint8_t g_scratch[G_END];

constexpr int C_LN = 0, C_WO = 256, C_O = 288, C_U = 800, C_HALO = 1312, C_CS = 2336;

#define TSX(sel, id)
#define TS(id)
#define TS0(id)
#define TSH(id)
#define TG(id)

#define POLL_NS 200
#define QDEPTH 3
#define Q0 QDEPTH
#define MC0 Q0
#define FMODE 1
constexpr uint32_t OFF_A = 0;
constexpr uint32_t OFF_B = 98304;
constexpr uint32_t OFF_Q = 184320, OFF_K = 198656, OFF_V = 213888;
constexpr uint32_t OFF_OST = OFF_Q, OFF_RECV2 = OFF_Q, OFF_RECV1 = OFF_Q + 16384, OFF_UST = OFF_Q + 30720, OFF_OUT = OFF_Q + 16384;
constexpr uint32_t OFF_STATS = 221184, OFF_CSIN = OFF_STATS + 2048, OFF_CSP = OFF_CSIN + 2688, OFF_LNST = OFF_CSP + 1792, OFF_CSOUT = OFF_LNST + 128;
constexpr uint32_t OFF_CS = 229376;
constexpr uint32_t OFF_EP = OFF_CS + 672;
constexpr uint32_t OFF_BAR = OFF_EP + 16;
constexpr uint32_t OFF_TS = OFF_BAR + 8 * 48;
constexpr uint32_t SMEM_BYTES = OFF_TS;

enum : int {
    B_FULLQ = 0, B_EMPTYQ = 7, B_FULL = 14, B_EMPTY = 20, B_AUX = 26, B_QKV = 27, B_HALO = 28, B_FREE = 29,
    B_RECV1 = 30, B_RECV2 = 32, B_UST = 34, B_EP = 36, B_OST = 37, B_LNST = 38, B_CSP = 39, B_LNFREE = 40, B_LN = 41,
    B_AUXL = 42, B_UDONE = 43, B_COUNT = 44
};
constexpr uint32_t XSLOT = 0x5432154u;
constexpr uint32_t WSLOT = 0x3421034u;
#define ATT_STEP 8

__device__ __forceinline__ uint32_t smem_u32(const void* p) { return (uint32_t)__cvta_generic_to_shared(p); }
__device__ __forceinline__ void mbar_init(uint32_t a, int c) { asm volatile("mbarrier.init.shared::cta.b64 [%0], %1;" ::"r"(a), "r"(c) : "memory"); }
__device__ __forceinline__ void mbar_expect(uint32_t a, uint32_t b) { asm volatile("mbarrier.arrive.expect_tx.shared::cta.b64 _, [%0], %1;" ::"r"(a), "r"(b) : "memory"); }
__device__ __forceinline__ void mbar_arrive(uint32_t a) { asm volatile("mbarrier.arrive.shared::cta.b64 _, [%0];" ::"r"(a) : "memory"); }
__device__ __forceinline__ void mbar_arrive_if0(uint32_t a, uint32_t sel) {
    asm volatile("{\n.reg .pred p;\nsetp.eq.u32 p, %1, 0;\n@p mbarrier.arrive.shared::cta.b64 _, [%0];\n}" ::"r"(a), "r"(sel) : "memory");
}
__device__ __forceinline__ void mbar_wait(uint32_t a, uint32_t parity) {
    asm volatile(
        "{\n.reg .pred p;\n.reg .u32 n;\nmov.u32 n, 0;\n"
        "W0:\nmbarrier.try_wait.parity.shared::cta.b64 p, [%0], %1;\n@p bra W1;\n"
        "add.u32 n, n, 1;\nsetp.lt.u32 p, n, 4194304;\n@p bra W0;\ntrap;\nW1:\n}\n" ::"r"(a), "r"(parity) : "memory");
}
__device__ __forceinline__ void mbar_wait_cluster(uint32_t a, uint32_t parity) {
    asm volatile(
        "{\n.reg .pred p;\n.reg .u32 n;\nmov.u32 n, 0;\n"
        "W0:\nmbarrier.try_wait.parity.acquire.cluster.shared::cta.b64 p, [%0], %1;\n@p bra W1;\n"
        "add.u32 n, n, 1;\nsetp.lt.u32 p, n, 4194304;\n@p bra W0;\ntrap;\nW1:\n}\n" ::"r"(a), "r"(parity) : "memory");
}
__device__ __forceinline__ uint32_t mapa(uint32_t a, uint32_t cta) { uint32_t r; asm("mapa.shared::cluster.u32 %0, %1, %2;" : "=r"(r) : "r"(a), "r"(cta)); return r; }
__device__ __forceinline__ void tma2d(uint32_t dst, const CUtensorMap* m, int c0, int c1, uint32_t bar) {
    asm volatile("cp.async.bulk.tensor.2d.shared::cluster.global.mbarrier::complete_tx::bytes [%0], [%1, {%3, %4}], [%2];" ::"r"(dst), "l"(m), "r"(bar), "r"(c0), "r"(c1) : "memory");
}
__device__ __forceinline__ void tma3d(uint32_t dst, const CUtensorMap* m, int c0, int c1, int c2, uint32_t bar) {
    asm volatile("cp.async.bulk.tensor.3d.shared::cluster.global.mbarrier::complete_tx::bytes [%0], [%1, {%3, %4, %5}], [%2];" ::"r"(dst), "l"(m), "r"(bar), "r"(c0), "r"(c1), "r"(c2) : "memory");
}
__device__ __forceinline__ void tma3d_mc(uint32_t dst, const CUtensorMap* m, int c0, int c1, int c2, uint32_t bar) {
    asm volatile("cp.async.bulk.tensor.3d.shared::cluster.global.mbarrier::complete_tx::bytes.multicast::cluster [%0], [%1, {%3, %4, %5}], [%2], %6;"
                 ::"r"(dst), "l"(m), "r"(bar), "r"(c0), "r"(c1), "r"(c2), "h"((uint16_t)3) : "memory");
}
__device__ __forceinline__ void tma2d_store(const CUtensorMap* m, uint32_t src, int c0, int c1) {
    asm volatile("cp.async.bulk.tensor.2d.global.shared::cta.bulk_group [%0, {%2, %3}], [%1];" ::"l"(m), "r"(src), "r"(c0), "r"(c1) : "memory");
}
__device__ __forceinline__ void tma4d_store(const CUtensorMap* m, uint32_t src, int c0, int c1, int c2, int c3) {
    asm volatile("cp.async.bulk.tensor.4d.global.shared::cta.bulk_group [%0, {%2, %3, %4, %5}], [%1];" ::"l"(m), "r"(src), "r"(c0), "r"(c1), "r"(c2), "r"(c3) : "memory");
}
__device__ __forceinline__ void bulk_load(uint32_t dst, const void* src, uint32_t bytes, uint32_t bar) {
    asm volatile("cp.async.bulk.shared::cluster.global.mbarrier::complete_tx::bytes [%0], [%1], %2, [%3];" ::"r"(dst), "l"(src), "r"(bytes), "r"(bar) : "memory");
}
__device__ __forceinline__ void bulk_store(void* dst, uint32_t src, uint32_t bytes) {
    asm volatile("cp.async.bulk.global.shared::cta.bulk_group [%0], [%1], %2;" ::"l"(dst), "r"(src), "r"(bytes) : "memory");
}
__device__ __forceinline__ void bulk_commit() { asm volatile("cp.async.bulk.commit_group;" ::: "memory"); }
__device__ __forceinline__ void bulk_wait_all() { asm volatile("cp.async.bulk.wait_group 0;" ::: "memory"); }
__device__ __forceinline__ void bulk_wait_read() { asm volatile("cp.async.bulk.wait_group.read 0;" ::: "memory"); }
__device__ __forceinline__ void l2_prefetch(const void* p) { asm volatile("prefetch.global.L2 [%0];" ::"l"(p)); }
__device__ __forceinline__ void fence_async_smem(uint32_t spare) {
    asm volatile("fence.proxy.async.shared::cta;" ::: "memory");
}
__device__ __forceinline__ void fence_async_global() { asm volatile("fence.proxy.async.global;" ::: "memory"); }
__device__ __forceinline__ void red_relaxed(unsigned* p) { asm volatile("red.relaxed.gpu.global.add.u32 [%0], 1;" ::"l"(p) : "memory"); }
__device__ __forceinline__ void red_release(unsigned* p) { asm volatile("red.release.gpu.global.add.u32 [%0], 1;" ::"l"(p) : "memory"); }
__device__ __forceinline__ unsigned ld_relaxed(const unsigned* p) { unsigned v; asm volatile("ld.relaxed.gpu.global.u32 %0, [%1];" : "=r"(v) : "l"(p) : "memory"); return v; }
__device__ __forceinline__ bool ctr_done(unsigned v, unsigned target) { return ((v - target) & 0x1FFFFFFu) == 0; }
__device__ __forceinline__ void poll(const unsigned* p, unsigned target) {
    int n = 0;
    while (!ctr_done(ld_relaxed(p), target)) { if (++n > (1 << 21)) __trap(); }
}
__device__ __forceinline__ void poll_slow(const unsigned* p, unsigned target) {
    int n = 0;
    while (!ctr_done(ld_relaxed(p), target)) { __nanosleep(POLL_NS); if (++n > (1 << 21)) __trap(); }
}
template <int ID, int N> __device__ __forceinline__ void bar_sync() { asm volatile("bar.sync %0, %1;" ::"n"(ID), "n"(N) : "memory"); }
__device__ __forceinline__ void bar_sync_id(int id, int n) { asm volatile("bar.sync %0, %1;" ::"r"(id), "r"(n) : "memory"); }
__device__ __forceinline__ void sched_fence(uint32_t never_zero) {
    asm volatile("{\n.reg .pred p;\nF0:\nsetp.eq.u32 p, %0, 0;\n@p bra F0;\n}\n" ::"r"(never_zero) : "memory");
}
__device__ __forceinline__ void wg_fence() { asm volatile("wgmma.fence.sync.aligned;" ::: "memory"); }
__device__ __forceinline__ void wg_commit() { asm volatile("wgmma.commit_group.sync.aligned;" ::: "memory"); }
template <int N> __device__ __forceinline__ void wg_wait() { asm volatile("wgmma.wait_group.sync.aligned %0;" ::"n"(N) : "memory"); }
template <int N> __device__ __forceinline__ void pin(float (&a)[N]) {
#pragma unroll
    for (int i = 0; i < N; i++) asm volatile("" : "+f"(a[i])::"memory");
}
__device__ __forceinline__ uint4 ldg_nc(const uint4* p) {
    uint4 v;
    asm volatile("ld.volatile.global.v4.u32 {%0,%1,%2,%3}, [%4];" : "=r"(v.x), "=r"(v.y), "=r"(v.z), "=r"(v.w) : "l"(p) : "memory");
    return v;
}
__device__ __forceinline__ uint32_t ldg_u16(const void* p) {
    uint32_t v;
    asm volatile("ld.global.nc.u16 %0, [%1];" : "=r"(v) : "l"(p) : "memory");
    return v;
}
__device__ __forceinline__ uint32_t pack2(float lo, float hi) { uint32_t r; asm("cvt.rn.bf16x2.f32 %0, %1, %2;" : "=r"(r) : "f"(hi), "f"(lo)); return r; }
__device__ __forceinline__ float bf_lo(uint32_t v) { return __uint_as_float(v << 16); }
__device__ __forceinline__ float bf_hi(uint32_t v) { return __uint_as_float(v & 0xFFFF0000u); }
__device__ __forceinline__ void stsm4(uint32_t a, uint32_t r0, uint32_t r1, uint32_t r2, uint32_t r3) {
    asm volatile("stmatrix.sync.aligned.m8n8.x4.shared.b16 [%0], {%1, %2, %3, %4};" ::"r"(a), "r"(r0), "r"(r1), "r"(r2), "r"(r3) : "memory");
}
__device__ __forceinline__ void stsm2(uint32_t a, uint32_t r0, uint32_t r1) {
    asm volatile("stmatrix.sync.aligned.m8n8.x2.shared.b16 [%0], {%1, %2};" ::"r"(a), "r"(r0), "r"(r1) : "memory");
}
__device__ __forceinline__ void ldsm4(uint32_t a, uint32_t (&r)[4]) {
    asm volatile("ldmatrix.sync.aligned.m8n8.x4.shared.b16 {%0, %1, %2, %3}, [%4];" : "=r"(r[0]), "=r"(r[1]), "=r"(r[2]), "=r"(r[3]) : "r"(a) : "memory");
}
__device__ __forceinline__ void ldsm4t(uint32_t a, uint32_t (&r)[4]) {
    asm volatile("ldmatrix.sync.aligned.m8n8.x4.trans.shared.b16 {%0, %1, %2, %3}, [%4];" : "=r"(r[0]), "=r"(r[1]), "=r"(r[2]), "=r"(r[3]) : "r"(a) : "memory");
}
__device__ __forceinline__ void mma16816(float (&c)[4], uint32_t a0, uint32_t a1, uint32_t a2, uint32_t a3, uint32_t b0, uint32_t b1) {
    asm volatile("mma.sync.aligned.m16n8k16.row.col.f32.bf16.bf16.f32 {%0,%1,%2,%3}, {%4,%5,%6,%7}, {%8,%9}, {%0,%1,%2,%3};"
                 : "+f"(c[0]), "+f"(c[1]), "+f"(c[2]), "+f"(c[3]) : "r"(a0), "r"(a1), "r"(a2), "r"(a3), "r"(b0), "r"(b1));
}
__device__ __forceinline__ void mma1688(float (&c)[4], uint32_t a0, uint32_t a1, uint32_t b0) {
    asm volatile("mma.sync.aligned.m16n8k8.row.col.f32.bf16.bf16.f32 {%0,%1,%2,%3}, {%4,%5}, {%6}, {%0,%1,%2,%3};"
                 : "+f"(c[0]), "+f"(c[1]), "+f"(c[2]), "+f"(c[3]) : "r"(a0), "r"(a1), "r"(b0));
}
__device__ __forceinline__ uint64_t mkdesc(uint32_t addr, uint32_t lbo, uint32_t sbo, uint32_t sw) {
    uint32_t lo = ((addr & 0x3FFFF) >> 4) | ((lbo >> 4) << 16), hi = (sbo >> 4) | (sw << 30);
    return ((uint64_t)hi << 32) | lo;
}
__device__ __forceinline__ float ex2(float x) { float r; asm("ex2.approx.ftz.f32 %0, %1;" : "=f"(r) : "f"(x)); return r; }
__device__ __forceinline__ float rcp(float x) { float r; asm("rcp.approx.ftz.f32 %0, %1;" : "=f"(r) : "f"(x)); return r; }
__device__ __forceinline__ float gelu_tanh(float x) {
    float y = x * fmaf(x * x, 0.0356774081363f, 0.7978845608029f), t;
    asm("tanh.approx.f32 %0, %1;" : "=f"(t) : "f"(y));
    float hx = 0.5f * x;
    return fmaf(hx, t, hx);
}

template <int TB>
__device__ __forceinline__ void wgmma_m64n56k16_rs(float (&d)[28], uint32_t a0, uint32_t a1, uint32_t a2, uint32_t a3, uint64_t db, int scale_d) {
    asm volatile("{\n.reg .pred p;\nsetp.ne.b32 p, %33, 0;\n"
        "wgmma.mma_async.sync.aligned.m64n56k16.f32.bf16.bf16 "
        "{%0, %1, %2, %3, %4, %5, %6, %7, %8, %9, %10, %11, %12, %13, %14, %15, %16, %17, %18, %19, %20, %21, %22, %23, %24, %25, %26, %27}, "
        "{%28, %29, %30, %31}, %32, p, 1, 1, %34;\n}\n"
        : "+f"(d[0]), "+f"(d[1]), "+f"(d[2]), "+f"(d[3]), "+f"(d[4]), "+f"(d[5]), "+f"(d[6]), "+f"(d[7]), "+f"(d[8]), "+f"(d[9]), "+f"(d[10]), "+f"(d[11]), "+f"(d[12]), "+f"(d[13]), "+f"(d[14]), "+f"(d[15]), "+f"(d[16]), "+f"(d[17]), "+f"(d[18]), "+f"(d[19]), "+f"(d[20]), "+f"(d[21]), "+f"(d[22]), "+f"(d[23]), "+f"(d[24]), "+f"(d[25]), "+f"(d[26]), "+f"(d[27])
        : "r"(a0), "r"(a1), "r"(a2), "r"(a3), "l"(db), "r"(scale_d), "n"(TB));
}
template <int TA, int TB>
__device__ __forceinline__ void wgmma_m64n112k16(float (&d)[56], uint64_t da, uint64_t db, int scale_d) {
    asm volatile("{\n.reg .pred p;\nsetp.ne.b32 p, %58, 0;\n"
        "wgmma.mma_async.sync.aligned.m64n112k16.f32.bf16.bf16 "
        "{%0, %1, %2, %3, %4, %5, %6, %7, %8, %9, %10, %11, %12, %13, %14, %15, %16, %17, %18, %19, %20, %21, %22, %23, %24, %25, %26, %27, %28, %29, %30, %31, %32, %33, %34, %35, %36, %37, %38, %39, %40, %41, %42, %43, %44, %45, %46, %47, %48, %49, %50, %51, %52, %53, %54, %55}, "
        "%56, %57, p, 1, 1, %59, %60;\n}\n"
        : "+f"(d[0]), "+f"(d[1]), "+f"(d[2]), "+f"(d[3]), "+f"(d[4]), "+f"(d[5]), "+f"(d[6]), "+f"(d[7]), "+f"(d[8]), "+f"(d[9]), "+f"(d[10]), "+f"(d[11]), "+f"(d[12]), "+f"(d[13]), "+f"(d[14]), "+f"(d[15]), "+f"(d[16]), "+f"(d[17]), "+f"(d[18]), "+f"(d[19]), "+f"(d[20]), "+f"(d[21]), "+f"(d[22]), "+f"(d[23]), "+f"(d[24]), "+f"(d[25]), "+f"(d[26]), "+f"(d[27]), "+f"(d[28]), "+f"(d[29]), "+f"(d[30]), "+f"(d[31]), "+f"(d[32]), "+f"(d[33]), "+f"(d[34]), "+f"(d[35]), "+f"(d[36]), "+f"(d[37]), "+f"(d[38]), "+f"(d[39]), "+f"(d[40]), "+f"(d[41]), "+f"(d[42]), "+f"(d[43]), "+f"(d[44]), "+f"(d[45]), "+f"(d[46]), "+f"(d[47]), "+f"(d[48]), "+f"(d[49]), "+f"(d[50]), "+f"(d[51]), "+f"(d[52]), "+f"(d[53]), "+f"(d[54]), "+f"(d[55])
        : "l"(da), "l"(db), "r"(scale_d), "n"(TA), "n"(TB));
}

__device__ __forceinline__ void send_half(const float (&a)[56], uint32_t rbuf, uint32_t rbar, int t) {
    uint32_t p[14];
#pragma unroll
    for (int i = 0; i < 14; i++) p[i] = pack2(a[28 + 2 * i], a[29 + 2 * i]);
#pragma unroll
    for (int i = 0; i < 3; i++)
        asm volatile("st.async.weak.shared::cluster.mbarrier::complete_tx::bytes.v4.b32 [%0], {%1,%2,%3,%4}, [%5];" ::"r"(rbuf + i * 2048 + t * 16),
                     "r"(p[4 * i]), "r"(p[4 * i + 1]), "r"(p[4 * i + 2]), "r"(p[4 * i + 3]), "r"(rbar) : "memory");
    asm volatile("st.async.weak.shared::cluster.mbarrier::complete_tx::bytes.v2.b32 [%0], {%1,%2}, [%3];" ::"r"(rbuf + 6144 + t * 8), "r"(p[12]), "r"(p[13]), "r"(rbar) : "memory");
}
__device__ __forceinline__ void recv_half(uint32_t (&p)[14], uint32_t buf, int t) {
#pragma unroll
    for (int i = 0; i < 3; i++)
        asm volatile("ld.shared.v4.b32 {%0,%1,%2,%3}, [%4];" : "=r"(p[4 * i]), "=r"(p[4 * i + 1]), "=r"(p[4 * i + 2]), "=r"(p[4 * i + 3]) : "r"(buf + i * 2048 + t * 16) : "memory");
    asm volatile("ld.shared.v2.b32 {%0,%1}, [%2];" : "=r"(p[12]), "=r"(p[13]) : "r"(buf + 6144 + t * 8) : "memory");
}

struct Maps { CUtensorMap x, wqkv, hst, w1, w2, xn, old_, ost, out[2]; };

__global__ void __cluster_dims__(2, 1, 1) __launch_bounds__(512, 1)
fused_kernel(const __nv_bfloat16* __restrict__ x, const __nv_bfloat16* __restrict__ wqkv, const __nv_bfloat16* __restrict__ wo,
             const __nv_bfloat16* __restrict__ b1, const __nv_bfloat16* __restrict__ b2, uint8_t* __restrict__ scr,
             const __grid_constant__ Maps mp) {
    extern __shared__ __align__(1024) uint8_t smem[];
    const uint32_t sb = smem_u32(smem);
    const uint32_t bar = sb + OFF_BAR;
    const int tid = threadIdx.x, lane = tid & 31;
    const int b = blockIdx.x, z = b & 1, c = b >> 1;
    unsigned* const ctr = reinterpret_cast<unsigned*>(scr + G_CTR);
    if (tid < 112) l2_prefetch(reinterpret_cast<const uint8_t*>(x) + (b * 112 + tid) * 128);
    const int warp = __shfl_sync(0xffffffffu, tid >> 5, 0);
    int q, j;
    if (c < 4) { q = 15; j = c; } else if (c < 36) { q = (c - 4) & 7; j = (c - 4) >> 3; } else { q = 8 + (c - 36) % 7; j = (c - 36) / 7; }
    const bool g1 = q < 14;
    const int R = q >> 1, P = (q & 1) * 4 + j;

    TS0(0);
    TG(60);
    auto qkv_load = [&](int kb) {
        mbar_expect(bar + 8 * (B_FULLQ + kb), 40960);
        const uint32_t wd = sb + OFF_B + ((WSLOT >> (4 * kb)) & 7) * 24576;
        if (kb < MC0) tma3d(wd, &mp.wqkv, (P * 56) & ~15, kb * 64, 0, bar + 8 * (B_FULLQ + kb));
        else if ((kb & 1) == z) tma3d_mc(wd, &mp.wqkv, (P * 56) & ~15, kb * 64, 0, bar + 8 * (B_FULLQ + kb));
        tma2d(sb + OFF_A + ((XSLOT >> (4 * kb)) & 7) * 16384, &mp.x, z * D_ + kb * 64, R * 128, bar + 8 * (B_FULLQ + kb));
    };
    if (tid == 384) {
#pragma unroll
        for (int i = 0; i < 7; i++) mbar_init(bar + 8 * (B_FULLQ + i), 1);
        asm volatile("fence.mbarrier_init.release.cluster;" ::: "memory");
#pragma unroll
        for (int kb = 0; kb < Q0; kb++) qkv_load(kb);
        TS(49);
    }
    auto slot = [](uint32_t r) { return r - 6 * ((r * 43) >> 8); };
    auto phase = [](uint32_t r) { return ((r * 43) >> 8) & 1; };
    const uint32_t r_o = g1 ? 16 : 0, r_u = r_o + 5;
    const uint32_t spare = bar + 8 * B_COUNT;

    if (warp < 8) {
        const int wg = warp >> 2, w4 = warp & 3, t = tid & 127, g = lane >> 2, tq = lane & 3;
        asm volatile("barrier.cluster.arrive.relaxed.aligned;" ::: "memory");
        if (Q0 * 1344 + b + tid * 128 < 9408) l2_prefetch(reinterpret_cast<const uint8_t*>(wqkv) + (Q0 * 1344 + b + tid * 128) * 128);
        asm volatile("setmaxnreg.inc.sync.aligned.u32 192;");
        TS0(44);
        bar_sync_id(8 + wg, 256);
        float a1[56];
        const int frow = (g1 ? q : 0) * 128 + wg * 64 + w4 * 16 + g;
        const int orow = q * 128 + wg * 64 + w4 * 16 + g;
        uint32_t bl, bh;
        const uint64_t dA = mkdesc(sb + OFF_A + wg * 8192, 16, 1024, 1);
        const uint64_t dH = mkdesc(sb + OFF_B, 1792, 128, 0);
        const uint64_t dU = mkdesc(sb + OFF_B, 128, 1024, 0);
        auto release = [&](uint32_t a) { mbar_arrive_if0(a, lane); };
        auto g1_wait = [&](uint32_t r) { mbar_wait(bar + 8 * (B_FULL + r % 6), g1 ? (r / 6) & 1 : 1); TS0(64 + r); };
        auto g1_free = [&](uint32_t r) { mbar_arrive_if0(bar + 8 * (B_EMPTY + r % 6), lane | !g1); };
        auto g1_mma = [&](uint32_t s) {
            wg_fence();
#pragma unroll
            for (int k = 0; k < 4; k++) wgmma_m64n112k16<1, 1>(a1, dA + s * 1024 + k * 128, dH + s * 896 + k * 224, 1);
            wg_commit();
        };
        {
            float aq0[28], aq1[28], aq2[28];
            const uint64_t dW = mkdesc(sb + OFF_B + (P & 1) * 16, 16, 1024, 1);
            uint32_t xf[2][4][4];
            const uint32_t xa = sb + OFF_A + wg * 8192 + (w4 * 16 + (lane & 15)) * 128;
            auto wait_x = [&](int kb) { mbar_wait(bar + 8 * (B_FULLQ + kb), 0); TS0(170 + kb); };
            auto load_x = [&](int kb) {
#pragma unroll
                for (int k = 0; k < 4; k++)
                    ldsm4(xa + ((XSLOT >> (4 * kb)) & 7) * 16384 + (((2 * k + (lane >> 4)) ^ (lane & 7)) << 4), xf[kb & 1][k]);
            };
            auto qkv_mma = [&](int kb, int k) {
                const uint32_t (&f)[4] = xf[kb & 1][k];
                const uint64_t d = dW + ((WSLOT >> (4 * kb)) & 7) * 1536 + k * 128;
                const int sc = (k > 0) | (kb > 0);
                wgmma_m64n56k16_rs<1>(aq0, f[0], f[1], f[2], f[3], d, sc);
                wgmma_m64n56k16_rs<1>(aq1, f[0], f[1], f[2], f[3], d + 512, sc);
                wgmma_m64n56k16_rs<1>(aq2, f[0], f[1], f[2], f[3], d + 1024, sc);
            };
#pragma unroll
            for (int kb = 0; kb < 7; kb++) {
                wait_x(kb); load_x(kb);
                wg_fence();
#pragma unroll
                for (int k = 0; k < 4; k++) qkv_mma(kb, k);
                wg_commit();
                if (kb == 0) asm volatile("barrier.cluster.wait.aligned;" ::: "memory");
                if (kb == 1) { bl = ldg_u16(b1 + frow); bh = ldg_u16(b1 + frow + 8); }
                if (kb > 0) { wg_wait<1>(); release(bar + 8 * (B_EMPTYQ + kb - 1)); }
                if (kb == 1 || kb == 2)
                    asm volatile("{\n.reg .pred p;\nsetp.eq.u32 p, %1, 0;\n@p mbarrier.arrive.shared::cluster.b64 _, [%0];\n}"
                                 ::"r"(mapa(bar + 8 * (B_EMPTYQ + kb - 1), z ^ 1)), "r"(lane) : "memory");
            }
            TS0(2);
            asm volatile("" : "+r"(bl), "+r"(bh)::"memory");
#pragma unroll
            for (int i = 0; i < 56; i++) a1[i] = i < 28 ? bf_lo((i & 2) ? bh : bl) : 0.f;
            pin(a1);
            g1_wait(0);
            g1_mma(0);
            wg_wait<1>();
            pin(aq0); pin(aq1); pin(aq2);
            release(bar + 8 * (B_EMPTYQ + 6));
            TS0(3);
            g1_wait(1);
            g1_mma(1);
            mbar_wait(bar + 8 * B_AUX, 0);
            const int row = wg * 64 + w4 * 16;
            float2 sl, sh;
            asm volatile("ld.shared.v2.f32 {%0,%1}, [%2];" : "=f"(sl.x), "=f"(sl.y) : "r"(sb + OFF_STATS + (row + g) * 16 + z * 8) : "memory");
            asm volatile("ld.shared.v2.f32 {%0,%1}, [%2];" : "=f"(sh.x), "=f"(sh.y) : "r"(sb + OFF_STATS + (row + g + 8) * 16 + z * 8) : "memory");
            bar_sync<1, 256>();
            const uint32_t so = (row + (lane & 15)) * 112 + (lane >> 4) * 16;
            auto put = [&](const float (&a)[28], int sec, uint32_t dst) {
                uint32_t p[14];
#pragma unroll
                for (int n = 0; n < 7; n++) {
                    const float2 cs = *reinterpret_cast<const float2*>(smem + OFF_CS + sec * 224 + n * 32 + tq * 8);
                    p[2 * n] = pack2(fmaf(a[4 * n], sl.x, sl.y * cs.x), fmaf(a[4 * n + 1], sl.x, sl.y * cs.y));
                    p[2 * n + 1] = pack2(fmaf(a[4 * n + 2], sh.x, sh.y * cs.x), fmaf(a[4 * n + 3], sh.x, sh.y * cs.y));
                }
#pragma unroll
                for (int n = 0; n < 3; n++) stsm4(dst + so + n * 32, p[4 * n], p[4 * n + 1], p[4 * n + 2], p[4 * n + 3]);
                stsm2(dst + (row + (lane & 15)) * 112 + 96, p[12], p[13]);
            };
            put(aq1, 1, sb + OFF_K + 896);
            wg_wait<1>(); g1_free(0); g1_wait(2); g1_mma(2); sched_fence(sb);
            put(aq2, 2, sb + OFF_V + 896);
            wg_wait<1>(); g1_free(1); g1_wait(3); g1_mma(3); sched_fence(sb);
            __syncwarp();
            release(bar + 8 * B_QKV);
            put(aq0, 0, sb + OFF_Q);
            TS0(4);
        }
        if (!g1) {
            const int ic = (q - 14) * 8 + j * 2 + z, pp = ic >> 1, cg0 = (ic & 1) * 28 + (lane >> 3);
            uint4 v[7];
#pragma unroll
            for (int i = 0; i < 7; i++) {
                v[i] = make_uint4(0, 0, 0, 0);
                if (warp < 7) v[i] = ldg_nc(reinterpret_cast<const uint4*>(wo + (size_t)(pp * 56 + warp * 8 + (lane & 7)) * D_) + cg0 + 4 * i);
            }
#pragma unroll
            for (int i = 0; i < 7; i++) {
                const int cg = cg0 + 4 * i;
                int pos = cg % 14 + (pp >= 4 ? 6 : 0);
                if (pos >= 14) pos -= 14;
                *reinterpret_cast<uint4*>(scr + G_BIMG + (pp * 4 + cg / 14) * BLK + pos * 1024 + warp * 128 + (lane & 7) * 16) = v[i];
            }
            if (tid < 112) {
                const int id = ic * 112 + tid, rem = id % 896, kg = (rem >> 3) & 7, r = rem & 7;
                const uint32_t one = ((rem >> 6) == kg && (id < 896 || kg < 6)) ? (0x3F80u << (16 * (r & 1))) : 0u;
                reinterpret_cast<uint4*>(scr + G_IDENT)[id] = make_uint4((r >> 1) == 0 ? one : 0, (r >> 1) == 1 ? one : 0, (r >> 1) == 2 ? one : 0, (r >> 1) == 3 ? one : 0);
            }
            fence_async_global();
            bar_sync<1, 256>();
            if (tid == 0) red_release(ctr + C_WO);
        }
        __syncwarp();
        wg_wait<1>();
        g1_free(2);
        auto g1_steps = [&](uint32_t r0, uint32_t r1) {
#pragma unroll 1
            for (uint32_t r = r0; r < r1; r++) {
                const uint32_t s = slot(r);
                mbar_wait(bar + 8 * (B_FULL + s), phase(r));
                TS0(64 + r);
                g1_mma(s);
                wg_wait<1>();
                release(bar + 8 * (B_EMPTY + slot(r - 1)));
            }
        };
        g1_steps(g1 ? 4 : ATT_STEP, ATT_STEP);
        {
            uint32_t qf[2][2][4], kf[2][3][4], vf[2][3][4];
            mbar_wait(bar + 8 * B_HALO, 0);
            {
                const uint32_t qa = sb + OFF_Q + (warp * 16 + (lane & 15)) * 112 + (lane >> 4) * 16;
                const uint32_t ka = sb + OFF_K + (warp * 16 + (lane & 7)) * 112 + (lane >> 3) * 16;
                const uint32_t va = sb + OFF_V + (warp * 16 + (lane & 15)) * 112 + (lane >> 4) * 16;
#pragma unroll
                for (int hd = 0; hd < 2; hd++) {
                    ldsm4(qa + hd * 48, qf[hd][0]); ldsm4(qa + hd * 48 + 32, qf[hd][1]);
#pragma unroll
                    for (int u = 0; u < 3; u++) ldsm4(ka + hd * 48 + u * 896, kf[hd][u]);
                    ldsm4t(va + hd * 48, vf[hd][0]); ldsm4t(va + hd * 48 + 32, vf[hd][1]);
                    ldsm4t(ka + (OFF_V - OFF_K) + hd * 48 + 1792, vf[hd][2]);
                }
            }
            if (tq >= 2) { qf[0][1][2] = 0; qf[0][1][3] = 0; } else { qf[1][0][0] = 0; qf[1][0][1] = 0; }
            const bool up0 = 2 * tq > g, up1 = 2 * tq + 1 > g, edge = (R | warp) == 0;
            const uint32_t mk = (up0 ? 0xFFFFu : 0u) | (up1 ? 0xFFFF0000u : 0u);
            const float scl = 0.18898223650461362f * 1.4426950408889634f;
            wg_wait<0>();
            g1_free(ATT_STEP - 1);
            bar_sync<1, 256>();
            sched_fence(sb);
            TS0(19);
            float sc[2][3][4];
#pragma unroll
            for (int hd = 0; hd < 2; hd++)
#pragma unroll
                for (int u = 0; u < 3; u++) {
                    sc[hd][u][0] = sc[hd][u][1] = sc[hd][u][2] = sc[hd][u][3] = 0.f;
                    mma16816(sc[hd][u], qf[hd][0][0], qf[hd][0][1], qf[hd][0][2], qf[hd][0][3], kf[hd][u][0], kf[hd][u][1]);
                }
#pragma unroll
            for (int hd = 0; hd < 2; hd++)
#pragma unroll
                for (int u = 0; u < 3; u++)
                    mma16816(sc[hd][u], qf[hd][1][0], qf[hd][1][1], qf[hd][1][2], qf[hd][1][3], kf[hd][u][2], kf[hd][u][3]);
            float e[2][2][2], mx[2][2], sm[2][2];
#pragma unroll
            for (int hd = 0; hd < 2; hd++) {
                e[hd][0][0] = up0 ? (edge ? -1e30f : sc[hd][0][0]) : sc[hd][1][0];
                e[hd][0][1] = up1 ? (edge ? -1e30f : sc[hd][0][1]) : sc[hd][1][1];
                e[hd][1][0] = up0 ? sc[hd][1][2] : sc[hd][2][2];
                e[hd][1][1] = up1 ? sc[hd][1][3] : sc[hd][2][3];
                mx[hd][0] = fmaxf(e[hd][0][0], e[hd][0][1]);
                mx[hd][1] = fmaxf(e[hd][1][0], e[hd][1][1]);
            }
#pragma unroll
            for (int o = 1; o <= 2; o <<= 1)
#pragma unroll
                for (int i = 0; i < 4; i++) mx[i >> 1][i & 1] = fmaxf(mx[i >> 1][i & 1], __shfl_xor_sync(0xffffffffu, mx[i >> 1][i & 1], o));
            uint32_t pp[2][2];
#pragma unroll
            for (int i = 0; i < 4; i++) {
                float* ee = e[i >> 1][i & 1];
                const float m = mx[i >> 1][i & 1] * scl;
                pp[i >> 1][i & 1] = pack2(ex2(fmaf(ee[0], scl, -m)), ex2(fmaf(ee[1], scl, -m)));
                sm[i >> 1][i & 1] = bf_lo(pp[i >> 1][i & 1]) + bf_hi(pp[i >> 1][i & 1]);
            }
            float ov[2][4][4];
#pragma unroll
            for (int hd = 0; hd < 2; hd++)
#pragma unroll
                for (int n = 0; n < 4; n++) {
                    ov[hd][n][0] = ov[hd][n][1] = ov[hd][n][2] = ov[hd][n][3] = 0.f;
                    mma16816(ov[hd][n], pp[hd][0] & mk, 0u, pp[hd][0] & ~mk, pp[hd][1] & mk, vf[hd][n >> 1][2 * (n & 1)], vf[hd][n >> 1][2 * (n & 1) + 1]);
                }
#pragma unroll
            for (int hd = 0; hd < 2; hd++)
#pragma unroll
                for (int n = 0; n < 4; n++) mma1688(ov[hd][n], 0u, pp[hd][1] & ~mk, vf[hd][2][n]);
            sched_fence(sb);
            bar_sync<1, 256>();
            TS0(53);
            g1_wait(ATT_STEP); g1_mma(ATT_STEP % 6);
            g1_wait(ATT_STEP + 1); g1_mma((ATT_STEP + 1) % 6);
            sched_fence(sb);
#pragma unroll
            for (int o = 1; o <= 2; o <<= 1)
#pragma unroll
                for (int i = 0; i < 4; i++) sm[i >> 1][i & 1] += __shfl_xor_sync(0xffffffffu, sm[i >> 1][i & 1], o);
            const uint32_t oa = sb + OFF_OST + (warp * 16 + (lane & 15)) * 128;
            uint32_t op[16];
            op[14] = op[15] = 0;
#pragma unroll
            for (int i = 0; i < 4; i++) sm[i >> 1][i & 1] = rcp(sm[i >> 1][i & 1]);
#pragma unroll
            for (int n = 0; n < 7; n++) {
                const bool hb = n > 3 || (n == 3 && tq >= 2);
#pragma unroll
                for (int h = 0; h < 2; h++) {
                    const float r = hb ? sm[1][h] : sm[0][h];
                    const float x0 = hb ? ov[1][n >= 3 ? n - 3 : 0][2 * h] : ov[0][n <= 3 ? n : 0][2 * h];
                    const float x1 = hb ? ov[1][n >= 3 ? n - 3 : 0][2 * h + 1] : ov[0][n <= 3 ? n : 0][2 * h + 1];
                    op[2 * n + h] = pack2(x0 * r, x1 * r);
                }
            }
#pragma unroll
            for (int n = 0; n < 4; n++) stsm4(oa + (((2 * n + (lane >> 4)) ^ (lane & 7)) << 4), op[4 * n], op[4 * n + 1], op[4 * n + 2], op[4 * n + 3]);
            __syncwarp();
            release(bar + 8 * B_OST);
            TS0(20);
            bl = ldg_u16(b2 + orow); bh = ldg_u16(b2 + orow + 8);
            wg_wait<1>();
            g1_free(ATT_STEP);
        }
        g1_steps(g1 ? ATT_STEP + 2 : 16, 16);
        TS0(5);
        float a2[56];
        asm volatile("" : "+r"(bl), "+r"(bh)::"memory");
        if (z) bl = bh = 0;
#pragma unroll
        for (int i = 0; i < 56; i++) a2[i] = bf_lo((i & 2) ? bh : bl);
        auto o_issue = [&](uint32_t r) {
            const uint32_t s = slot(r);
            mbar_wait(bar + 8 * (B_FULL + s), phase(r));
            wg_fence();
#pragma unroll
            for (int k = 0; k < 4; k++) wgmma_m64n112k16<0, 1>(a2, dA + s * 1024 + k * 2, dU + s * 896 + k * 16, 1);
            wg_commit();
        };
        const uint32_t peer = z ^ 1;
        pin(a2);
        o_issue(r_o);
        wg_wait<1>();
        pin(a1);
        TS0(6);
        mbar_wait_cluster(bar + 8 * B_FREE, 0);
        if (g1) {
            release(bar + 8 * (B_EMPTY + 3));
            send_half(a1, mapa(sb + OFF_RECV1 + wg * 7168, peer), mapa(bar + 8 * (B_RECV1 + wg), peer), t);
        }
        o_issue(r_o + 1);
        TS0(7);
        if (g1) {
            uint32_t p[14];
            mbar_wait_cluster(bar + 8 * (B_RECV1 + wg), 0);
            TS0(8);
            recv_half(p, sb + OFF_RECV1 + wg * 7168, t);
#pragma unroll
            for (int i = 0; i < 14; i++) p[i] = pack2(gelu_tanh(a1[2 * i] + bf_lo(p[i])), gelu_tanh(a1[2 * i + 1] + bf_hi(p[i])));
            const uint32_t dst = sb + OFF_UST + wg * 7168 + w4 * 256 + (lane & 15) * 16;
#pragma unroll
            for (int n = 0; n < 3; n++) stsm4(dst + (2 * n + (lane >> 4)) * 1024, p[4 * n], p[4 * n + 1], p[4 * n + 2], p[4 * n + 3]);
            stsm2(dst + 6144, p[12], p[13]);
            __syncwarp();
            release(bar + 8 * (B_UST + wg));
        }
        TS0(9);
        __syncwarp();
        wg_wait<1>();
        release(bar + 8 * (B_EMPTY + slot(r_o)));
#pragma unroll 1
        for (uint32_t r = r_o + 2; r < r_u; r++) {
            o_issue(r);
            wg_wait<1>();
            release(bar + 8 * (B_EMPTY + slot(r - 1)));
        }
        wg_wait<0>();
        release(bar + 8 * (B_EMPTY + slot(r_u - 1)));
        TS0(10);
#pragma unroll 1
        for (uint32_t r = r_u; r < r_u + 14; r++) {
            const uint32_t s = slot(r);
            mbar_wait(bar + 8 * (B_FULL + s), phase(r));
            TS0(85 + r - r_u);
            wg_fence();
#pragma unroll
            for (int k = 0; k < 4; k++) wgmma_m64n112k16<1, 1>(a2, dA + s * 1024 + k * 128, dU + s * 896 + k * 16, 1);
            wg_commit();
            wg_wait<1>();
            mbar_arrive_if0(bar + 8 * (B_EMPTY + slot(r - 1)), lane | (r == r_u));
        }
        mbar_wait(bar + 8 * B_UDONE, g1 ? 0 : 1);
        wg_wait<0>();
        pin(a2);
        TS0(11);
        {
            const uint32_t rbuf = mapa(sb + OFF_RECV2 + wg * 8192 + t * 16, peer) - (z ? 0 : 2048), rbar = mapa(bar + 8 * (B_RECV2 + wg), peer);
#pragma unroll
            for (int i = 3; i >= 0; i--)
                if (i > 0 || z)
                    asm volatile("st.async.weak.shared::cluster.mbarrier::complete_tx::bytes.v4.b32 [%0], {%1,%2,%3,%4}, [%5];" ::"r"(rbuf + i * 2048),
                                 "r"(pack2(a2[24 + 8 * i], a2[25 + 8 * i])), "r"(pack2(a2[26 + 8 * i], a2[27 + 8 * i])),
                                 "r"(pack2(a2[28 + 8 * i], a2[29 + 8 * i])), "r"(pack2(a2[30 + 8 * i], a2[31 + 8 * i])), "r"(rbar) : "memory");
            mbar_wait_cluster(bar + 8 * (B_RECV2 + wg), 0);
            TS0(12);
            const uint32_t dst = sb + OFF_OUT + wg * 8192 + (w4 * 16 + (lane & 15)) * 128;
#pragma unroll
            for (int i = 0; i < 4; i++) {
                uint32_t p[4];
                asm volatile("ld.shared.v4.b32 {%0,%1,%2,%3}, [%4];" : "=r"(p[0]), "=r"(p[1]), "=r"(p[2]), "=r"(p[3]) : "r"(sb + OFF_RECV2 + wg * 8192 + i * 2048 + t * 16) : "memory");
#pragma unroll
                for (int e = 0; e < 4; e++) p[e] = pack2(a2[8 * i + 2 * e] + bf_lo(p[e]), a2[8 * i + 2 * e + 1] + bf_hi(p[e]));
                stsm4(dst + (((2 * i + (lane >> 4)) ^ (lane & 7)) << 4), p[0], p[1], p[2], p[3]);
            }
            bar_sync_id(2 + wg, 128);
            if (t == 0) {
                fence_async_smem(spare);
                tma2d_store(&mp.out[z], sb + OFF_OUT + wg * 8192, j * 112 + z * 64, q * 128 + wg * 64);
                bulk_commit();
                bulk_wait_read();
            }
        }
        TS0(13);
        TG(61);
    } else if (warp < 12) {
        asm volatile("setmaxnreg.dec.sync.aligned.u32 96;");
        const int hw = warp - 8;
        TSH(46);
        uint4 xr[7];
        {
            const uint4* px = reinterpret_cast<const uint4*>(x + (size_t)(16 * b + hw * 4 + (lane & 3)) * D_) + (lane >> 2);
#pragma unroll
            for (int i = 0; i < 7; i++) xr[i] = ldg_nc(px + 8 * i);
        }
        asm volatile("barrier.cluster.arrive.relaxed.aligned;" ::: "memory");
        {
            float v[56];
            float s = 0.f;
#pragma unroll
            for (int i = 0; i < 7; i++) {
                const uint32_t u[4] = {xr[i].x, xr[i].y, xr[i].z, xr[i].w};
#pragma unroll
                for (int e = 0; e < 4; e++) { v[8 * i + 2 * e] = bf_lo(u[e]); v[8 * i + 2 * e + 1] = bf_hi(u[e]); }
                s += ((v[8 * i] + v[8 * i + 1]) + (v[8 * i + 2] + v[8 * i + 3])) + ((v[8 * i + 4] + v[8 * i + 5]) + (v[8 * i + 6] + v[8 * i + 7]));
            }
            TSH(16);
            s += __shfl_xor_sync(0xffffffffu, s, 4); s += __shfl_xor_sync(0xffffffffu, s, 8); s += __shfl_xor_sync(0xffffffffu, s, 16);
            const float mean = s * (1.f / D_);
            float s1[4] = {0.f, 0.f, 0.f, 0.f}, s2[4] = {0.f, 0.f, 0.f, 0.f};
#pragma unroll
            for (int i = 0; i < 56; i++) { v[i] -= mean; s1[i & 3] += v[i]; s2[i & 3] = fmaf(v[i], v[i], s2[i & 3]); }
            float d1 = (s1[0] + s1[1]) + (s1[2] + s1[3]), d2 = (s2[0] + s2[1]) + (s2[2] + s2[3]);
#pragma unroll
            for (int o = 4; o <= 16; o <<= 1) { d1 += __shfl_xor_sync(0xffffffffu, d1, o); d2 += __shfl_xor_sync(0xffffffffu, d2, o); }
            d1 *= (1.f / D_); d2 *= (1.f / D_);
            const float r1 = rsqrtf(d2 + 1e-5f);
            const float r2 = rsqrtf((d2 - d1 * d1) * r1 * r1 + 1e-5f);
            const float sc = r1 * r2, of = -d1 * sc;
            const int rl = hw * 4 + (lane & 3);
            const uint32_t rot = b >= 64 ? 7 : 0;
            uint8_t* hdst = smem + OFF_A + (rl >> 3) * 1792 + (rl & 7) * 16;
#pragma unroll
            for (int i = 0; i < 7; i++) {
                const uint32_t ch = (lane >> 2) + 8 * i, sl = ch / 14;
                uint32_t pos = ch % 14 + rot;
                if (pos >= 14) pos -= 14;
                uint4 o;
                o.x = pack2(fmaf(v[8 * i], sc, of), fmaf(v[8 * i + 1], sc, of));
                o.y = pack2(fmaf(v[8 * i + 2], sc, of), fmaf(v[8 * i + 3], sc, of));
                o.z = pack2(fmaf(v[8 * i + 4], sc, of), fmaf(v[8 * i + 5], sc, of));
                o.w = pack2(fmaf(v[8 * i + 6], sc, of), fmaf(v[8 * i + 7], sc, of));
                *reinterpret_cast<uint4*>(hdst + sl * 3584 + pos * 128) = o;
            }
            if (lane < 4) *reinterpret_cast<float2*>(smem + OFF_LNST + rl * 8) = make_float2(r1, -mean * r1);
            TS(24 + hw);
            bar_sync<10, 160>();
        }
        if (b < 96) {
            const uint4* pw = reinterpret_cast<const uint4*>(wqkv + (size_t)((b / 24) * 112 + hw * 28 + (lane >> 3)) * (3 * D_) + (b % 24) * 56) + min(lane & 7, 6);
#pragma unroll
            for (int i = 0; i < 7; i++) xr[i] = ldg_nc(pw + (size_t)i * 4 * (3 * D_ / 8));
            float cs[8] = {0.f, 0.f, 0.f, 0.f, 0.f, 0.f, 0.f, 0.f};
#pragma unroll
            for (int i = 0; i < 7; i++) {
                const uint32_t u[4] = {xr[i].x, xr[i].y, xr[i].z, xr[i].w};
#pragma unroll
                for (int e = 0; e < 4; e++) { cs[2 * e] += bf_lo(u[e]); cs[2 * e + 1] += bf_hi(u[e]); }
            }
#pragma unroll
            for (int o = 8; o <= 16; o <<= 1)
#pragma unroll
                for (int e = 0; e < 8; e++) cs[e] += __shfl_xor_sync(0xffffffffu, cs[e], o);
            if (lane < 7) {
                float4* part = reinterpret_cast<float4*>(smem + OFF_CSP + hw * 224 + lane * 32);
                part[0] = make_float4(cs[0], cs[1], cs[2], cs[3]);
                part[1] = make_float4(cs[4], cs[5], cs[6], cs[7]);
            }
            bar_sync<11, 128>();
            TSH(45);
            if (hw == 3) {
                if (lane < 28) {
                    const float2* p = reinterpret_cast<const float2*>(smem + OFF_CSP) + lane;
                    float2 a = p[0];
#pragma unroll
                    for (int i = 1; i < 4; i++) { const float2 v = p[28 * i]; a.x += v.x; a.y += v.y; }
                    reinterpret_cast<float2*>(smem + OFF_CSOUT)[lane] = a;
                }
                __syncwarp();
                if (lane == 0) {
                    asm volatile("fence.proxy.async.shared::cta;" ::: "memory");
                    bulk_store(scr + G_CS + (((b % 24) & 7) * 672 + (b / 24) * 168 + ((b % 24) >> 3) * 56) * 4, sb + OFF_CSOUT, 224);
                    bulk_commit();
                    bulk_wait_all();
                    red_relaxed(ctr + C_CS + ((b % 24) & 7) * 32);
                    TS(41);
                }
            }
        }
        __syncwarp();
        asm volatile("barrier.cluster.wait.aligned;" ::: "memory");
        if (hw == 2 && lane == 0) {
            mbar_wait(bar + 8 * B_OST, 0);
            fence_async_smem(spare);
            tma2d_store(&mp.ost, sb + OFF_OST, z * 64, P * 1024 + R * 128);
            bulk_commit();
            bulk_wait_all();
            red_relaxed(ctr + C_O + q * 32);
            TS(21);
            mbar_arrive(bar + 8 * B_FREE);
            asm volatile("fence.release.sync_restrict::shared::cta.cluster;" ::: "memory");
            asm volatile("mbarrier.arrive.relaxed.cluster.shared::cluster.b64 _, [%0];" ::"r"(mapa(bar + 8 * B_FREE, z ^ 1)) : "memory");
        } else if (hw < 2 && lane == 0 && g1) {
            const int ub = 2 * q + hw, zz = ub >= 14 ? 1 : 0;
            uint8_t* ud = scr + G_BIMG + ((8 + ub) * 4 + j) * BLK;
            mbar_wait(bar + 8 * (B_UST + hw), 0);
            fence_async_smem(spare);
            bulk_store(ud + ((7 * z + 1 + 6 * zz) % 14) * 1024, sb + OFF_UST + hw * 7168 + 1024, 6144);
            bulk_store(ud + (7 * z + 6 * zz) * 1024, sb + OFF_UST + hw * 7168, 1024);
            bulk_commit();
            bulk_wait_all();
            red_relaxed(ctr + C_U + ((j * 2 + zz) * 2 + hw) * 32);
            TS(22 + hw);
            mbar_arrive(bar + 8 * B_UDONE);
        }
    } else {
        asm volatile("setmaxnreg.dec.sync.aligned.u32 32;");
        auto epoch = [&]() { mbar_wait(bar + 8 * B_EP, 0); return *reinterpret_cast<volatile unsigned*>(smem + OFF_EP); };
        auto wait_free = [&](uint32_t r, uint32_t first) {
            const uint32_t a = r < 6 ? B_EMPTYQ + ((first >> (4 * r)) & 7) : B_EMPTY + slot(r);
            mbar_wait(bar + 8 * a, r < 6 ? 0 : phase(r) ^ 1);
        };
        if (warp == 12) {
            __syncwarp();
            asm volatile("bar.arrive 8, 256;\nbar.arrive 9, 256;" ::: "memory");
            asm volatile("barrier.cluster.arrive.relaxed.aligned;" ::: "memory");
            TS(51);
            bar_sync<7, 128>();
            TS(52);
            asm volatile("barrier.cluster.wait.aligned;" ::: "memory");
            TS(48);
            if (lane == 0) {
#pragma unroll 1
                for (int kb = Q0; kb < QDEPTH; kb++) qkv_load(kb);
#pragma unroll 1
                for (int kb = QDEPTH; kb < 7; kb++) {
                    mbar_wait(bar + 8 * (B_FULLQ + kb - QDEPTH), 0);
                    if (kb >= 5) mbar_wait(bar + 8 * (B_EMPTYQ + kb - 5), 0);
                    qkv_load(kb);
                }
                TS(50);
                mbar_wait(bar + 8 * B_LNFREE, 0);
#pragma unroll 1
                for (uint32_t r = 0; r < r_o; r++) {
                    const uint32_t s = slot(r), fb = bar + 8 * (B_FULL + s);
                    wait_free(r, 0x654320u);
                    mbar_expect(fb, 16384);
                    tma3d(sb + OFF_A + s * 16384, &mp.w1, 0, z * 1024 + r * 64, 2 * q, fb);
                    TS(99 + r);
                }
#pragma unroll 1
                for (uint32_t r = r_o; r < r_u; r++) {
                    const uint32_t s = slot(r), fb = bar + 8 * (B_FULL + s);
                    if (r == r_o + 1) { poll_slow(ctr + C_O + (R * 2 + z) * 32, epoch() * 8); fence_async_global(); TS(32); }
                    wait_free(r, 0x654320u);
                    mbar_expect(fb, 16384);
                    if (r == r_o) tma2d(sb + OFF_A + s * 16384, &mp.xn, j * 112 + z * 64, q * 128, fb);
                    else tma2d(sb + OFF_A + s * 16384, &mp.old_, 0, (4 * z + r - r_o - 1) * S_ + q * 128, fb);
                    TS(99 + 16 + r - r_o);
                }
#pragma unroll 1
                for (uint32_t i = 0; i < 14; i++) {
                    const uint32_t r = r_u + i, s = slot(r), fb = bar + 8 * (B_FULL + s);
                    wait_free(r, 0x654320u);
                    mbar_expect(fb, 16384);
                    tma3d(sb + OFF_A + s * 16384, &mp.w2, 0, (14 * z + (i < 7 ? 2 * i : 2 * i - 13)) * 64, 2 * q, fb);
                    TS(99 + 21 + i);
                }
            }
        } else if (warp == 13) {
            if (lane == 0) {
#pragma unroll
                for (int i = B_EMPTYQ; i < B_EMPTY; i++) mbar_init(bar + 8 * i, i >= B_FULL ? 2 : i < B_EMPTYQ + 2 ? 16 : 8);
                asm volatile("fence.mbarrier_init.release.cluster;" ::: "memory");
            }
            __syncwarp();
            asm volatile("bar.arrive 8, 256;\nbar.arrive 9, 256;" ::: "memory");
            asm volatile("barrier.cluster.arrive.relaxed.aligned;" ::: "memory");
            bar_sync<7, 128>();
            if (lane == 0) {
                const unsigned e1 = epoch();
                auto run = [&](uint32_t r0, uint32_t n, const uint8_t* src, uint32_t stride, uint32_t ts) {
#pragma unroll 1
                    for (uint32_t r = r0; r < r0 + n; r++, src += stride) {
                        const uint32_t s = slot(r), fb = bar + 8 * (B_FULL + s);
                        wait_free(r, 0x644332u);
                        mbar_expect(fb, BLK);
                        bulk_load(sb + OFF_B + s * BLK, src, BLK, fb);
                        TS(ts + r - r0);
                    }
                };
#pragma unroll 1
                for (int ph = g1 ? 0 : 1; ph < 5; ph++) {
                    if (ph == 0) mbar_wait(bar + 8 * B_LN, 0);
                    else if (ph == 1) poll_slow(ctr + C_WO, e1 * 16);
                    else if (ph > 2) poll(ctr + C_U + ((j * 2 + z) * 2 + ph - 3) * 32, e1 * 14);
                    fence_async_global();
                    TS(ph == 0 ? 33 : ph == 3 ? 34 : ph == 4 ? 35 : 63);
                    const uint8_t* src = ph == 0 ? scr + G_HIMG + (64 * z + j) * BLK : ph == 1 ? scr + G_IDENT + z * BLK
                                                 : scr + G_BIMG + ((ph == 2 ? 4 * z : 5 + 14 * z + ph) * 4 + j) * BLK;
                    const uint32_t off = ph < 2 ? 0 : ph == 2 ? 1 : 5 + 7 * (ph - 3);
                    run(ph == 0 ? 0 : r_o + off, ph == 0 ? 16 : ph == 1 ? 1 : ph == 2 ? 4 : 7, src, ph < 3 ? 4 * BLK : 8 * BLK, 134 + (ph == 0 ? 0 : 16 + off));
                }
            }
        } else if (warp == 14) {
            if (lane == 0) {
#pragma unroll
                for (int i = B_EMPTY; i < B_AUX; i++) mbar_init(bar + 8 * i, 8);
            }
            __syncwarp();
            asm volatile("bar.arrive 8, 256;\nbar.arrive 9, 256;" ::: "memory");
            asm volatile("barrier.cluster.arrive.relaxed.aligned;" ::: "memory");
            unsigned* lnc = ctr + C_LN + 32 * (c & 7);
            const unsigned e1 = (ld_relaxed(lnc) >> 7) + 1;
            bar_sync<7, 128>();
            if (lane == 0) {
                *reinterpret_cast<volatile unsigned*>(smem + OFF_EP) = e1;
                mbar_arrive(bar + 8 * B_EP);
                TS(36);
            }
            bar_sync<10, 160>();
            if (lane == 0) {
                fence_async_smem(spare);
                TS(42);
                tma4d_store(&mp.hst, sb + OFF_A, 0, 0, b & 3, b & ~3);
                bulk_store(scr + G_STATS + 128 * b, sb + OFF_LNST, 128);
                bulk_commit();
                bulk_wait_all();
            }
            __syncwarp();
            if (lane < 8) red_relaxed(ctr + C_LN + 32 * lane);
            if (lane == 0) {
                mbar_arrive(bar + 8 * B_LNFREE);
                TS(37);
                poll(lnc, e1 * 128);
                mbar_arrive(bar + 8 * B_LN);
                fence_async_global();
                mbar_expect(bar + 8 * B_AUXL, 2048 + 2688);
                bulk_load(sb + OFF_STATS, scr + G_STATS + R * 2048, 2048, bar + 8 * B_AUXL);
                poll(ctr + C_CS + P * 32, e1 * 12);
                fence_async_global();
                bulk_load(sb + OFF_CSIN, scr + G_CS + P * 2688, 2688, bar + 8 * B_AUXL);
                TS(38);
            }
            __syncwarp();
            mbar_wait(bar + 8 * B_AUXL, 0);
            if (lane < 28) {
#pragma unroll
                for (int s = 0; s < 3; s++) {
                    const float2* p = reinterpret_cast<const float2*>(smem + OFF_CSIN) + s * 28 + lane;
                    const float2 c0 = p[0], c1 = p[84], c2 = p[168], c3 = p[252];
                    reinterpret_cast<float2*>(smem + OFF_CS)[s * 28 + lane] = make_float2((c0.x + c1.x) + (c2.x + c3.x), (c0.y + c1.y) + (c2.y + c3.y));
                }
            }
            __syncwarp();
            if (lane == 0) mbar_arrive(bar + 8 * B_AUX);
            TS(39);
        } else {
            if (lane == 0) {
                if (sb & 1023) __trap();
#pragma unroll
                for (int i = B_AUX; i < B_COUNT; i++)
                    mbar_init(bar + 8 * i, (i == B_QKV || i == B_OST) ? 8 : (i == B_FREE || i == B_UDONE) ? 2
                                           : (i == B_UST || i == B_UST + 1 || i == B_LNST || i == B_CSP) ? 4 : 1);
#pragma unroll
                for (int i = B_RECV1; i < B_UST; i++) mbar_expect(bar + 8 * i, i < B_RECV2 ? 7168 : 8192 - 2048 * z);
                asm volatile("fence.mbarrier_init.release.cluster;" ::: "memory");
            }
            __syncwarp();
            asm volatile("bar.arrive 8, 256;\nbar.arrive 9, 256;" ::: "memory");
            asm volatile("barrier.cluster.arrive.relaxed.aligned;" ::: "memory");
            asm volatile("bar.arrive 7, 128;" ::: "memory");
            if (lane == 0) {
#pragma unroll
                for (int i = 2; i < 10; i++) asm volatile("prefetch.tensormap [%0];" ::"l"(reinterpret_cast<const CUtensorMap*>(&mp) + i) : "memory");
            }
            const int me = (R * 8 + P) * 2 + z;
            mbar_wait(bar + 8 * B_QKV, 0);
            if (R == 0) {
                for (int i = lane; i < 56; i += 32) {
                    *reinterpret_cast<uint4*>(smem + OFF_K + i * 16) = make_uint4(0, 0, 0, 0);
                    *reinterpret_cast<uint4*>(smem + OFF_V + i * 16) = make_uint4(0, 0, 0, 0);
                }
                __syncwarp();
            }
            if (lane == 0) {
                if (R < 7) {
                    fence_async_smem(spare);
                    bulk_store(scr + G_HALO + me * 1792, sb + OFF_K + 128 * 112, 896);
                    bulk_store(scr + G_HALO + me * 1792 + 896, sb + OFF_V + 128 * 112, 896);
                    bulk_commit();
                    bulk_wait_all();
                    red_relaxed(ctr + C_HALO + me * 8);
                }
                if (R > 0) {
                    poll(ctr + C_HALO + (me - 16) * 8, epoch());
                    fence_async_global();
                    mbar_expect(bar + 8 * B_HALO, 1792);
                    bulk_load(sb + OFF_K, scr + G_HALO + (me - 16) * 1792, 896, bar + 8 * B_HALO);
                    bulk_load(sb + OFF_V, scr + G_HALO + (me - 16) * 1792 + 896, 896, bar + 8 * B_HALO);
                } else {
                    mbar_arrive(bar + 8 * B_HALO);
                }
                TS(40);
            }
        }
    }
}

typedef CUresult (*EncodeFn)(CUtensorMap*, CUtensorMapDataType, cuuint32_t, void*, const cuuint64_t*, const cuuint64_t*, const cuuint32_t*,
                             const cuuint32_t*, CUtensorMapInterleave, CUtensorMapSwizzle, CUtensorMapL2promotion, CUtensorMapFloatOOBfill);

void encode(EncodeFn fn, CUtensorMap* m, const void* p, int rank, const cuuint64_t* dims, const cuuint64_t* strides, const cuuint32_t* box, bool swz) {
    const cuuint32_t es[4] = {1, 1, 1, 1};
    fn(m, CU_TENSOR_MAP_DATA_TYPE_BFLOAT16, rank, const_cast<void*>(p), dims, strides, box, es, CU_TENSOR_MAP_INTERLEAVE_NONE,
       swz ? CU_TENSOR_MAP_SWIZZLE_128B : CU_TENSOR_MAP_SWIZZLE_NONE, CU_TENSOR_MAP_L2_PROMOTION_L2_128B, CU_TENSOR_MAP_FLOAT_OOB_FILL_NONE);
}

}

extern "C" void kernel_launch(void* const* d_in, const int* in_sizes, int n_in, void* d_out, int out_size) {
    const __nv_bfloat16* x = (const __nv_bfloat16*)d_in[0];
    const __nv_bfloat16* wqkv = (const __nv_bfloat16*)d_in[1];
    const __nv_bfloat16* wo = (const __nv_bfloat16*)d_in[2];
    const __nv_bfloat16* w1 = (const __nv_bfloat16*)d_in[4];
    const __nv_bfloat16* b1 = (const __nv_bfloat16*)d_in[5];
    const __nv_bfloat16* w2 = (const __nv_bfloat16*)d_in[6];
    const __nv_bfloat16* b2 = (const __nv_bfloat16*)d_in[7];

    void* fp = nullptr;
    cudaDriverEntryPointQueryResult qr;
    cudaGetDriverEntryPoint("cuTensorMapEncodeTiled", &fp, cudaEnableDefault, &qr);
    EncodeFn fn = (EncodeFn)fp;
    void* sp = nullptr;
    cudaGetSymbolAddress(&sp, g_scratch);
    uint8_t* scr = (uint8_t*)sp;
    void *o = scr + G_O, *himg = scr + G_HIMG;

    Maps mp;
    { cuuint64_t d[2] = {896, 1024}, s[1] = {1792}; cuuint32_t bx[2] = {64, 128}; encode(fn, &mp.x, x, 2, d, s, bx, true); }
    { cuuint64_t d[3] = {448, 448, 3}, s[2] = {2688, 896}; cuuint32_t bx[3] = {64, 64, 3}; encode(fn, &mp.wqkv, wqkv, 3, d, s, bx, true); }
    { cuuint64_t d[3] = {64, 2048, 28}, s[2] = {3584, 128}; cuuint32_t bx[3] = {64, 64, 2}; encode(fn, &mp.w1, w1, 3, d, s, bx, true); }
    { cuuint64_t d[3] = {64, 1792, 32}, s[2] = {4096, 128}; cuuint32_t bx[3] = {64, 64, 2}; encode(fn, &mp.w2, w2, 3, d, s, bx, true); }
    { cuuint64_t d[4] = {64, 28, 4, 128}, s[3] = {128, 3584, BLK}; cuuint32_t bx[4] = {64, 28, 1, 4}; encode(fn, &mp.hst, himg, 4, d, s, bx, false); }
    { cuuint64_t d[2] = {448, 2048}, s[1] = {896}; cuuint32_t bx[2] = {64, 128}; encode(fn, &mp.xn, x, 2, d, s, bx, true); }
    { cuuint64_t d[2] = {64, 8 * 2048}, s[1] = {128}; cuuint32_t bx[2] = {64, 128}; encode(fn, &mp.old_, o, 2, d, s, bx, true); }
    { cuuint64_t d[2] = {128, 8 * 1024}, s[1] = {256}; cuuint32_t bx[2] = {64, 128}; encode(fn, &mp.ost, o, 2, d, s, bx, true); }
    { cuuint64_t d[2] = {448, 2048}, s[1] = {896}; cuuint32_t bx[2] = {64, 64}; encode(fn, &mp.out[0], d_out, 2, d, s, bx, true); }
    { cuuint64_t d[2] = {448, 2048}, s[1] = {896}; cuuint32_t bx[2] = {48, 64}; encode(fn, &mp.out[1], d_out, 2, d, s, bx, true); }

    cudaFuncSetAttribute(fused_kernel, cudaFuncAttributeMaxDynamicSharedMemorySize, SMEM_BYTES);
    fused_kernel<<<128, 512, SMEM_BYTES>>>(x, wqkv, wo, b1, b2, scr, mp);
}
```

```cpp
#include <cuda_runtime.h>
#include <cuda.h>
#include <cuda_bf16.h>
#include <stdint.h>

namespace {

constexpr int S_ = 2048, D_ = 448;
constexpr uint32_t BLK = 14336;

constexpr uint32_t G_HIMG = 0;
constexpr uint32_t G_BIMG = G_HIMG + 32 * 4 * BLK;
constexpr uint32_t G_O = G_BIMG + 36 * 4 * BLK;
constexpr uint32_t G_STATS = G_O + 8 * S_ * 128;
constexpr uint32_t G_CS = G_STATS + S_ * 16;
constexpr uint32_t G_HALO = G_CS + 8 * 7 * 1536;
constexpr uint32_t G_CTR = G_HALO + 128 * 3584;
constexpr uint32_t G_END = G_CTR + 1312 * 4;
__device__ __align__(1024) uint8_t g_scratch[G_END];

constexpr int C_LN = 0, C_WO = 256, C_O = 288, C_U = 800;

#define TSX(sel, id)
#define TS(id)
#define TS0(id)
#define TSH(id)
#define TG(id)

#define POLL_NS 200
#define QDEPTH 3
#define DLY1 1200
#define DLY2 1800
#define GATHER 5
#define PFW 0
#define PF_N 0
#define PF_T0 2800
#define PF_DT 320
#define ROTM 6
constexpr uint32_t OFF_A = 0;
constexpr uint32_t OFF_B = 98304;
constexpr uint32_t OFF_Q = 184320, OFF_K = 198656, OFF_V = 213888;
constexpr uint32_t OFF_OST = OFF_Q, OFF_RECV2 = OFF_Q, OFF_RECV1 = OFF_Q + 16384, OFF_UST = OFF_Q + 30720, OFF_OUT = OFF_Q + 16384;
constexpr uint32_t OFF_LNX = 221184, OFF_CSP = OFF_LNX + 512;
constexpr uint32_t OFF_STATS = 229376;
constexpr uint32_t OFF_CS = OFF_STATS + 1088;
constexpr uint32_t OFF_LNST = OFF_CS + 672;
constexpr uint32_t OFF_EP = OFF_LNST + 128;
constexpr uint32_t OFF_BAR = OFF_EP + 16;
constexpr uint32_t OFF_TS = OFF_BAR + 8 * 42;
constexpr uint32_t SMEM_BYTES = OFF_TS;

enum : int {
    B_FULLQ = 0, B_LNIN = 7, B_EMPTYQ = 8, B_FULL = 15, B_EMPTY = 21, B_AUX = 27, B_QKV = 28, B_HALO = 29, B_FREE = 30,
    B_RECV1 = 31, B_RECV2 = 33, B_UST = 35, B_EP = 37, B_OST = 38, B_LNFREE = 39, B_LN = 40, B_UDONE = 41, B_COUNT = 42
};
constexpr uint32_t XSLOT = 0x5432154u;
constexpr uint32_t WSLOT = 0x3421034u;
#define ATT_STEP 10

__device__ __forceinline__ uint32_t smem_u32(const void* p) { return (uint32_t)__cvta_generic_to_shared(p); }
__device__ __forceinline__ void mbar_init(uint32_t a, int c) { asm volatile("mbarrier.init.shared::cta.b64 [%0], %1;" ::"r"(a), "r"(c) : "memory"); }
__device__ __forceinline__ void mbar_expect(uint32_t a, uint32_t b) { asm volatile("mbarrier.arrive.expect_tx.shared::cta.b64 _, [%0], %1;" ::"r"(a), "r"(b) : "memory"); }
__device__ __forceinline__ void mbar_arrive(uint32_t a) { asm volatile("mbarrier.arrive.shared::cta.b64 _, [%0];" ::"r"(a) : "memory"); }
__device__ __forceinline__ void mbar_arrive_if0(uint32_t a, uint32_t sel) {
    asm volatile("{\n.reg .pred p;\nsetp.eq.u32 p, %1, 0;\n@p mbarrier.arrive.shared::cta.b64 _, [%0];\n}" ::"r"(a), "r"(sel) : "memory");
}
__device__ __forceinline__ void mbar_wait(uint32_t a, uint32_t parity) {
    asm volatile("{\n.reg .pred p;\nW0:\nmbarrier.try_wait.parity.shared::cta.b64 p, [%0], %1;\n@!p bra W0;\n}\n" ::"r"(a), "r"(parity) : "memory");
}
__device__ __forceinline__ void mbar_wait_cluster(uint32_t a, uint32_t parity) {
    asm volatile("{\n.reg .pred p;\nW0:\nmbarrier.try_wait.parity.acquire.cluster.shared::cta.b64 p, [%0], %1;\n@!p bra W0;\n}\n" ::"r"(a), "r"(parity) : "memory");
}
__device__ __forceinline__ void mbar_watch(uint32_t a) {
    asm volatile(
        "{\n.reg .pred p;\n.reg .u32 n;\nmov.u32 n, 0;\n"
        "W0:\nmbarrier.try_wait.parity.shared::cta.b64 p, [%0], 0;\n@p bra W1;\n"
        "add.u32 n, n, 1;\nsetp.lt.u32 p, n, 4194304;\n@p bra W0;\ntrap;\nW1:\n}\n" ::"r"(a) : "memory");
}
__device__ __forceinline__ bool elect() {
    uint32_t r;
    asm volatile("{\n.reg .pred p;\nelect.sync _|p, 0xffffffff;\nselp.u32 %0, 1, 0, p;\n}" : "=r"(r));
    return r;
}
__device__ __forceinline__ uint32_t mapa(uint32_t a, uint32_t cta) { uint32_t r; asm("mapa.shared::cluster.u32 %0, %1, %2;" : "=r"(r) : "r"(a), "r"(cta)); return r; }
__device__ __forceinline__ void tma2d(uint32_t dst, const CUtensorMap* m, int c0, int c1, uint32_t bar) {
    asm volatile("cp.async.bulk.tensor.2d.shared::cluster.global.mbarrier::complete_tx::bytes [%0], [%1, {%3, %4}], [%2];" ::"r"(dst), "l"(m), "r"(bar), "r"(c0), "r"(c1) : "memory");
}
__device__ __forceinline__ void tma3d(uint32_t dst, const CUtensorMap* m, int c0, int c1, int c2, uint32_t bar) {
    asm volatile("cp.async.bulk.tensor.3d.shared::cluster.global.mbarrier::complete_tx::bytes [%0], [%1, {%3, %4, %5}], [%2];" ::"r"(dst), "l"(m), "r"(bar), "r"(c0), "r"(c1), "r"(c2) : "memory");
}
__device__ __forceinline__ void tma3d_mc(uint32_t dst, const CUtensorMap* m, int c0, int c1, int c2, uint32_t bar) {
    asm volatile("cp.async.bulk.tensor.3d.shared::cluster.global.mbarrier::complete_tx::bytes.multicast::cluster [%0], [%1, {%3, %4, %5}], [%2], %6;"
                 ::"r"(dst), "l"(m), "r"(bar), "r"(c0), "r"(c1), "r"(c2), "h"((uint16_t)3) : "memory");
}
__device__ __forceinline__ void tma2d_store(const CUtensorMap* m, uint32_t src, int c0, int c1) {
    asm volatile("cp.async.bulk.tensor.2d.global.shared::cta.bulk_group [%0, {%2, %3}], [%1];" ::"l"(m), "r"(src), "r"(c0), "r"(c1) : "memory");
}
__device__ __forceinline__ void tma4d_store(const CUtensorMap* m, uint32_t src, int c0, int c1, int c2, int c3) {
    asm volatile("cp.async.bulk.tensor.4d.global.shared::cta.bulk_group [%0, {%2, %3, %4, %5}], [%1];" ::"l"(m), "r"(src), "r"(c0), "r"(c1), "r"(c2), "r"(c3) : "memory");
}
__device__ __forceinline__ void bulk_load(uint32_t dst, const void* src, uint32_t bytes, uint32_t bar) {
    asm volatile("cp.async.bulk.shared::cluster.global.mbarrier::complete_tx::bytes [%0], [%1], %2, [%3];" ::"r"(dst), "l"(src), "r"(bytes), "r"(bar) : "memory");
}
__device__ __forceinline__ void bulk_store(void* dst, uint32_t src, uint32_t bytes) {
    asm volatile("cp.async.bulk.global.shared::cta.bulk_group [%0], [%1], %2;" ::"l"(dst), "r"(src), "r"(bytes) : "memory");
}
__device__ __forceinline__ void bulk_commit() { asm volatile("cp.async.bulk.commit_group;" ::: "memory"); }
__device__ __forceinline__ void bulk_wait_all() { asm volatile("cp.async.bulk.wait_group 0;" ::: "memory"); }
__device__ __forceinline__ void bulk_wait_read() { asm volatile("cp.async.bulk.wait_group.read 0;" ::: "memory"); }
__device__ __forceinline__ void l2_prefetch(const void* p) { asm volatile("prefetch.global.L2 [%0];" ::"l"(p)); }
__device__ __forceinline__ void fence_async_smem() { asm volatile("fence.proxy.async.shared::cta;" ::: "memory"); }
__device__ __forceinline__ void fence_async_global() { asm volatile("fence.proxy.async.global;" ::: "memory"); }
__device__ __forceinline__ void red_relaxed(unsigned* p) { asm volatile("red.relaxed.gpu.global.add.u32 [%0], 1;" ::"l"(p) : "memory"); }
__device__ __forceinline__ unsigned ld_relaxed(const unsigned* p) { unsigned v; asm volatile("ld.relaxed.gpu.global.u32 %0, [%1];" : "=r"(v) : "l"(p) : "memory"); return v; }
__device__ __forceinline__ bool ctr_done(unsigned v, unsigned target) { return ((v - target) & 0x1FFFFFFu) == 0; }
__device__ __forceinline__ void poll(const unsigned* p, unsigned target) { while (!ctr_done(ld_relaxed(p), target)) {} }
__device__ __forceinline__ void poll_slow(const unsigned* p, unsigned target) { while (!ctr_done(ld_relaxed(p), target)) __nanosleep(POLL_NS); }
__device__ __forceinline__ void cell_put(void* p, uint32_t a, uint32_t b, uint32_t tag) {
    asm volatile("st.relaxed.gpu.global.v4.b32 [%0], {%1, %3, %2, %3};" ::"l"(p), "r"(a), "r"(b), "r"(tag) : "memory");
}
__device__ __forceinline__ uint32_t cell_get(const void* p, uint32_t& a, uint32_t& b, uint32_t tag) {
    uint32_t t0, t1;
    asm volatile("ld.relaxed.gpu.global.v4.b32 {%0, %1, %2, %3}, [%4];" : "=r"(a), "=r"(t0), "=r"(b), "=r"(t1) : "l"(p) : "memory");
    return (t0 ^ tag) | (t1 ^ tag);
}
template <int ID, int N> __device__ __forceinline__ void bar_sync() { asm volatile("bar.sync %0, %1;" ::"n"(ID), "n"(N) : "memory"); }
__device__ __forceinline__ void bar_sync_id(int id, int n) { asm volatile("bar.sync %0, %1;" ::"r"(id), "r"(n) : "memory"); }
__device__ __forceinline__ uint32_t clock32() { uint32_t c; asm volatile("mov.u32 %0, %%clock;" : "=r"(c)::"memory"); return c; }
__device__ __forceinline__ void wg_fence() { asm volatile("wgmma.fence.sync.aligned;" ::: "memory"); }
__device__ __forceinline__ void wg_commit() { asm volatile("wgmma.commit_group.sync.aligned;" ::: "memory"); }
template <int N> __device__ __forceinline__ void wg_wait() { asm volatile("wgmma.wait_group.sync.aligned %0;" ::"n"(N) : "memory"); }
template <int N> __device__ __forceinline__ void pin(float (&a)[N]) {
#pragma unroll
    for (int i = 0; i < N; i++) asm volatile("" : "+f"(a[i])::"memory");
}
__device__ __forceinline__ uint32_t ldg_u16(const void* p) {
    uint32_t v;
    asm volatile("ld.global.nc.u16 %0, [%1];" : "=r"(v) : "l"(p) : "memory");
    return v;
}
__device__ __forceinline__ uint32_t pack2(float lo, float hi) { uint32_t r; asm("cvt.rn.bf16x2.f32 %0, %1, %2;" : "=r"(r) : "f"(hi), "f"(lo)); return r; }
__device__ __forceinline__ float bf_lo(uint32_t v) { return __uint_as_float(v << 16); }
__device__ __forceinline__ float bf_hi(uint32_t v) { return __uint_as_float(v & 0xFFFF0000u); }
__device__ __forceinline__ void stsm4(uint32_t a, uint32_t r0, uint32_t r1, uint32_t r2, uint32_t r3) {
    asm volatile("stmatrix.sync.aligned.m8n8.x4.shared.b16 [%0], {%1, %2, %3, %4};" ::"r"(a), "r"(r0), "r"(r1), "r"(r2), "r"(r3) : "memory");
}
__device__ __forceinline__ void stsm2(uint32_t a, uint32_t r0, uint32_t r1) {
    asm volatile("stmatrix.sync.aligned.m8n8.x2.shared.b16 [%0], {%1, %2};" ::"r"(a), "r"(r0), "r"(r1) : "memory");
}
__device__ __forceinline__ void ldsm4(uint32_t a, uint32_t (&r)[4]) {
    asm volatile("ldmatrix.sync.aligned.m8n8.x4.shared.b16 {%0, %1, %2, %3}, [%4];" : "=r"(r[0]), "=r"(r[1]), "=r"(r[2]), "=r"(r[3]) : "r"(a) : "memory");
}
__device__ __forceinline__ void ldsm4t(uint32_t a, uint32_t (&r)[4]) {
    asm volatile("ldmatrix.sync.aligned.m8n8.x4.trans.shared.b16 {%0, %1, %2, %3}, [%4];" : "=r"(r[0]), "=r"(r[1]), "=r"(r[2]), "=r"(r[3]) : "r"(a) : "memory");
}
__device__ __forceinline__ void mma16816(float (&c)[4], uint32_t a0, uint32_t a1, uint32_t a2, uint32_t a3, uint32_t b0, uint32_t b1) {
    asm volatile("mma.sync.aligned.m16n8k16.row.col.f32.bf16.bf16.f32 {%0,%1,%2,%3}, {%4,%5,%6,%7}, {%8,%9}, {%0,%1,%2,%3};"
                 : "+f"(c[0]), "+f"(c[1]), "+f"(c[2]), "+f"(c[3]) : "r"(a0), "r"(a1), "r"(a2), "r"(a3), "r"(b0), "r"(b1));
}
__device__ __forceinline__ void mma1688(float (&c)[4], uint32_t a0, uint32_t a1, uint32_t b0) {
    asm volatile("mma.sync.aligned.m16n8k8.row.col.f32.bf16.bf16.f32 {%0,%1,%2,%3}, {%4,%5}, {%6}, {%0,%1,%2,%3};"
                 : "+f"(c[0]), "+f"(c[1]), "+f"(c[2]), "+f"(c[3]) : "r"(a0), "r"(a1), "r"(b0));
}
__device__ __forceinline__ uint32_t desc_lo(uint32_t addr, uint32_t lbo) { return ((addr & 0x3FFFF) >> 4) | ((lbo >> 4) << 16); }
constexpr uint32_t H_SW = (1024 >> 4) | (1u << 30), H_H = 128 >> 4, H_U = 1024 >> 4;
__device__ __forceinline__ float ex2(float x) { float r; asm("ex2.approx.ftz.f32 %0, %1;" : "=f"(r) : "f"(x)); return r; }
__device__ __forceinline__ float rsq(float x) { float r; asm("rsqrt.approx.ftz.f32 %0, %1;" : "=f"(r) : "f"(x)); return r; }
__device__ __forceinline__ float rcp(float x) { float r; asm("rcp.approx.ftz.f32 %0, %1;" : "=f"(r) : "f"(x)); return r; }
__device__ __forceinline__ float gelu_tanh(float x) {
    float y = x * fmaf(x * x, 0.0356774081363f, 0.7978845608029f), t;
    asm("tanh.approx.f32 %0, %1;" : "=f"(t) : "f"(y));
    float hx = 0.5f * x;
    return fmaf(hx, t, hx);
}

template <uint32_t HB>
__device__ __forceinline__ void wgmma_n56_rs(float (&d)[28], const uint32_t (&a)[4], uint32_t lb, int scale_d) {
    asm volatile("{\n.reg .pred p;\n.reg .b64 db;\nsetp.ne.b32 p, %33, 0;\nmov.b64 db, {%32, %34};\n"
        "wgmma.mma_async.sync.aligned.m64n56k16.f32.bf16.bf16 "
        "{%0, %1, %2, %3, %4, %5, %6, %7, %8, %9, %10, %11, %12, %13, %14, %15, %16, %17, %18, %19, %20, %21, %22, %23, %24, %25, %26, %27}, "
        "{%28, %29, %30, %31}, db, p, 1, 1, 1;\n}\n"
        : "+f"(d[0]), "+f"(d[1]), "+f"(d[2]), "+f"(d[3]), "+f"(d[4]), "+f"(d[5]), "+f"(d[6]), "+f"(d[7]), "+f"(d[8]), "+f"(d[9]), "+f"(d[10]), "+f"(d[11]), "+f"(d[12]), "+f"(d[13]), "+f"(d[14]), "+f"(d[15]), "+f"(d[16]), "+f"(d[17]), "+f"(d[18]), "+f"(d[19]), "+f"(d[20]), "+f"(d[21]), "+f"(d[22]), "+f"(d[23]), "+f"(d[24]), "+f"(d[25]), "+f"(d[26]), "+f"(d[27])
        : "r"(a[0]), "r"(a[1]), "r"(a[2]), "r"(a[3]), "r"(lb), "r"(scale_d), "n"(HB));
}
template <int TA, uint32_t HA, uint32_t HB>
__device__ __forceinline__ void wgmma_n112(float (&d)[56], uint32_t la, uint32_t lb) {
    asm volatile("{\n.reg .b64 da, db;\nmov.b64 da, {%56, %59};\nmov.b64 db, {%57, %60};\n"
        "wgmma.mma_async.sync.aligned.m64n112k16.f32.bf16.bf16 "
        "{%0, %1, %2, %3, %4, %5, %6, %7, %8, %9, %10, %11, %12, %13, %14, %15, %16, %17, %18, %19, %20, %21, %22, %23, %24, %25, %26, %27, %28, %29, %30, %31, %32, %33, %34, %35, %36, %37, %38, %39, %40, %41, %42, %43, %44, %45, %46, %47, %48, %49, %50, %51, %52, %53, %54, %55}, "
        "da, db, 1, 1, 1, %58, 1;\n}\n"
        : "+f"(d[0]), "+f"(d[1]), "+f"(d[2]), "+f"(d[3]), "+f"(d[4]), "+f"(d[5]), "+f"(d[6]), "+f"(d[7]), "+f"(d[8]), "+f"(d[9]), "+f"(d[10]), "+f"(d[11]), "+f"(d[12]), "+f"(d[13]), "+f"(d[14]), "+f"(d[15]), "+f"(d[16]), "+f"(d[17]), "+f"(d[18]), "+f"(d[19]), "+f"(d[20]), "+f"(d[21]), "+f"(d[22]), "+f"(d[23]), "+f"(d[24]), "+f"(d[25]), "+f"(d[26]), "+f"(d[27]), "+f"(d[28]), "+f"(d[29]), "+f"(d[30]), "+f"(d[31]), "+f"(d[32]), "+f"(d[33]), "+f"(d[34]), "+f"(d[35]), "+f"(d[36]), "+f"(d[37]), "+f"(d[38]), "+f"(d[39]), "+f"(d[40]), "+f"(d[41]), "+f"(d[42]), "+f"(d[43]), "+f"(d[44]), "+f"(d[45]), "+f"(d[46]), "+f"(d[47]), "+f"(d[48]), "+f"(d[49]), "+f"(d[50]), "+f"(d[51]), "+f"(d[52]), "+f"(d[53]), "+f"(d[54]), "+f"(d[55])
        : "r"(la), "r"(lb), "n"(TA), "n"(HA), "n"(HB));
}

__device__ __forceinline__ void send_half(const float (&a)[56], uint32_t rbuf, uint32_t rbar, int t) {
    uint32_t p[14];
#pragma unroll
    for (int i = 0; i < 14; i++) p[i] = pack2(a[28 + 2 * i], a[29 + 2 * i]);
#pragma unroll
    for (int i = 0; i < 3; i++)
        asm volatile("st.async.weak.shared::cluster.mbarrier::complete_tx::bytes.v4.b32 [%0], {%1,%2,%3,%4}, [%5];" ::"r"(rbuf + i * 2048 + t * 16),
                     "r"(p[4 * i]), "r"(p[4 * i + 1]), "r"(p[4 * i + 2]), "r"(p[4 * i + 3]), "r"(rbar) : "memory");
    asm volatile("st.async.weak.shared::cluster.mbarrier::complete_tx::bytes.v2.b32 [%0], {%1,%2}, [%3];" ::"r"(rbuf + 6144 + t * 8), "r"(p[12]), "r"(p[13]), "r"(rbar) : "memory");
}
__device__ __forceinline__ void recv_half(uint32_t (&p)[14], uint32_t buf, int t) {
#pragma unroll
    for (int i = 0; i < 3; i++)
        asm volatile("ld.shared.v4.b32 {%0,%1,%2,%3}, [%4];" : "=r"(p[4 * i]), "=r"(p[4 * i + 1]), "=r"(p[4 * i + 2]), "=r"(p[4 * i + 3]) : "r"(buf + i * 2048 + t * 16) : "memory");
    asm volatile("ld.shared.v2.b32 {%0,%1}, [%2];" : "=r"(p[12]), "=r"(p[13]) : "r"(buf + 6144 + t * 8) : "memory");
}

struct Maps { CUtensorMap xl, x, wqkv, hst, w1, w2, xn, old_, ost, out[2], wo; };

__global__ void __cluster_dims__(2, 1, 1) __launch_bounds__(512, 1)
fused_kernel(const __nv_bfloat16* __restrict__ x, const __nv_bfloat16* __restrict__ wqkv,
             const __nv_bfloat16* __restrict__ b1, const __nv_bfloat16* __restrict__ b2, uint8_t* __restrict__ scr,
             const __nv_bfloat16* __restrict__ w1, const __grid_constant__ Maps mp, const __nv_bfloat16* __restrict__ w2) {
    extern __shared__ __align__(1024) uint8_t smem[];
    const uint32_t sb = smem_u32(smem);
    const uint32_t bar = sb + OFF_BAR;
    const int tid = threadIdx.x, lane = tid & 31;
    const int b = blockIdx.x, z = b & 1, c = b >> 1;
    unsigned* const ctr = reinterpret_cast<unsigned*>(scr + G_CTR);
    if (tid < 112) l2_prefetch(reinterpret_cast<const uint8_t*>(x) + (b * 112 + tid) * 128);
    const int wline = (tid & 127) * 128 + b;
    const bool wfirst = ((wline / 1344) & ~ROTM) == 0;
    if (PFW && (tid >> 7) == 1 && wline < 9408 && wfirst) l2_prefetch(reinterpret_cast<const uint8_t*>(wqkv) + wline * 128);
    const uint32_t t_in = clock32();
    TS0(0);
    TG(60);
    const int warp = __shfl_sync(0xffffffffu, tid >> 5, 0);
    int q, j;
    if (c < 4) { q = 15; j = c; } else if (c < 36) { q = (c - 4) & 7; j = (c - 4) >> 3; } else { q = 8 + (c - 36) % 7; j = (c - 36) / 7; }
    const bool g1 = q < 14;
    const int R = q < 8 ? q : q == 15 ? 2 : q < 10 ? q - 8 : q - 7, P = (q >> 3) * 4 + j;
    auto krow = [&](int kb) { const int k = kb + (R & ROTM); return (k >= 7 ? k - 7 : k) * 64; };
    auto x_load = [&](int kb) {
        mbar_expect(bar + 8 * (B_FULLQ + kb), 40960);
        tma2d(sb + OFF_A + ((XSLOT >> (4 * kb)) & 7) * 16384, &mp.x, z * D_ + krow(kb), R * 128, bar + 8 * (B_FULLQ + kb));
    };
    if (warp == 12 && elect()) {
#pragma unroll
        for (int i = B_FULLQ; i < B_EMPTYQ; i++) mbar_init(bar + 8 * i, 1);
        mbar_expect(bar + 8 * B_LNIN, BLK);
        tma3d(sb + OFF_A, &mp.xl, 0, 16 * b, 0, bar + 8 * B_LNIN);
        x_load(0);
        TS(49);
    }
    if (warp == 13 && elect()) {
#pragma unroll
        for (int i = B_EMPTYQ; i < B_COUNT; i++)
            mbar_init(bar + 8 * i, i < B_FULL ? (i < B_EMPTYQ + 2 ? 2 : 1) * (i - B_EMPTYQ == (R & ~ROTM) ? 9 : 8)
                                   : (i < B_EMPTY || i == B_FREE || i == B_UDONE) ? 2 : (i < B_AUX || i == B_QKV || i == B_OST) ? 8
                                   : (i == B_UST || i == B_UST + 1 || i == B_AUX || i == B_HALO) ? 4 : 1);
#pragma unroll
        for (int i = B_RECV1; i < B_UST; i++) mbar_expect(bar + 8 * i, i < B_RECV2 ? 7168 : 8192 - 2048 * z);
    }
    asm volatile("fence.mbarrier_init.release.cluster;" ::: "memory");
    __syncwarp();
    asm volatile("barrier.cluster.arrive.relaxed.aligned;\nbarrier.cluster.wait.aligned;" ::: "memory");
    auto slot = [](uint32_t r) { return r - 6 * ((r * 43) >> 8); };
    auto phase = [](uint32_t r) { return ((r * 43) >> 8) & 1; };
    const uint32_t r_o = g1 ? 16 : 0, r_u = r_o + 5;
    auto epoch = [&]() { mbar_wait(bar + 8 * B_EP, 0); return *reinterpret_cast<volatile unsigned*>(smem + OFF_EP); };

    if (warp < 8) {
        const int wg = warp >> 2, w4 = warp & 3, t = tid & 127, g = lane >> 2, tq = lane & 3;
        asm volatile("setmaxnreg.inc.sync.aligned.u32 192;");
        const int frow = (g1 ? q : 0) * 128 + wg * 64 + w4 * 16 + g;
        uint32_t bl = ldg_u16(b1 + frow), bh = ldg_u16(b1 + frow + 8);
        uint32_t xa[4];
#pragma unroll
        for (int k = 0; k < 4; k++) xa[k] = sb + OFF_A + (warp * 16 + (lane & 15)) * 128 + (((2 * k + (lane >> 4)) ^ (lane & 7)) << 4);
        {
            const int rg = warp & 1, jq = warp >> 1;
            uint32_t r[4][4], la[4], ha[4], ex = sb + OFF_LNX + (rg * 8 + g) * 32;
#pragma unroll
            for (int i = 0; i < 4; i++) {
                const int cg = 14 * jq + 4 * i + ((lane >> 3) & (i < 3 ? 3 : 1));
                la[i] = sb + OFF_A + (cg >> 3) * 2048 + rg * 1024 + (lane & 7) * 128 + (((cg ^ lane) & 7) << 4);
                int pos = 4 * i + (lane >> 3) + (b >= 64 ? 7 : 0);
                if (pos >= 14) pos -= 14;
                ha[i] = sb + OFF_A + jq * 3584 + rg * 1792 + (lane & 7) * 16 + pos * 128;
                asm volatile("" : "+r"(la[i]), "+r"(ha[i]), "+r"(xa[i]), "+r"(ex));
            }
            TS0(46);
            mbar_wait(bar + 8 * B_LNIN, 0);
            TS0(16);
#pragma unroll
            for (int i = 0; i < 4; i++) ldsm4(la[i], r[i]);
            float rs[4] = {0.f, 0.f, 0.f, 0.f}, v[28];
#pragma unroll
            for (int i = 0; i < 3; i++) mma16816(rs, r[i][0], r[i][1], r[i][2], r[i][3], 0x3F803F80u, 0x3F803F80u);
            mma1688(rs, r[3][0], r[3][1], 0x3F803F80u);
            const float mq = (rs[0] + rs[2]) * (1.f / 112);
#pragma unroll
            for (int n = 0; n < 14; n++) { v[2 * n] = bf_lo(r[n >> 2][n & 3]) - mq; v[2 * n + 1] = bf_hi(r[n >> 2][n & 3]) - mq; }
#pragma unroll
            for (int n = 0; n < 28; n++) rs[n & 3] = n < 4 ? v[n] * v[n] : fmaf(v[n], v[n], rs[n & 3]);
            float m2 = (rs[0] + rs[1]) + (rs[2] + rs[3]);
            m2 += __shfl_xor_sync(0xffffffffu, m2, 1);
            m2 += __shfl_xor_sync(0xffffffffu, m2, 2);
            asm volatile("st.shared.v2.f32 [%0], {%1, %2};" ::"r"(ex + jq * 8), "f"(mq), "f"(m2) : "memory");
            bar_sync<1, 256>();
            float4 e0, e1;
            asm volatile("ld.shared.v4.f32 {%0,%1,%2,%3}, [%4];" : "=f"(e0.x), "=f"(e0.y), "=f"(e0.z), "=f"(e0.w) : "r"(ex) : "memory");
            asm volatile("ld.shared.v4.f32 {%0,%1,%2,%3}, [%4];" : "=f"(e1.x), "=f"(e1.y), "=f"(e1.z), "=f"(e1.w) : "r"(ex + 16) : "memory");
            const float mean = 0.25f * ((e0.x + e0.z) + (e1.x + e1.z));
            const float d0 = e0.x - mean, d1 = e0.z - mean, d2 = e1.x - mean, d3 = e1.z - mean;
            const float var = ((e0.y + e0.w) + (e1.y + e1.w)) * (1.f / D_) + 0.25f * (fmaf(d0, d0, d1 * d1) + fmaf(d2, d2, d3 * d3));
            const float r1 = rsq(var + 1e-5f);
            const float sc = r1 * rsq(var * r1 * r1 + 1e-5f), of = (mq - mean) * sc;
#pragma unroll
            for (int n = 0; n < 14; n++) r[n >> 2][n & 3] = pack2(fmaf(v[2 * n], sc, of), fmaf(v[2 * n + 1], sc, of));
#pragma unroll
            for (int i = 0; i < 3; i++) stsm4(ha[i], r[i][0], r[i][1], r[i][2], r[i][3]);
            stsm2(ha[3], r[3][0], r[3][1]);
            *reinterpret_cast<float2*>(smem + OFF_LNST + (rg * 8 + g) * 8) = make_float2(r1, -mean);
            TS0(24);
            asm volatile("bar.arrive 10, 288;" ::: "memory");
        }
        float a1[56];
        const int orow = q * 128 + wg * 64 + w4 * 16 + g;
        uint32_t qp[14];
        const uint32_t dA = desc_lo(sb + OFF_A + wg * 8192, 16), dH = desc_lo(sb + OFF_B, 1792), dU = desc_lo(sb + OFF_B, 128);
        auto release = [&](uint32_t a) { mbar_arrive_if0(a, lane); };
        auto sched_fence = [&]() { mbar_wait(bar + 8 * B_LNIN, 0); };
        auto g1_wait = [&](uint32_t r) { mbar_wait(bar + 8 * (g1 ? B_FULL + r % 6 : B_LNIN), g1 && ((r / 6) & 1)); TS0(64 + r); };
        auto g1_free = [&](uint32_t r) { mbar_arrive_if0(bar + 8 * (B_EMPTY + r % 6), lane | !g1); };
        auto g1_mma = [&](uint32_t s) {
            wg_fence();
#pragma unroll
            for (int k = 0; k < 4; k++) wgmma_n112<1, H_SW, H_H>(a1, dA + s * 1024 + k * 128, dH + s * 896 + k * 224);
            wg_commit();
        };
        auto g1_step = [&](uint32_t r) { g1_wait(r); g1_mma(r % 6); wg_wait<1>(); g1_free(r - 1); sched_fence(); };
        {
            float aq0[28], aq1[28], aq2[28];
            const uint32_t dW = desc_lo(sb + OFF_B + (P & 1) * 16, 16);
            uint32_t xf[2][4][4];
            const uint32_t rq = mapa(bar + 8 * (B_EMPTYQ - 1), z ^ 1);
            auto stage = [&](int kb, uint32_t (&f)[4][4]) {
                TS0(178 + kb);
                mbar_wait(bar + 8 * (B_FULLQ + kb), 0);
                TS0(170 + kb);
                const uint32_t sh = 4 * kb;
#pragma unroll
                for (int k = 0; k < 4; k++) ldsm4(xa[k] + ((XSLOT >> sh) & 7) * 16384, f[k]);
                const uint32_t d0 = dW + ((WSLOT >> sh) & 7) * 1536;
                wg_fence();
#pragma unroll
                for (int k = 0; k < 4; k++) {
                    const uint32_t d = d0 + (k >> 1) * 768 + (k & 1) * 128;
                    const int sc = k > 0 ? 1 : kb;
                    wgmma_n56_rs<H_SW>(aq0, f[k], d, sc);
                    wgmma_n56_rs<H_SW>(aq1, f[k], d + 256, sc);
                    wgmma_n56_rs<H_SW>(aq2, f[k], d + 512, sc);
                }
                wg_commit();
                wg_wait<1>();
                mbar_arrive_if0(bar + 8 * (B_EMPTYQ + kb - 1), lane | (kb < 1));
                asm volatile("{\n.reg .pred p;\nsetp.eq.u32 p, %1, 0;\n@p mbarrier.arrive.shared::cluster.b64 _, [%0];\n}"
                             ::"r"(rq + 8 * kb), "r"(lane | ((uint32_t)(kb - 1) > 1)) : "memory");
            };
            stage(0, xf[0]);
#pragma unroll 1
            for (int kb = 1; kb < 7; kb += 2) {
                stage(kb, xf[1]);
                stage(kb + 1, xf[0]);
            }
            TS0(2);
            asm volatile("" : "+r"(bl), "+r"(bh)::"memory");
#pragma unroll
            for (int i = 0; i < 56; i++) a1[i] = i < 28 ? bf_lo((i & 2) ? bh : bl) : 0.f;
            pin(a1);
            g1_wait(0);
            g1_mma(0);
            wg_wait<1>();
            pin(aq0); pin(aq1); pin(aq2);
            release(bar + 8 * (B_EMPTYQ + 6));
            TS0(3);
            mbar_wait(bar + 8 * B_AUX, 0);
            const float nl = *reinterpret_cast<const float*>(smem + OFF_STATS + 68 + (warp * 16 + g) * 8);
            const float nh = *reinterpret_cast<const float*>(smem + OFF_STATS + 132 + (warp * 16 + g) * 8);
            auto center = [&](const float (&a)[28], int sec, uint32_t (&p)[14]) {
#pragma unroll
                for (int n = 0; n < 7; n++) {
                    const float2 cs = *reinterpret_cast<const float2*>(smem + OFF_CS + sec * 224 + n * 32 + tq * 8);
                    p[2 * n] = pack2(fmaf(nl, cs.x, a[4 * n]), fmaf(nl, cs.y, a[4 * n + 1]));
                    p[2 * n + 1] = pack2(fmaf(nh, cs.x, a[4 * n + 2]), fmaf(nh, cs.y, a[4 * n + 3]));
                }
            };
            auto put = [&](uint32_t dst) {
                dst += (warp * 16 + 8 + (lane & 15)) * 112;
#pragma unroll
                for (int n = 0; n < 3; n++) stsm4(dst + (lane >> 4) * 16 + n * 32, qp[4 * n], qp[4 * n + 1], qp[4 * n + 2], qp[4 * n + 3]);
                stsm2(dst + 96, qp[12], qp[13]);
            };
            center(aq1, 1, qp);
            mbar_wait(bar + 8 * (B_EMPTYQ + 5), 0);
            put(sb + OFF_K);
            g1_step(1);
            center(aq2, 2, qp);
            put(sb + OFF_V);
            __syncwarp();
            release(bar + 8 * B_QKV);
            g1_step(2);
            center(aq0, 0, qp);
            TS0(4);
        }
        auto g1_steps = [&](uint32_t r0, uint32_t r1) {
#pragma unroll 1
            for (uint32_t r = r0; r < r1; r++) {
                const uint32_t s = slot(r);
                mbar_wait(bar + 8 * (B_FULL + s), phase(r));
                TS0(64 + r);
                g1_mma(s);
                wg_wait<1>();
                release(bar + 8 * (B_EMPTY + slot(r - 1)));
            }
        };
        g1_steps(g1 ? 3 : ATT_STEP, ATT_STEP);
        {
            uint32_t kf[2][3][4], vf[2][3][4];
            const bool up0 = 2 * tq > g, up1 = 2 * tq + 1 > g, edge = (R | warp) == 0;
            float rk[2][2], fs[2][2];
#pragma unroll
            for (int i = 0; i < 4; i++) {
                const float* st = reinterpret_cast<const float*>(smem + OFF_STATS) + (warp * 16 + (i >> 1) * 8) * 2;
                rk[i >> 1][i & 1] = st[(2 * tq + (i & 1) + (((i & 1) ? up1 : up0) ? 0 : 8)) * 2];
                fs[i >> 1][i & 1] = rk[i >> 1][i & 1] * (st[(g + 8) * 2] * (0.18898223650461362f * 1.4426950408889634f));
            }
            mbar_wait(bar + 8 * B_HALO, 0);
            {
                const uint32_t ka = sb + OFF_K + (warp * 16 + (lane & 7)) * 112 + (lane >> 3) * 16;
                const uint32_t va = sb + OFF_V + (warp * 16 + (lane & 15)) * 112 + (lane >> 4) * 16;
#pragma unroll
                for (int hd = 0; hd < 2; hd++) {
#pragma unroll
                    for (int u = 0; u < 3; u++) ldsm4(ka + hd * 48 + u * 896, kf[hd][u]);
                    ldsm4t(va + hd * 48, vf[hd][0]); ldsm4t(va + hd * 48 + 32, vf[hd][1]);
                    ldsm4t(ka + (OFF_V - OFF_K) + hd * 48 + 1792, vf[hd][2]);
                }
            }
            const uint32_t q0l = tq < 2 ? qp[6] : 0, q0h = tq < 2 ? qp[7] : 0, q1l = tq < 2 ? 0 : qp[6], q1h = tq < 2 ? 0 : qp[7];
            const uint32_t mk = (up0 ? 0xFFFFu : 0u) | (up1 ? 0xFFFF0000u : 0u);
            wg_wait<0>();
            g1_free(ATT_STEP - 1);
            sched_fence();
            TS0(19);
            float sc[2][3][4];
#pragma unroll
            for (int u = 0; u < 3; u++) {
#pragma unroll
                for (int i = 0; i < 8; i++) sc[i >> 2][u][i & 3] = 0.f;
                mma16816(sc[0][u], qp[0], qp[1], qp[2], qp[3], kf[0][u][0], kf[0][u][1]);
                mma16816(sc[1][u], q1l, q1h, qp[8], qp[9], kf[1][u][0], kf[1][u][1]);
            }
#pragma unroll
            for (int u = 0; u < 3; u++) {
                mma16816(sc[0][u], qp[4], qp[5], q0l, q0h, kf[0][u][2], kf[0][u][3]);
                mma16816(sc[1][u], qp[10], qp[11], qp[12], qp[13], kf[1][u][2], kf[1][u][3]);
            }
            float e[2][2][2], mx[2][2], sm[2][2];
#pragma unroll
            for (int hd = 0; hd < 2; hd++) {
                e[hd][0][0] = (up0 ? sc[hd][0][0] : sc[hd][1][0]) * fs[0][0];
                e[hd][0][1] = (up1 ? sc[hd][0][1] : sc[hd][1][1]) * fs[0][1];
                e[hd][1][0] = (up0 ? sc[hd][1][2] : sc[hd][2][2]) * fs[1][0];
                e[hd][1][1] = (up1 ? sc[hd][1][3] : sc[hd][2][3]) * fs[1][1];
                if (edge && up0) e[hd][0][0] = -1e30f;
                if (edge && up1) e[hd][0][1] = -1e30f;
                mx[hd][0] = fmaxf(e[hd][0][0], e[hd][0][1]);
                mx[hd][1] = fmaxf(e[hd][1][0], e[hd][1][1]);
            }
#pragma unroll
            for (int o = 1; o <= 2; o <<= 1)
#pragma unroll
                for (int i = 0; i < 4; i++) mx[i >> 1][i & 1] = fmaxf(mx[i >> 1][i & 1], __shfl_xor_sync(0xffffffffu, mx[i >> 1][i & 1], o));
            uint32_t pp[2][2];
#pragma unroll
            for (int i = 0; i < 4; i++) {
                const float p0 = ex2(e[i >> 1][i & 1][0] - mx[i >> 1][i & 1]), p1 = ex2(e[i >> 1][i & 1][1] - mx[i >> 1][i & 1]);
                pp[i >> 1][i & 1] = pack2(p0 * rk[i & 1][0], p1 * rk[i & 1][1]);
                sm[i >> 1][i & 1] = p0 + p1;
            }
            float ov[2][4][4];
#pragma unroll
            for (int hd = 0; hd < 2; hd++)
#pragma unroll
                for (int n = 0; n < 4; n++) {
                    ov[hd][n][0] = ov[hd][n][1] = ov[hd][n][2] = ov[hd][n][3] = 0.f;
                    mma16816(ov[hd][n], pp[hd][0] & mk, 0u, pp[hd][0] & ~mk, pp[hd][1] & mk, vf[hd][n >> 1][2 * (n & 1)], vf[hd][n >> 1][2 * (n & 1) + 1]);
                }
#pragma unroll
            for (int hd = 0; hd < 2; hd++)
#pragma unroll
                for (int n = 0; n < 4; n++) mma1688(ov[hd][n], 0u, pp[hd][1] & ~mk, vf[hd][2][n]);
            sched_fence();
            bar_sync<1, 256>();
            TS0(53);
            g1_wait(ATT_STEP); g1_mma(ATT_STEP % 6);
            sched_fence();
#pragma unroll
            for (int o = 1; o <= 2; o <<= 1)
#pragma unroll
                for (int i = 0; i < 4; i++) sm[i >> 1][i & 1] += __shfl_xor_sync(0xffffffffu, sm[i >> 1][i & 1], o);
            const uint32_t oa = sb + OFF_OST + (warp * 16 + (lane & 15)) * 128;
            uint32_t op[16];
            op[14] = op[15] = 0;
#pragma unroll
            for (int i = 0; i < 4; i++) sm[i >> 1][i & 1] = rcp(sm[i >> 1][i & 1]);
            asm volatile("" : "+f"(sm[0][0]), "+f"(sm[0][1]), "+f"(sm[1][0]), "+f"(sm[1][1])::"memory");
            g1_step(ATT_STEP + 1);
#pragma unroll
            for (int n = 0; n < 7; n++) {
                const bool hb = n > 3 || (n == 3 && tq >= 2);
#pragma unroll
                for (int h = 0; h < 2; h++) {
                    const float r = hb ? sm[1][h] : sm[0][h];
                    const float x0 = hb ? ov[1][n >= 3 ? n - 3 : 0][2 * h] : ov[0][n <= 3 ? n : 0][2 * h];
                    const float x1 = hb ? ov[1][n >= 3 ? n - 3 : 0][2 * h + 1] : ov[0][n <= 3 ? n : 0][2 * h + 1];
                    op[2 * n + h] = pack2(x0 * r, x1 * r);
                }
            }
#pragma unroll
            for (int n = 0; n < 4; n++) stsm4(oa + (((2 * n + (lane >> 4)) ^ (lane & 7)) << 4), op[4 * n], op[4 * n + 1], op[4 * n + 2], op[4 * n + 3]);
            __syncwarp();
            release(bar + 8 * B_OST);
            TS0(20);
            bl = ldg_u16(b2 + orow); bh = ldg_u16(b2 + orow + 8);
        }
        g1_steps(g1 ? ATT_STEP + 2 : 16, 16);
        TS0(5);
        const uint32_t peer = z ^ 1;
        mbar_wait_cluster(bar + 8 * B_FREE, 0);
        wg_wait<0>();
        pin(a1);
        TS0(6);
        if (g1) {
            send_half(a1, mapa(sb + OFF_RECV1 + wg * 7168, peer), mapa(bar + 8 * (B_RECV1 + wg), peer), t);
            release(bar + 8 * (B_EMPTY + 3));
            uint32_t p[14];
            TS0(7);
            mbar_wait_cluster(bar + 8 * (B_RECV1 + wg), 0);
            TS0(8);
            recv_half(p, sb + OFF_RECV1 + wg * 7168, t);
#pragma unroll
            for (int i = 0; i < 14; i++) p[i] = pack2(gelu_tanh(a1[2 * i] + bf_lo(p[i])), gelu_tanh(a1[2 * i + 1] + bf_hi(p[i])));
            const uint32_t dst = sb + OFF_UST + wg * 7168 + w4 * 256 + (lane & 15) * 16;
#pragma unroll
            for (int n = 0; n < 3; n++) stsm4(dst + (2 * n + (lane >> 4)) * 1024, p[4 * n], p[4 * n + 1], p[4 * n + 2], p[4 * n + 3]);
            stsm2(dst + 6144, p[12], p[13]);
            __syncwarp();
            release(bar + 8 * (B_UST + wg));
        }
        TS0(9);
        float a2[56];
        {
            const uint32_t s = slot(r_o);
            mbar_wait(bar + 8 * (B_FULL + s), phase(r_o));
            uint32_t xr[4][4];
#pragma unroll
            for (int k = 0; k < 4; k++) ldsm4(xa[k] + s * 16384, xr[k]);
            if (z) bl = bh = xr[3][0] = xr[3][1] = xr[3][2] = xr[3][3] = 0;
#pragma unroll
            for (int i = 0; i < 56; i++) {
                a2[i] = bf_lo((i & 2) ? bh : bl);
                if (i < 32) a2[i] += (i & 1) ? bf_hi(xr[i >> 3][(i >> 1) & 3]) : bf_lo(xr[i >> 3][(i >> 1) & 3]);
            }
            pin(a2);
        }
#pragma unroll 1
        for (uint32_t r = r_o + 1; r < r_u; r++) {
            const uint32_t s = slot(r);
            mbar_wait(bar + 8 * (B_FULL + s), phase(r));
            TS0(64 + 16 + r - r_o);
            wg_fence();
#pragma unroll
            for (int k = 0; k < 4; k++) wgmma_n112<0, H_SW, H_U>(a2, dA + s * 1024 + k * 2, dU + s * 896 + k * 16);
            wg_commit();
            wg_wait<1>();
            release(bar + 8 * (B_EMPTY + slot(r - 1)));
        }
        wg_wait<0>();
        release(bar + 8 * (B_EMPTY + slot(r_u - 1)));
        TS0(10);
#pragma unroll 1
        for (uint32_t r = r_u; r < r_u + 14; r++) {
            const uint32_t s = slot(r);
            mbar_wait(bar + 8 * (B_FULL + s), phase(r));
            TS0(85 + r - r_u);
            wg_fence();
#pragma unroll
            for (int k = 0; k < 4; k++) wgmma_n112<1, H_SW, H_U>(a2, dA + s * 1024 + k * 128, dU + s * 896 + k * 16);
            wg_commit();
            wg_wait<1>();
            mbar_arrive_if0(bar + 8 * (B_EMPTY + slot(r - 1)), lane | (r == r_u));
        }
        mbar_wait(bar + 8 * B_UDONE, g1 ? 0 : 1);
        wg_wait<0>();
        pin(a2);
        TS0(11);
        {
            const uint32_t rbuf = mapa(sb + OFF_RECV2 + wg * 8192 + t * 16, peer) - (z ? 0 : 2048), rbar = mapa(bar + 8 * (B_RECV2 + wg), peer);
#pragma unroll
            for (int i = 3; i >= 0; i--)
                if (i > 0 || z)
                    asm volatile("st.async.weak.shared::cluster.mbarrier::complete_tx::bytes.v4.b32 [%0], {%1,%2,%3,%4}, [%5];" ::"r"(rbuf + i * 2048),
                                 "r"(pack2(a2[24 + 8 * i], a2[25 + 8 * i])), "r"(pack2(a2[26 + 8 * i], a2[27 + 8 * i])),
                                 "r"(pack2(a2[28 + 8 * i], a2[29 + 8 * i])), "r"(pack2(a2[30 + 8 * i], a2[31 + 8 * i])), "r"(rbar) : "memory");
            mbar_wait_cluster(bar + 8 * (B_RECV2 + wg), 0);
            TS0(12);
            const uint32_t dst = sb + OFF_OUT + wg * 8192 + (w4 * 16 + (lane & 15)) * 128;
#pragma unroll
            for (int i = 0; i < 4; i++) {
                uint32_t p[4];
                asm volatile("ld.shared.v4.b32 {%0,%1,%2,%3}, [%4];" : "=r"(p[0]), "=r"(p[1]), "=r"(p[2]), "=r"(p[3]) : "r"(sb + OFF_RECV2 + wg * 8192 + i * 2048 + t * 16) : "memory");
#pragma unroll
                for (int e = 0; e < 4; e++) p[e] = pack2(a2[8 * i + 2 * e] + bf_lo(p[e]), a2[8 * i + 2 * e + 1] + bf_hi(p[e]));
                stsm4(dst + (((2 * i + (lane >> 4)) ^ (lane & 7)) << 4), p[0], p[1], p[2], p[3]);
            }
            bar_sync_id(2 + wg, 128);
            if (w4 == 0 && elect()) {
                fence_async_smem();
                tma2d_store(&mp.out[z], sb + OFF_OUT + wg * 8192, j * 112 + z * 64, q * 128 + wg * 64);
                bulk_commit();
                bulk_wait_read();
            }
        }
        TS0(13);
        TG(61);
    } else if (warp < 12) {
        asm volatile("setmaxnreg.dec.sync.aligned.u32 96;");
        const int hw = warp - 8, t = tid & 127;
        while (clock32() - t_in < DLY1) {}
        if (wline < 9408 && !wfirst) l2_prefetch(reinterpret_cast<const uint8_t*>(wqkv) + wline * 128);
        uint8_t* cells = scr + G_HALO + ((R * 8 + P) * 2 + z) * 3584 + min(t, 111) * 16;
        cell_put(cells, 0, 0, 0);
        cell_put(cells + 1792, 0, 0, 0);
        const unsigned e1 = epoch();
        {
            const int st = R & ~ROTM, ch = z * 12 + lane % 12, rp = lane / 12;
            mbar_wait(bar + 8 * (B_FULLQ + st), 0);
            TSH(47);
            if (lane < 24) {
                float cs[8] = {0.f, 0.f, 0.f, 0.f, 0.f, 0.f, 0.f, 0.f};
                const uint32_t wa = sb + OFF_B + ((WSLOT >> (4 * st)) & 7) * 24576 + (hw >> 1) * 12288 + (ch >> 3) * 4096 + (hw & 1) * 2048 + rp * 1024;
#pragma unroll
                for (int r = 0; r < 8; r++) {
                    uint32_t u[4];
                    asm volatile("ld.shared.v4.b32 {%0,%1,%2,%3}, [%4];" : "=r"(u[0]), "=r"(u[1]), "=r"(u[2]), "=r"(u[3]) : "r"(wa + r * 128 + (((ch ^ r) & 7) << 4)) : "memory");
#pragma unroll
                    for (int e = 0; e < 4; e++) { cs[2 * e] += bf_lo(u[e]); cs[2 * e + 1] += bf_hi(u[e]); }
                }
                float4* part = reinterpret_cast<float4*>(smem + OFF_CSP + hw * 768 + lane * 32);
                part[0] = make_float4(cs[0], cs[1], cs[2], cs[3]);
                part[1] = make_float4(cs[4], cs[5], cs[6], cs[7]);
            }
            bar_sync<12, 128>();
            TSH(45);
            if (t < (st < 2 ? 2 : 1)) asm volatile("mbarrier.arrive.shared::cluster.b64 _, [%0];" ::"r"(mapa(bar + 8 * (B_EMPTYQ + st), z ^ t)) : "memory");
            if (t < 48 && R < 7) {
                const float2* p = reinterpret_cast<const float2*>(smem + OFF_CSP) + t;
                float2 a = p[0];
#pragma unroll
                for (int i = 1; i < 8; i++) { const float2 v = p[48 * i]; a.x += v.x; a.y += v.y; }
                cell_put(scr + G_CS + (P * 7 + R) * 1536 + (z * 48 + t) * 16, __float_as_uint(a.x), __float_as_uint(a.y), e1);
            }
            TSH(43);
        }
        mbar_wait(bar + 8 * (B_FULLQ + GATHER), 0);
        {
            const bool cw = hw < 3;
            const uint8_t* src = cw ? scr + G_CS + P * 7 * 1536 + (hw * 32 + (P & 1) * 4 + min(lane, 27)) * 16 : scr + G_STATS + (z * 1024 + R * 128 - 8) * 16;
            uint32_t a[7], d[7], bad;
            do {
                bad = 0;
#pragma unroll
                for (int i = 0; i < 7; i++) bad |= cell_get(src + (cw ? i * 1536 : max(min(lane + 32 * i, 135), R ? 0 : 8) * 16), a[i], d[i], e1);
            } while (bad);
            if (cw) {
                float2 sum = make_float2(0.f, 0.f);
#pragma unroll
                for (int i = 0; i < 7; i++) { sum.x += __uint_as_float(a[i]); sum.y += __uint_as_float(d[i]); }
                reinterpret_cast<float2*>(smem + OFF_CS)[hw * 28 + min(lane, 27)] = sum;
            } else {
#pragma unroll
                for (int i = 0; i < 5; i++) reinterpret_cast<uint2*>(smem + OFF_STATS)[min(lane + 32 * i, 135)] = make_uint2(a[i], d[i]);
            }
            __syncwarp();
            mbar_arrive_if0(bar + 8 * B_AUX, lane);
            TSH(41);
        }
        {
            uint2* kv = reinterpret_cast<uint2*>(smem + OFF_K) + min(t, 111);
            mbar_wait(bar + 8 * B_QKV, 0);
            uint2 k2 = kv[1792], v2 = kv[1792 + (OFF_V - OFF_K) / 8];
            cell_put(cells, k2.x, k2.y, e1);
            cell_put(cells + 1792, v2.x, v2.y, e1);
            k2 = v2 = make_uint2(0, 0);
            if (R > 0) while (cell_get(cells - 16 * 3584, k2.x, k2.y, e1) | cell_get(cells - 16 * 3584 + 1792, v2.x, v2.y, e1)) {}
            kv[0] = k2;
            kv[(OFF_V - OFF_K) / 8] = v2;
            __syncwarp();
            mbar_arrive_if0(bar + 8 * B_HALO, lane);
            TSH(40);
        }
        if (hw == 2) {
            if (elect()) {
                mbar_wait(bar + 8 * B_OST, 0);
                fence_async_smem();
                tma2d_store(&mp.ost, sb + OFF_OST, z * 64, P * 1024 + R * 128);
                bulk_commit();
                bulk_wait_all();
                red_relaxed(ctr + C_O + (R * 2 + (P >> 2)) * 32);
                TS(21);
                mbar_arrive(bar + 8 * B_FREE);
                asm volatile("fence.release.sync_restrict::shared::cta.cluster;" ::: "memory");
                asm volatile("mbarrier.arrive.relaxed.cluster.shared::cluster.b64 _, [%0];" ::"r"(mapa(bar + 8 * B_FREE, z ^ 1)) : "memory");
            }
        } else if (hw < 2 && g1) {
            if (elect()) {
                const int ub = 2 * q + hw, zz = ub >= 14 ? 1 : 0;
                uint8_t* ud = scr + G_BIMG + ((8 + ub) * 4 + j) * BLK;
                mbar_wait(bar + 8 * (B_UST + hw), 0);
                fence_async_smem();
                bulk_store(ud + ((7 * z + 1 + 6 * zz) % 14) * 1024, sb + OFF_UST + hw * 7168 + 1024, 6144);
                bulk_store(ud + (7 * z + 6 * zz) * 1024, sb + OFF_UST + hw * 7168, 1024);
                bulk_commit();
                bulk_wait_all();
                red_relaxed(ctr + C_U + ((j * 2 + zz) * 2 + hw) * 32);
                TS(22 + hw);
                mbar_arrive(bar + 8 * B_UDONE);
            }
        }
    } else {
        asm volatile("setmaxnreg.dec.sync.aligned.u32 32;");
        auto wait_free = [&](uint32_t r, uint32_t first) {
            const uint32_t a = r < 6 ? B_EMPTYQ + ((first >> (4 * r)) & 7) : B_EMPTY + slot(r);
            mbar_wait(bar + 8 * a, r < 6 ? 0 : phase(r) ^ 1);
        };
        if (warp == 12) {
            TS(48);
            if (elect()) {
#pragma unroll 1
                for (int kb = 0; kb < 7; kb++) {
                    if (kb == 1) while (clock32() - t_in < DLY2) {}
                    if (kb >= QDEPTH) mbar_wait(bar + 8 * (B_FULLQ + kb - QDEPTH), 0);
                    if (kb >= 5) mbar_wait(bar + 8 * (B_EMPTYQ + kb - 5), 0);
                    if (kb > 0) x_load(kb);
                    tma3d_mc(sb + OFF_B + ((WSLOT >> (4 * kb)) & 7) * 24576 + z * 12288, &mp.wqkv, (P * 56) & ~15, krow(kb) + z * 32, 0, bar + 8 * (B_FULLQ + kb));
                }
                TS(50);
                ld_relaxed(ctr + C_O + ((q & ~1) + z) * 32);
                mbar_wait(bar + 8 * B_LNFREE, 0);
                if (!g1) {
                    const int ic = (q - 14) * 8 + j * 2 + z, rot = ic >> 3;
                    mbar_wait(bar + 8 * (B_EMPTYQ + 2), 0);
                    mbar_expect(bar + 8 * B_LN, 2 * BLK);
#pragma unroll 1
                    for (int i = 0; i < 2; i++) tma3d(sb + OFF_A + i * BLK, &mp.wo, 0, (ic >> 1) * 56, (z * 2 + i) * 14, bar + 8 * B_LN);
                    mbar_wait(bar + 8 * B_LN, 0);
#pragma unroll 1
                    for (int i = 0; i < 2; i++) {
                        uint8_t* dst = scr + G_BIMG + (ic * 2 + i) * BLK;
                        bulk_store(dst + rot * 6144, sb + OFF_A + i * BLK, 8192);
                        bulk_store(dst + (rot ^ 1) * 8192, sb + OFF_A + i * BLK + 8192, 6144);
                    }
                    bulk_commit();
                    bulk_wait_all();
                    red_relaxed(ctr + C_WO);
                    TS(44);
                }
#pragma unroll 1
                for (uint32_t r = 0; r < r_o; r++) {
                    const uint32_t s = slot(r), fb = bar + 8 * (B_FULL + s);
                    wait_free(r, 0x654320u);
                    mbar_expect(fb, 16384);
                    tma3d(sb + OFF_A + s * 16384, &mp.w1, 0, z * 1024 + r * 64, 2 * q, fb);
                    TS(99 + r);
                }
#pragma unroll 1
                for (uint32_t r = r_o; r < r_u; r++) {
                    const uint32_t s = slot(r), fb = bar + 8 * (B_FULL + s);
                    if (r == r_o + 1) { poll_slow(ctr + C_O + ((q & ~1) + z) * 32, epoch() * 8); fence_async_global(); TS(32); }
                    wait_free(r, 0x654320u);
                    mbar_expect(fb, 16384);
                    if (r == r_o) tma2d(sb + OFF_A + s * 16384, &mp.xn, j * 112 + z * 64, q * 128, fb);
                    else tma2d(sb + OFF_A + s * 16384, &mp.old_, 0, (4 * z + r - r_o - 1) * S_ + q * 128, fb);
                    TS(99 + 16 + r - r_o);
                }
#pragma unroll 1
                for (uint32_t i = 0; i < 14; i++) {
                    const uint32_t r = r_u + i, s = slot(r), fb = bar + 8 * (B_FULL + s);
                    wait_free(r, 0x654320u);
                    mbar_expect(fb, 16384);
                    tma3d(sb + OFF_A + s * 16384, &mp.w2, 0, (14 * z + (i < 7 ? 2 * i : 2 * i - 13)) * 64, 2 * q, fb);
                    TS(99 + 21 + i);
                }
            }
        } else if (warp == 13) {
            if (elect()) {
                const unsigned e1 = epoch();
                ld_relaxed(ctr + C_WO);
                ld_relaxed(ctr + C_U + (j * 2 + z) * 64);
                ld_relaxed(ctr + C_U + (j * 2 + z) * 64 + 32);
                auto run = [&](uint32_t r0, uint32_t n, const uint8_t* src, uint32_t stride, uint32_t ts) {
#pragma unroll 1
                    for (uint32_t r = r0; r < r0 + n; r++, src += stride) {
                        const uint32_t s = slot(r), fb = bar + 8 * (B_FULL + s);
                        wait_free(r, 0x644332u);
                        mbar_expect(fb, BLK);
                        bulk_load(sb + OFF_B + s * BLK, src, BLK, fb);
                        TS(ts + r - r0);
                    }
                };
#pragma unroll 1
                for (int ph = g1 ? 0 : 1; ph < 4; ph++) {
                    if (ph == 0) {
                        mbar_wait(bar + 8 * B_LN, 0);
                    } else if (ph == 1) {
                        wait_free(r_o, 0x644332u);
                        mbar_arrive(bar + 8 * (B_FULL + slot(r_o)));
                        poll_slow(ctr + C_WO, e1 * 16);
                    } else {
                        poll(ctr + C_U + ((j * 2 + z) * 2 + ph - 2) * 32, e1 * 14);
                    }
                    fence_async_global();
                    TS(ph == 0 ? 33 : ph == 2 ? 34 : ph == 3 ? 35 : 63);
                    const uint8_t* src = ph == 0 ? scr + G_HIMG + (64 * z + j) * BLK : scr + G_BIMG + ((ph == 1 ? 4 * z : 6 + 14 * z + ph) * 4 + j) * BLK;
                    const uint32_t off = ph == 1 ? 1 : 7 * ph - 9;
                    run(ph == 0 ? 0 : r_o + off, ph == 0 ? 16 : ph == 1 ? 4 : 7, src, ph < 2 ? 4 * BLK : 8 * BLK, 134 + (ph == 0 ? 0 : 16 + off));
                }
            }
        } else if (warp == 14) {
            unsigned* lnc = ctr + C_LN + 32 * (c & 7);
            const unsigned e1 = (ld_relaxed(lnc) >> 7) + 1;
            if (lane == 0) {
                *reinterpret_cast<volatile unsigned*>(smem + OFF_EP) = e1;
                mbar_arrive(bar + 8 * B_EP);
                TS(36);
            }
            bar_sync<10, 288>();
            if (elect()) {
                fence_async_smem();
                TS(42);
                tma4d_store(&mp.hst, sb + OFF_A, 0, 0, b & 3, b & ~3);
                bulk_commit();
            }
            __syncwarp();
            if (lane < 16) {
                const uint2 v = reinterpret_cast<const uint2*>(smem + OFF_LNST)[lane];
                cell_put(scr + G_STATS + ((lane & 1) * 1024 + 8 * b + (lane >> 1)) * 16, v.x, v.y, e1);
            }
            bulk_wait_all();
            __syncwarp();
            if (lane < 8) red_relaxed(ctr + C_LN + 32 * lane);
            if (lane == 0) {
                mbar_arrive(bar + 8 * B_LNFREE);
                TS(37);
                if (g1) {
                    poll(lnc, e1 * 128);
                    mbar_arrive(bar + 8 * B_LN);
                }
            }
        } else {
            if (elect()) {
#pragma unroll 1
                for (int i = 2; i < 12; i++) asm volatile("prefetch.tensormap [%0];" ::"l"(reinterpret_cast<const CUtensorMap*>(&mp) + i) : "memory");
            }
            __syncwarp();
#pragma unroll 1
            for (int i = 0; i < PF_N; i++) {
                while (clock32() - t_in < PF_T0 + i * PF_DT) __nanosleep(32);
                const int k = i - 16;
                if (k >= 0) l2_prefetch(w2 + (size_t)(((b >> 6) * 14 + (k < 7 ? 2 * k : 2 * k - 13)) * 64 + (b & 63)) * S_ + lane * 64);
                else if (lane < 28) l2_prefetch(w1 + (size_t)((b >> 6) * 1024 + i * 64 + (b & 63)) * 1792 + lane * 64);
            }
            if (elect()) {
                mbar_watch(bar + 8 * B_RECV2);
                mbar_watch(bar + 8 * (B_RECV2 + 1));
            }
        }
    }
}

typedef CUresult (*EncodeFn)(CUtensorMap*, CUtensorMapDataType, cuuint32_t, void*, const cuuint64_t*, const cuuint64_t*, const cuuint32_t*,
                             const cuuint32_t*, CUtensorMapInterleave, CUtensorMapSwizzle, CUtensorMapL2promotion, CUtensorMapFloatOOBfill);

void encode(EncodeFn fn, CUtensorMap* m, const void* p, int rank, const cuuint64_t* dims, const cuuint64_t* strides, const cuuint32_t* box, bool swz) {
    const cuuint32_t es[4] = {1, 1, 1, 1};
    fn(m, CU_TENSOR_MAP_DATA_TYPE_BFLOAT16, rank, const_cast<void*>(p), dims, strides, box, es, CU_TENSOR_MAP_INTERLEAVE_NONE,
       swz ? CU_TENSOR_MAP_SWIZZLE_128B : CU_TENSOR_MAP_SWIZZLE_NONE, CU_TENSOR_MAP_L2_PROMOTION_L2_128B, CU_TENSOR_MAP_FLOAT_OOB_FILL_NONE);
}

}

extern "C" void kernel_launch(void* const* d_in, const int* in_sizes, int n_in, void* d_out, int out_size) {
    const __nv_bfloat16* x = (const __nv_bfloat16*)d_in[0];
    const __nv_bfloat16* wqkv = (const __nv_bfloat16*)d_in[1];
    const __nv_bfloat16* wo = (const __nv_bfloat16*)d_in[2];
    const __nv_bfloat16* w1 = (const __nv_bfloat16*)d_in[4];
    const __nv_bfloat16* b1 = (const __nv_bfloat16*)d_in[5];
    const __nv_bfloat16* w2 = (const __nv_bfloat16*)d_in[6];
    const __nv_bfloat16* b2 = (const __nv_bfloat16*)d_in[7];

    void* fp = nullptr;
    cudaDriverEntryPointQueryResult qr;
    cudaGetDriverEntryPoint("cuTensorMapEncodeTiled", &fp, cudaEnableDefault, &qr);
    EncodeFn fn = (EncodeFn)fp;
    void* sp = nullptr;
    cudaGetSymbolAddress(&sp, g_scratch);
    uint8_t* scr = (uint8_t*)sp;
    void *o = scr + G_O, *himg = scr + G_HIMG;

    Maps mp;
    { cuuint64_t d[3] = {64, 2048, 7}, s[2] = {896, 128}; cuuint32_t bx[3] = {64, 16, 7}; encode(fn, &mp.xl, x, 3, d, s, bx, true); }
    { cuuint64_t d[2] = {896, 1024}, s[1] = {1792}; cuuint32_t bx[2] = {64, 128}; encode(fn, &mp.x, x, 2, d, s, bx, true); }
    { cuuint64_t d[3] = {448, 448, 3}, s[2] = {2688, 896}; cuuint32_t bx[3] = {64, 32, 3}; encode(fn, &mp.wqkv, wqkv, 3, d, s, bx, true); }
    { cuuint64_t d[3] = {64, 2048, 28}, s[2] = {3584, 128}; cuuint32_t bx[3] = {64, 64, 2}; encode(fn, &mp.w1, w1, 3, d, s, bx, true); }
    { cuuint64_t d[3] = {64, 1792, 32}, s[2] = {4096, 128}; cuuint32_t bx[3] = {64, 64, 2}; encode(fn, &mp.w2, w2, 3, d, s, bx, true); }
    { cuuint64_t d[4] = {64, 28, 4, 128}, s[3] = {128, 3584, BLK}; cuuint32_t bx[4] = {64, 28, 1, 4}; encode(fn, &mp.hst, himg, 4, d, s, bx, false); }
    { cuuint64_t d[2] = {448, 2048}, s[1] = {896}; cuuint32_t bx[2] = {64, 128}; encode(fn, &mp.xn, x, 2, d, s, bx, true); }
    { cuuint64_t d[2] = {64, 8 * 2048}, s[1] = {128}; cuuint32_t bx[2] = {64, 128}; encode(fn, &mp.old_, o, 2, d, s, bx, true); }
    { cuuint64_t d[2] = {128, 8 * 1024}, s[1] = {256}; cuuint32_t bx[2] = {64, 128}; encode(fn, &mp.ost, o, 2, d, s, bx, true); }
    { cuuint64_t d[2] = {448, 2048}, s[1] = {896}; cuuint32_t bx[2] = {64, 64}; encode(fn, &mp.out[0], d_out, 2, d, s, bx, true); }
    { cuuint64_t d[2] = {448, 2048}, s[1] = {896}; cuuint32_t bx[2] = {48, 64}; encode(fn, &mp.out[1], d_out, 2, d, s, bx, true); }
    { cuuint64_t d[3] = {8, 448, 56}, s[2] = {896, 16}; cuuint32_t bx[3] = {8, 64, 14}; encode(fn, &mp.wo, wo, 3, d, s, bx, false); }

    cudaFuncSetAttribute(fused_kernel, cudaFuncAttributeMaxDynamicSharedMemorySize, SMEM_BYTES);
    fused_kernel<<<128, 512, SMEM_BYTES>>>(x, wqkv, b1, b2, scr, w1, mp, w2);
}
```

```cpp
#include <cuda_runtime.h>
#include <cuda.h>
#include <cuda_bf16.h>
#include <stdint.h>

namespace {

constexpr int S_ = 2048, D_ = 448;
constexpr uint32_t BLK = 14336;

constexpr uint32_t G_HIMG = 0;
constexpr uint32_t G_BIMG = G_HIMG + 32 * 4 * BLK;
constexpr uint32_t G_O = G_BIMG + 36 * 4 * BLK;
constexpr uint32_t G_STATS = G_O + 8 * S_ * 128;
constexpr uint32_t G_CS = G_STATS + S_ * 16;
constexpr uint32_t G_HALO = G_CS + 8 * 7 * 1536;
constexpr uint32_t G_CTR = G_HALO + 128 * 3584;
constexpr uint32_t G_END = G_CTR + 1312 * 4;
__device__ __align__(1024) uint8_t g_scratch[G_END];

constexpr int C_LN = 0, C_WO = 256, C_O = 288, C_U = 800;

#define TSX(sel, id)
#define TS(id)
#define TS0(id)
#define TSH(id)
#define TSW(id)
#define TG(id)

#define POLL_NS 200
#define QDEPTH 3
#define DLY1 1200
#define DLY2 1800
#define GATHER 5
#define PFW 0
#define PF_N 0
#define PF_T0 2800
#define PF_DT 320
#define NS1 4
#define NS2 4
#define ROTM 6
constexpr uint32_t OFF_A = 0;
constexpr uint32_t OFF_B = 98304;
constexpr uint32_t OFF_Q = 184320, OFF_K = 198656, OFF_V = 213888;
constexpr uint32_t OFF_OST = OFF_Q, OFF_RECV2 = OFF_Q, OFF_RECV1 = OFF_Q + 16384, OFF_UST = OFF_Q + 30720, OFF_OUT = OFF_Q + 16384;
constexpr uint32_t OFF_LNX = 221184, OFF_CSP = OFF_LNX + 512;
constexpr uint32_t OFF_STATS = 229376;
constexpr uint32_t OFF_CS = OFF_STATS + 1088;
constexpr uint32_t OFF_LNST = OFF_CS + 672;
constexpr uint32_t OFF_EP = OFF_LNST + 128;
constexpr uint32_t OFF_BAR = OFF_EP + 16;
constexpr uint32_t OFF_TS = OFF_BAR + 8 * 42;
constexpr uint32_t SMEM_BYTES = OFF_TS;

enum : int {
    B_FULLQ = 0, B_LNIN = 7, B_EMPTYQ = 8, B_FULL = 15, B_EMPTY = 21, B_AUX = 27, B_QKV = 28, B_HALO = 29, B_FREE = 30,
    B_RECV1 = 31, B_RECV2 = 33, B_UST = 35, B_EP = 37, B_OST = 38, B_LNFREE = 39, B_LN = 40, B_UDONE = 41, B_COUNT = 42
};
constexpr uint32_t XSLOT = 0x5432154u;
constexpr uint32_t WSLOT = 0x3421034u;
#define ATT_STEP 10

__device__ __forceinline__ uint32_t smem_u32(const void* p) { return (uint32_t)__cvta_generic_to_shared(p); }
__device__ __forceinline__ void mbar_init(uint32_t a, int c) { asm volatile("mbarrier.init.shared::cta.b64 [%0], %1;" ::"r"(a), "r"(c) : "memory"); }
__device__ __forceinline__ void mbar_expect(uint32_t a, uint32_t b) { asm volatile("mbarrier.arrive.expect_tx.shared::cta.b64 _, [%0], %1;" ::"r"(a), "r"(b) : "memory"); }
__device__ __forceinline__ void mbar_arrive(uint32_t a) { asm volatile("mbarrier.arrive.shared::cta.b64 _, [%0];" ::"r"(a) : "memory"); }
__device__ __forceinline__ void mbar_arrive_if0(uint32_t a, uint32_t sel) {
    asm volatile("{\n.reg .pred p;\nsetp.eq.u32 p, %1, 0;\n@p mbarrier.arrive.shared::cta.b64 _, [%0];\n}" ::"r"(a), "r"(sel) : "memory");
}
__device__ __forceinline__ void mbar_wait(uint32_t a, uint32_t parity) {
    asm volatile("{\n.reg .pred p;\nW0:\nmbarrier.try_wait.parity.shared::cta.b64 p, [%0], %1;\n@!p bra W0;\n}\n" ::"r"(a), "r"(parity) : "memory");
}
__device__ __forceinline__ void mbar_wait_cluster(uint32_t a, uint32_t parity) {
    asm volatile("{\n.reg .pred p;\nW0:\nmbarrier.try_wait.parity.acquire.cluster.shared::cta.b64 p, [%0], %1;\n@!p bra W0;\n}\n" ::"r"(a), "r"(parity) : "memory");
}
__device__ __forceinline__ void mbar_watch(uint32_t a) {
    asm volatile(
        "{\n.reg .pred p;\n.reg .u32 n;\nmov.u32 n, 0;\n"
        "W0:\nmbarrier.try_wait.parity.shared::cta.b64 p, [%0], 0;\n@p bra W1;\n"
        "add.u32 n, n, 1;\nsetp.lt.u32 p, n, 4194304;\n@p bra W0;\ntrap;\nW1:\n}\n" ::"r"(a) : "memory");
}
__device__ __forceinline__ bool elect() {
    uint32_t r;
    asm volatile("{\n.reg .pred p;\nelect.sync _|p, 0xffffffff;\nselp.u32 %0, 1, 0, p;\n}" : "=r"(r));
    return r;
}
__device__ __forceinline__ uint32_t mapa(uint32_t a, uint32_t cta) { uint32_t r; asm("mapa.shared::cluster.u32 %0, %1, %2;" : "=r"(r) : "r"(a), "r"(cta)); return r; }
__device__ __forceinline__ void tma2d(uint32_t dst, const CUtensorMap* m, int c0, int c1, uint32_t bar) {
    asm volatile("cp.async.bulk.tensor.2d.shared::cluster.global.mbarrier::complete_tx::bytes [%0], [%1, {%3, %4}], [%2];" ::"r"(dst), "l"(m), "r"(bar), "r"(c0), "r"(c1) : "memory");
}
__device__ __forceinline__ void tma3d(uint32_t dst, const CUtensorMap* m, int c0, int c1, int c2, uint32_t bar) {
    asm volatile("cp.async.bulk.tensor.3d.shared::cluster.global.mbarrier::complete_tx::bytes [%0], [%1, {%3, %4, %5}], [%2];" ::"r"(dst), "l"(m), "r"(bar), "r"(c0), "r"(c1), "r"(c2) : "memory");
}
__device__ __forceinline__ void tma3d_mc(uint32_t dst, const CUtensorMap* m, int c0, int c1, int c2, uint32_t bar) {
    asm volatile("cp.async.bulk.tensor.3d.shared::cluster.global.mbarrier::complete_tx::bytes.multicast::cluster [%0], [%1, {%3, %4, %5}], [%2], %6;"
                 ::"r"(dst), "l"(m), "r"(bar), "r"(c0), "r"(c1), "r"(c2), "h"((uint16_t)3) : "memory");
}
__device__ __forceinline__ void tma2d_store(const CUtensorMap* m, uint32_t src, int c0, int c1) {
    asm volatile("cp.async.bulk.tensor.2d.global.shared::cta.bulk_group [%0, {%2, %3}], [%1];" ::"l"(m), "r"(src), "r"(c0), "r"(c1) : "memory");
}
__device__ __forceinline__ void tma4d_store(const CUtensorMap* m, uint32_t src, int c0, int c1, int c2, int c3) {
    asm volatile("cp.async.bulk.tensor.4d.global.shared::cta.bulk_group [%0, {%2, %3, %4, %5}], [%1];" ::"l"(m), "r"(src), "r"(c0), "r"(c1), "r"(c2), "r"(c3) : "memory");
}
__device__ __forceinline__ void bulk_load(uint32_t dst, const void* src, uint32_t bytes, uint32_t bar) {
    asm volatile("cp.async.bulk.shared::cluster.global.mbarrier::complete_tx::bytes [%0], [%1], %2, [%3];" ::"r"(dst), "l"(src), "r"(bytes), "r"(bar) : "memory");
}
__device__ __forceinline__ void bulk_store(void* dst, uint32_t src, uint32_t bytes) {
    asm volatile("cp.async.bulk.global.shared::cta.bulk_group [%0], [%1], %2;" ::"l"(dst), "r"(src), "r"(bytes) : "memory");
}
__device__ __forceinline__ void bulk_commit() { asm volatile("cp.async.bulk.commit_group;" ::: "memory"); }
__device__ __forceinline__ void bulk_wait_all() { asm volatile("cp.async.bulk.wait_group 0;" ::: "memory"); }
__device__ __forceinline__ void bulk_wait_read() { asm volatile("cp.async.bulk.wait_group.read 0;" ::: "memory"); }
__device__ __forceinline__ void l2_prefetch(const void* p) { asm volatile("prefetch.global.L2 [%0];" ::"l"(p)); }
__device__ __forceinline__ void fence_async_smem() { asm volatile("fence.proxy.async.shared::cta;" ::: "memory"); }
__device__ __forceinline__ void fence_async_global() { asm volatile("fence.proxy.async.global;" ::: "memory"); }
__device__ __forceinline__ void red_relaxed(unsigned* p) { asm volatile("red.relaxed.gpu.global.add.u32 [%0], 1;" ::"l"(p) : "memory"); }
__device__ __forceinline__ unsigned ld_relaxed(const unsigned* p) { unsigned v; asm volatile("ld.relaxed.gpu.global.u32 %0, [%1];" : "=r"(v) : "l"(p) : "memory"); return v; }
__device__ __forceinline__ bool ctr_done(unsigned v, unsigned target) { return ((v - target) & 0x1FFFFFFu) == 0; }
__device__ __forceinline__ void poll(const unsigned* p, unsigned target) { while (!ctr_done(ld_relaxed(p), target)) {} }
__device__ __forceinline__ void poll_slow(const unsigned* p, unsigned target) { while (!ctr_done(ld_relaxed(p), target)) __nanosleep(POLL_NS); }
__device__ __forceinline__ void cell_put(void* p, uint32_t a, uint32_t b, uint32_t tag) {
    asm volatile("st.relaxed.gpu.global.v4.b32 [%0], {%1, %3, %2, %3};" ::"l"(p), "r"(a), "r"(b), "r"(tag) : "memory");
}
__device__ __forceinline__ uint32_t cell_get(const void* p, uint32_t& a, uint32_t& b, uint32_t tag) {
    uint32_t t0, t1;
    asm volatile("ld.relaxed.gpu.global.v4.b32 {%0, %1, %2, %3}, [%4];" : "=r"(a), "=r"(t0), "=r"(b), "=r"(t1) : "l"(p) : "memory");
    return (t0 ^ tag) | (t1 ^ tag);
}
template <int ID, int N> __device__ __forceinline__ void bar_sync() { asm volatile("bar.sync %0, %1;" ::"n"(ID), "n"(N) : "memory"); }
__device__ __forceinline__ void bar_sync_id(int id, int n) { asm volatile("bar.sync %0, %1;" ::"r"(id), "r"(n) : "memory"); }
__device__ __forceinline__ void gate_wait(uint32_t on) { asm volatile("{\n.reg .pred p;\nsetp.ne.u32 p, %0, 0;\n@p bar.sync 4, 256;\n}" ::"r"(on) : "memory"); }
__device__ __forceinline__ void gate_open(uint32_t off) { asm volatile("{\n.reg .pred p;\nsetp.eq.u32 p, %0, 0;\n@p bar.arrive 4, 256;\n}" ::"r"(off) : "memory"); }
__device__ __forceinline__ uint32_t clock32() { uint32_t c; asm volatile("mov.u32 %0, %%clock;" : "=r"(c)::"memory"); return c; }
__device__ __forceinline__ void wg_fence() { asm volatile("wgmma.fence.sync.aligned;" ::: "memory"); }
__device__ __forceinline__ void wg_commit() { asm volatile("wgmma.commit_group.sync.aligned;" ::: "memory"); }
template <int N> __device__ __forceinline__ void wg_wait() { asm volatile("wgmma.wait_group.sync.aligned %0;" ::"n"(N) : "memory"); }
template <int LO = 0, int HI = 56, int N> __device__ __forceinline__ void pin(float (&a)[N]) {
#pragma unroll
    for (int i = LO; i < (HI < N ? HI : N); i++) asm volatile("" : "+f"(a[i])::"memory");
}
__device__ __forceinline__ uint32_t ldg_u16(const void* p) {
    uint32_t v;
    asm volatile("ld.global.nc.u16 %0, [%1];" : "=r"(v) : "l"(p) : "memory");
    return v;
}
__device__ __forceinline__ uint32_t pack2(float lo, float hi) { uint32_t r; asm("cvt.rn.bf16x2.f32 %0, %1, %2;" : "=r"(r) : "f"(hi), "f"(lo)); return r; }
__device__ __forceinline__ float bf_lo(uint32_t v) { return __uint_as_float(v << 16); }
__device__ __forceinline__ float bf_hi(uint32_t v) { return __uint_as_float(v & 0xFFFF0000u); }
__device__ __forceinline__ void stsm4(uint32_t a, uint32_t r0, uint32_t r1, uint32_t r2, uint32_t r3) {
    asm volatile("stmatrix.sync.aligned.m8n8.x4.shared.b16 [%0], {%1, %2, %3, %4};" ::"r"(a), "r"(r0), "r"(r1), "r"(r2), "r"(r3) : "memory");
}
__device__ __forceinline__ void stsm2(uint32_t a, uint32_t r0, uint32_t r1) {
    asm volatile("stmatrix.sync.aligned.m8n8.x2.shared.b16 [%0], {%1, %2};" ::"r"(a), "r"(r0), "r"(r1) : "memory");
}
__device__ __forceinline__ void ldsm4(uint32_t a, uint32_t (&r)[4]) {
    asm volatile("ldmatrix.sync.aligned.m8n8.x4.shared.b16 {%0, %1, %2, %3}, [%4];" : "=r"(r[0]), "=r"(r[1]), "=r"(r[2]), "=r"(r[3]) : "r"(a) : "memory");
}
__device__ __forceinline__ void ldsm4t(uint32_t a, uint32_t (&r)[4]) {
    asm volatile("ldmatrix.sync.aligned.m8n8.x4.trans.shared.b16 {%0, %1, %2, %3}, [%4];" : "=r"(r[0]), "=r"(r[1]), "=r"(r[2]), "=r"(r[3]) : "r"(a) : "memory");
}
__device__ __forceinline__ void mma16816(float (&c)[4], uint32_t a0, uint32_t a1, uint32_t a2, uint32_t a3, uint32_t b0, uint32_t b1) {
    asm volatile("mma.sync.aligned.m16n8k16.row.col.f32.bf16.bf16.f32 {%0,%1,%2,%3}, {%4,%5,%6,%7}, {%8,%9}, {%0,%1,%2,%3};"
                 : "+f"(c[0]), "+f"(c[1]), "+f"(c[2]), "+f"(c[3]) : "r"(a0), "r"(a1), "r"(a2), "r"(a3), "r"(b0), "r"(b1));
}
__device__ __forceinline__ void mma1688(float (&c)[4], uint32_t a0, uint32_t a1, uint32_t b0) {
    asm volatile("mma.sync.aligned.m16n8k8.row.col.f32.bf16.bf16.f32 {%0,%1,%2,%3}, {%4,%5}, {%6}, {%0,%1,%2,%3};"
                 : "+f"(c[0]), "+f"(c[1]), "+f"(c[2]), "+f"(c[3]) : "r"(a0), "r"(a1), "r"(b0));
}
__device__ __forceinline__ uint32_t desc_lo(uint32_t addr, uint32_t lbo) { return ((addr & 0x3FFFF) >> 4) | ((lbo >> 4) << 16); }
constexpr uint32_t H_SW = (1024 >> 4) | (1u << 30), H_H = 128 >> 4, H_U = 1024 >> 4;
__device__ __forceinline__ float ex2(float x) { float r; asm("ex2.approx.ftz.f32 %0, %1;" : "=f"(r) : "f"(x)); return r; }
__device__ __forceinline__ float rsq(float x) { float r; asm("rsqrt.approx.ftz.f32 %0, %1;" : "=f"(r) : "f"(x)); return r; }
__device__ __forceinline__ float rcp(float x) { float r; asm("rcp.approx.ftz.f32 %0, %1;" : "=f"(r) : "f"(x)); return r; }
__device__ __forceinline__ float gelu_tanh(float x) {
    float y = x * fmaf(x * x, 0.0356774081363f, 0.7978845608029f), t;
    asm("tanh.approx.f32 %0, %1;" : "=f"(t) : "f"(y));
    float hx = 0.5f * x;
    return fmaf(hx, t, hx);
}

template <uint32_t HB>
__device__ __forceinline__ void wgmma_n56_rs(float (&d)[28], const uint32_t (&a)[4], uint32_t lb, int scale_d) {
    asm volatile("{\n.reg .pred p;\n.reg .b64 db;\nsetp.ne.b32 p, %33, 0;\nmov.b64 db, {%32, %34};\n"
        "wgmma.mma_async.sync.aligned.m64n56k16.f32.bf16.bf16 "
        "{%0, %1, %2, %3, %4, %5, %6, %7, %8, %9, %10, %11, %12, %13, %14, %15, %16, %17, %18, %19, %20, %21, %22, %23, %24, %25, %26, %27}, "
        "{%28, %29, %30, %31}, db, p, 1, 1, 1;\n}\n"
        : "+f"(d[0]), "+f"(d[1]), "+f"(d[2]), "+f"(d[3]), "+f"(d[4]), "+f"(d[5]), "+f"(d[6]), "+f"(d[7]), "+f"(d[8]), "+f"(d[9]), "+f"(d[10]), "+f"(d[11]), "+f"(d[12]), "+f"(d[13]), "+f"(d[14]), "+f"(d[15]), "+f"(d[16]), "+f"(d[17]), "+f"(d[18]), "+f"(d[19]), "+f"(d[20]), "+f"(d[21]), "+f"(d[22]), "+f"(d[23]), "+f"(d[24]), "+f"(d[25]), "+f"(d[26]), "+f"(d[27])
        : "r"(a[0]), "r"(a[1]), "r"(a[2]), "r"(a[3]), "r"(lb), "r"(scale_d), "n"(HB));
}
template <int TA, uint32_t HA, uint32_t HB, int O = 0>
__device__ __forceinline__ void wgmma_n112(float (&d)[56], uint32_t la, uint32_t lb, int scale_d = 1) {
    asm volatile("{\n.reg .b64 da, db;\n.reg .pred p;\nsetp.ne.b32 p, %61, 0;\nmov.b64 da, {%56, %59};\nmov.b64 db, {%57, %60};\n"
        "wgmma.mma_async.sync.aligned.m64n112k16.f32.bf16.bf16 "
        "{%0, %1, %2, %3, %4, %5, %6, %7, %8, %9, %10, %11, %12, %13, %14, %15, %16, %17, %18, %19, %20, %21, %22, %23, %24, %25, %26, %27, %28, %29, %30, %31, %32, %33, %34, %35, %36, %37, %38, %39, %40, %41, %42, %43, %44, %45, %46, %47, %48, %49, %50, %51, %52, %53, %54, %55}, "
        "da, db, p, 1, 1, %58, 1;\n}\n"
        : "+f"(d[O + 0]), "+f"(d[O + 1]), "+f"(d[O + 2]), "+f"(d[O + 3]), "+f"(d[O + 4]), "+f"(d[O + 5]), "+f"(d[O + 6]), "+f"(d[O + 7]), "+f"(d[O + 8]), "+f"(d[O + 9]), "+f"(d[O + 10]), "+f"(d[O + 11]), "+f"(d[O + 12]), "+f"(d[O + 13]), "+f"(d[O + 14]), "+f"(d[O + 15]), "+f"(d[O + 16]), "+f"(d[O + 17]), "+f"(d[O + 18]), "+f"(d[O + 19]), "+f"(d[O + 20]), "+f"(d[O + 21]), "+f"(d[O + 22]), "+f"(d[O + 23]), "+f"(d[O + 24]), "+f"(d[O + 25]), "+f"(d[O + 26]), "+f"(d[O + 27]), "+f"(d[O + 28]), "+f"(d[O + 29]), "+f"(d[O + 30]), "+f"(d[O + 31]), "+f"(d[O + 32]), "+f"(d[O + 33]), "+f"(d[O + 34]), "+f"(d[O + 35]), "+f"(d[O + 36]), "+f"(d[O + 37]), "+f"(d[O + 38]), "+f"(d[O + 39]), "+f"(d[O + 40]), "+f"(d[O + 41]), "+f"(d[O + 42]), "+f"(d[O + 43]), "+f"(d[O + 44]), "+f"(d[O + 45]), "+f"(d[O + 46]), "+f"(d[O + 47]), "+f"(d[O + 48]), "+f"(d[O + 49]), "+f"(d[O + 50]), "+f"(d[O + 51]), "+f"(d[O + 52]), "+f"(d[O + 53]), "+f"(d[O + 54]), "+f"(d[O + 55])
        : "r"(la), "r"(lb), "n"(TA), "n"(HA), "n"(HB), "r"(scale_d));
}

__device__ __forceinline__ void send8(const float* a, uint32_t rbuf, uint32_t rbar, uint32_t on) {
    asm volatile("{\n.reg .pred p;\nsetp.ne.u32 p, %6, 0;\n@p st.async.weak.shared::cluster.mbarrier::complete_tx::bytes.v4.b32 [%0], {%1,%2,%3,%4}, [%5];\n}"
                 ::"r"(rbuf), "r"(pack2(a[0], a[1])), "r"(pack2(a[2], a[3])), "r"(pack2(a[4], a[5])), "r"(pack2(a[6], a[7])), "r"(rbar), "r"(on) : "memory");
}
__device__ __forceinline__ void send_half(const float (&a)[56], uint32_t rbuf, uint32_t rbar, int t, uint32_t on) {
#pragma unroll
    for (int i = 0; i < 3; i++) send8(a + 28 + 8 * i, rbuf + i * 2048 + t * 16, rbar, on);
    asm volatile("{\n.reg .pred p;\nsetp.ne.u32 p, %4, 0;\n@p st.async.weak.shared::cluster.mbarrier::complete_tx::bytes.v2.b32 [%0], {%1,%2}, [%3];\n}"
                 ::"r"(rbuf + 6144 + t * 8), "r"(pack2(a[52], a[53])), "r"(pack2(a[54], a[55])), "r"(rbar), "r"(on) : "memory");
}
__device__ __forceinline__ void recv_half(uint32_t (&p)[14], uint32_t buf, int t) {
#pragma unroll
    for (int i = 0; i < 3; i++)
        asm volatile("ld.shared.v4.b32 {%0,%1,%2,%3}, [%4];" : "=r"(p[4 * i]), "=r"(p[4 * i + 1]), "=r"(p[4 * i + 2]), "=r"(p[4 * i + 3]) : "r"(buf + i * 2048 + t * 16) : "memory");
    asm volatile("ld.shared.v2.b32 {%0,%1}, [%2];" : "=r"(p[12]), "=r"(p[13]) : "r"(buf + 6144 + t * 8) : "memory");
}

struct Maps { CUtensorMap xl, x, wqkv, hst, w1, w2, xn, old_, ost, out[2], wo; };

__global__ void __cluster_dims__(2, 1, 1) __launch_bounds__(512, 1)
fused_kernel(const __nv_bfloat16* __restrict__ x, const __nv_bfloat16* __restrict__ wqkv,
             const __nv_bfloat16* __restrict__ b1, const __nv_bfloat16* __restrict__ b2, uint8_t* __restrict__ scr,
             const __nv_bfloat16* __restrict__ w1, const __grid_constant__ Maps mp, const __nv_bfloat16* __restrict__ w2) {
    extern __shared__ __align__(1024) uint8_t smem[];
    const uint32_t sb = smem_u32(smem);
    const uint32_t bar = sb + OFF_BAR;
    const int tid = threadIdx.x, lane = tid & 31;
    const int b = blockIdx.x, z = b & 1, c = b >> 1;
    unsigned* const ctr = reinterpret_cast<unsigned*>(scr + G_CTR);
    if (tid < 112) l2_prefetch(reinterpret_cast<const uint8_t*>(x) + (b * 112 + tid) * 128);
    const int wline = (tid & 127) * 128 + b;
    const bool wfirst = ((wline / 1344) & ~ROTM) == 0;
    if (PFW && (tid >> 7) == 1 && wline < 9408 && wfirst) l2_prefetch(reinterpret_cast<const uint8_t*>(wqkv) + wline * 128);
    const uint32_t t_in = clock32();
    TS0(0);
    TG(60);
    const int warp = __shfl_sync(0xffffffffu, tid >> 5, 0);
    int q, j;
    if (c < 4) { q = 15; j = c; } else if (c < 36) { q = (c - 4) & 7; j = (c - 4) >> 3; } else { q = 8 + (c - 36) % 7; j = (c - 36) / 7; }
    const bool g1 = q < 14;
    const int R = q < 8 ? q : q == 15 ? 2 : q < 10 ? q - 8 : q - 7, P = (q >> 3) * 4 + j;
    auto krow = [&](int kb) { const int k = kb + (R & ROTM); return (k >= 7 ? k - 7 : k) * 64; };
    auto x_load = [&](int kb) {
        mbar_expect(bar + 8 * (B_FULLQ + kb), 40960);
        tma2d(sb + OFF_A + ((XSLOT >> (4 * kb)) & 7) * 16384, &mp.x, z * D_ + krow(kb), R * 128, bar + 8 * (B_FULLQ + kb));
    };
    if (warp == 12 && elect()) {
#pragma unroll
        for (int i = B_FULLQ; i < B_EMPTYQ; i++) mbar_init(bar + 8 * i, 1);
        mbar_expect(bar + 8 * B_LNIN, BLK);
        tma3d(sb + OFF_A, &mp.xl, 0, 16 * b, 0, bar + 8 * B_LNIN);
        x_load(0);
        TS(49);
    }
    if (warp == 13 && elect()) {
#pragma unroll
        for (int i = B_EMPTYQ; i < B_COUNT; i++)
            mbar_init(bar + 8 * i, i < B_FULL ? (i < B_EMPTYQ + 2 ? 2 : 1) * (i - B_EMPTYQ == (R & ~ROTM) ? 9 : 8)
                                   : i < B_EMPTY ? 2 : i == B_UDONE ? (g1 ? 3 : 1) : (i < B_AUX || i == B_QKV || i == B_OST) ? 8
                                   : (i == B_UST || i == B_UST + 1 || i == B_AUX || i == B_HALO) ? 4 : 1);
#pragma unroll
        for (int i = B_RECV1; i < B_UST; i++) mbar_expect(bar + 8 * i, i < B_RECV2 ? 7168 : 8192 - 2048 * z);
    }
    asm volatile("fence.mbarrier_init.release.cluster;" ::: "memory");
    __syncwarp();
    asm volatile("barrier.cluster.arrive.relaxed.aligned;\nbarrier.cluster.wait.aligned;" ::: "memory");
    auto slot = [](uint32_t r) { return r - 6 * ((r * 43) >> 8); };
    auto phase = [](uint32_t r) { return ((r * 43) >> 8) & 1; };
    const uint32_t r_o = g1 ? 16 : 0, r_u = r_o + 5;
    auto epoch = [&]() { mbar_wait(bar + 8 * B_EP, 0); return *reinterpret_cast<volatile unsigned*>(smem + OFF_EP); };

    if (warp < 8) {
        const int wg = warp >> 2, w4 = warp & 3, t = tid & 127, g = lane >> 2, tq = lane & 3;
        asm volatile("setmaxnreg.inc.sync.aligned.u32 192;");
        const int frow = (g1 ? q : 0) * 128 + wg * 64 + w4 * 16 + g;
        uint32_t bl = ldg_u16(b1 + frow), bh = ldg_u16(b1 + frow + 8);
        uint32_t xa[4];
#pragma unroll
        for (int k = 0; k < 4; k++) xa[k] = sb + OFF_A + (warp * 16 + (lane & 15)) * 128 + (((2 * k + (lane >> 4)) ^ (lane & 7)) << 4);
        {
            const int rg = warp & 1, jq = warp >> 1;
            uint32_t r[4][4], la[4], ha[4], ex = sb + OFF_LNX + (rg * 8 + g) * 32;
#pragma unroll
            for (int i = 0; i < 4; i++) {
                const int cg = 14 * jq + 4 * i + ((lane >> 3) & (i < 3 ? 3 : 1));
                la[i] = sb + OFF_A + (cg >> 3) * 2048 + rg * 1024 + (lane & 7) * 128 + (((cg ^ lane) & 7) << 4);
                int pos = 4 * i + (lane >> 3) + (b >= 64 ? 7 : 0);
                if (pos >= 14) pos -= 14;
                ha[i] = sb + OFF_A + jq * 3584 + rg * 1792 + (lane & 7) * 16 + pos * 128;
                asm volatile("" : "+r"(la[i]), "+r"(ha[i]), "+r"(xa[i]), "+r"(ex));
            }
            TS0(46);
            mbar_wait(bar + 8 * B_LNIN, 0);
            TS0(16);
#pragma unroll
            for (int i = 0; i < 4; i++) ldsm4(la[i], r[i]);
            float rs[4] = {0.f, 0.f, 0.f, 0.f}, v[28];
#pragma unroll
            for (int i = 0; i < 3; i++) mma16816(rs, r[i][0], r[i][1], r[i][2], r[i][3], 0x3F803F80u, 0x3F803F80u);
            mma1688(rs, r[3][0], r[3][1], 0x3F803F80u);
            const float mq = (rs[0] + rs[2]) * (1.f / 112);
#pragma unroll
            for (int n = 0; n < 14; n++) { v[2 * n] = bf_lo(r[n >> 2][n & 3]) - mq; v[2 * n + 1] = bf_hi(r[n >> 2][n & 3]) - mq; }
#pragma unroll
            for (int n = 0; n < 28; n++) rs[n & 3] = n < 4 ? v[n] * v[n] : fmaf(v[n], v[n], rs[n & 3]);
            float m2 = (rs[0] + rs[1]) + (rs[2] + rs[3]);
            m2 += __shfl_xor_sync(0xffffffffu, m2, 1);
            m2 += __shfl_xor_sync(0xffffffffu, m2, 2);
            asm volatile("st.shared.v2.f32 [%0], {%1, %2};" ::"r"(ex + jq * 8), "f"(mq), "f"(m2) : "memory");
            bar_sync<1, 256>();
            float4 e0, e1;
            asm volatile("ld.shared.v4.f32 {%0,%1,%2,%3}, [%4];" : "=f"(e0.x), "=f"(e0.y), "=f"(e0.z), "=f"(e0.w) : "r"(ex) : "memory");
            asm volatile("ld.shared.v4.f32 {%0,%1,%2,%3}, [%4];" : "=f"(e1.x), "=f"(e1.y), "=f"(e1.z), "=f"(e1.w) : "r"(ex + 16) : "memory");
            const float mean = 0.25f * ((e0.x + e0.z) + (e1.x + e1.z));
            const float d0 = e0.x - mean, d1 = e0.z - mean, d2 = e1.x - mean, d3 = e1.z - mean;
            const float var = ((e0.y + e0.w) + (e1.y + e1.w)) * (1.f / D_) + 0.25f * (fmaf(d0, d0, d1 * d1) + fmaf(d2, d2, d3 * d3));
            const float r1 = rsq(var + 1e-5f);
            const float sc = r1 * rsq(var * r1 * r1 + 1e-5f), of = (mq - mean) * sc;
#pragma unroll
            for (int n = 0; n < 14; n++) r[n >> 2][n & 3] = pack2(fmaf(v[2 * n], sc, of), fmaf(v[2 * n + 1], sc, of));
#pragma unroll
            for (int i = 0; i < 3; i++) stsm4(ha[i], r[i][0], r[i][1], r[i][2], r[i][3]);
            stsm2(ha[3], r[3][0], r[3][1]);
            *reinterpret_cast<float2*>(smem + OFF_LNST + (rg * 8 + g) * 8) = make_float2(r1, -mean);
            TS0(24);
            asm volatile("bar.arrive 10, 288;" ::: "memory");
        }
        float a1[56];
        const int orow = q * 128 + wg * 64 + w4 * 16 + g;
        uint32_t qp[14];
        const uint32_t dA = desc_lo(sb + OFF_A + wg * 8192, 16), dH = desc_lo(sb + OFF_B, 1792), dU = desc_lo(sb + OFF_B, 128);
        auto release = [&](uint32_t a) { mbar_arrive_if0(a, lane); };
        auto sched_fence = [&]() { mbar_wait(bar + 8 * B_LNIN, 0); };
        auto g1_wait = [&](uint32_t r) { mbar_wait(bar + 8 * (g1 ? B_FULL + r % 6 : B_LNIN), g1 && ((r / 6) & 1)); TS0(64 + r); };
        auto g1_free = [&](uint32_t r) { mbar_arrive_if0(bar + 8 * (B_EMPTY + r % 6), lane | !g1); };
        auto g1_mma = [&](uint32_t s) {
            wg_fence();
#pragma unroll
            for (int k = 0; k < 4; k++) wgmma_n112<1, H_SW, H_H>(a1, dA + s * 1024 + k * 128, dH + s * 896 + k * 224);
            wg_commit();
        };
        auto g1_step = [&](uint32_t r) { g1_wait(r); g1_mma(r % 6); wg_wait<1>(); g1_free(r - 1); sched_fence(); };
        {
            float aq0[28], aq1[28], aq2[28];
            const uint32_t dW = desc_lo(sb + OFF_B + (P & 1) * 16, 16);
            uint32_t xf[2][4][4];
            const uint32_t rq = mapa(bar + 8 * (B_EMPTYQ - 1), z ^ 1);
            auto stage = [&](int kb, uint32_t (&f)[4][4]) {
                TS0(178 + kb);
                mbar_wait(bar + 8 * (B_FULLQ + kb), 0);
                TS0(170 + kb);
                const uint32_t sh = 4 * kb;
#pragma unroll
                for (int k = 0; k < 4; k++) ldsm4(xa[k] + ((XSLOT >> sh) & 7) * 16384, f[k]);
                const uint32_t d0 = dW + ((WSLOT >> sh) & 7) * 1536;
                wg_fence();
#pragma unroll
                for (int k = 0; k < 4; k++) {
                    const uint32_t d = d0 + (k >> 1) * 768 + (k & 1) * 128;
                    const int sc = k > 0 ? 1 : kb;
                    wgmma_n56_rs<H_SW>(aq0, f[k], d, sc);
                    wgmma_n56_rs<H_SW>(aq1, f[k], d + 256, sc);
                    wgmma_n56_rs<H_SW>(aq2, f[k], d + 512, sc);
                }
                wg_commit();
                wg_wait<1>();
                mbar_arrive_if0(bar + 8 * (B_EMPTYQ + kb - 1), lane | (kb < 1));
                asm volatile("{\n.reg .pred p;\nsetp.eq.u32 p, %1, 0;\n@p mbarrier.arrive.shared::cluster.b64 _, [%0];\n}"
                             ::"r"(rq + 8 * kb), "r"(lane | ((uint32_t)(kb - 1) > 1)) : "memory");
            };
            stage(0, xf[0]);
#pragma unroll 1
            for (int kb = 1; kb < 7; kb += 2) {
                stage(kb, xf[1]);
                stage(kb + 1, xf[0]);
            }
            TS0(2);
            asm volatile("" : "+r"(bl), "+r"(bh)::"memory");
#pragma unroll
            for (int i = 0; i < 56; i++) a1[i] = i < 28 ? bf_lo((i & 2) ? bh : bl) : 0.f;
            pin(a1);
            g1_wait(0);
            g1_mma(0);
            wg_wait<1>();
            pin(aq0); pin(aq1); pin(aq2);
            release(bar + 8 * (B_EMPTYQ + 6));
            TS0(3);
            mbar_wait(bar + 8 * B_AUX, 0);
            const float nl = *reinterpret_cast<const float*>(smem + OFF_STATS + 68 + (warp * 16 + g) * 8);
            const float nh = *reinterpret_cast<const float*>(smem + OFF_STATS + 132 + (warp * 16 + g) * 8);
            auto center = [&](const float (&a)[28], int sec, uint32_t (&p)[14]) {
#pragma unroll
                for (int n = 0; n < 7; n++) {
                    const float2 cs = *reinterpret_cast<const float2*>(smem + OFF_CS + sec * 224 + n * 32 + tq * 8);
                    p[2 * n] = pack2(fmaf(nl, cs.x, a[4 * n]), fmaf(nl, cs.y, a[4 * n + 1]));
                    p[2 * n + 1] = pack2(fmaf(nh, cs.x, a[4 * n + 2]), fmaf(nh, cs.y, a[4 * n + 3]));
                }
            };
            auto put = [&](uint32_t dst) {
                dst += (warp * 16 + 8 + (lane & 15)) * 112;
#pragma unroll
                for (int n = 0; n < 3; n++) stsm4(dst + (lane >> 4) * 16 + n * 32, qp[4 * n], qp[4 * n + 1], qp[4 * n + 2], qp[4 * n + 3]);
                stsm2(dst + 96, qp[12], qp[13]);
            };
            center(aq1, 1, qp);
            mbar_wait(bar + 8 * (B_EMPTYQ + 5), 0);
            put(sb + OFF_K);
            g1_step(1);
            center(aq2, 2, qp);
            put(sb + OFF_V);
            __syncwarp();
            release(bar + 8 * B_QKV);
            g1_step(2);
            center(aq0, 0, qp);
            TS0(4);
        }
        auto g1_steps = [&](uint32_t r0, uint32_t r1) {
#pragma unroll 1
            for (uint32_t r = r0; r < r1; r++) {
                const uint32_t s = slot(r);
                mbar_wait(bar + 8 * (B_FULL + s), phase(r));
                TS0(64 + r);
                g1_mma(s);
                wg_wait<1>();
                release(bar + 8 * (B_EMPTY + slot(r - 1)));
            }
        };
        g1_steps(g1 ? 3 : ATT_STEP, ATT_STEP);
        {
            uint32_t kf[2][3][4], vf[2][3][4];
            const bool up0 = 2 * tq > g, up1 = 2 * tq + 1 > g, edge = (R | warp) == 0;
            float rk[2][2], fs[2][2];
#pragma unroll
            for (int i = 0; i < 4; i++) {
                const float* st = reinterpret_cast<const float*>(smem + OFF_STATS) + (warp * 16 + (i >> 1) * 8) * 2;
                rk[i >> 1][i & 1] = st[(2 * tq + (i & 1) + (((i & 1) ? up1 : up0) ? 0 : 8)) * 2];
                fs[i >> 1][i & 1] = rk[i >> 1][i & 1] * (st[(g + 8) * 2] * (0.18898223650461362f * 1.4426950408889634f));
            }
            mbar_wait(bar + 8 * B_HALO, 0);
            {
                const uint32_t ka = sb + OFF_K + (warp * 16 + (lane & 7)) * 112 + (lane >> 3) * 16;
                const uint32_t va = sb + OFF_V + (warp * 16 + (lane & 15)) * 112 + (lane >> 4) * 16;
#pragma unroll
                for (int hd = 0; hd < 2; hd++) {
#pragma unroll
                    for (int u = 0; u < 3; u++) ldsm4(ka + hd * 48 + u * 896, kf[hd][u]);
                    ldsm4t(va + hd * 48, vf[hd][0]); ldsm4t(va + hd * 48 + 32, vf[hd][1]);
                    ldsm4t(ka + (OFF_V - OFF_K) + hd * 48 + 1792, vf[hd][2]);
                }
            }
            const uint32_t q0l = tq < 2 ? qp[6] : 0, q0h = tq < 2 ? qp[7] : 0, q1l = tq < 2 ? 0 : qp[6], q1h = tq < 2 ? 0 : qp[7];
            const uint32_t mk = (up0 ? 0xFFFFu : 0u) | (up1 ? 0xFFFF0000u : 0u);
            wg_wait<0>();
            g1_free(ATT_STEP - 1);
            sched_fence();
            TS0(19);
            float sc[2][3][4];
#pragma unroll
            for (int u = 0; u < 3; u++) {
#pragma unroll
                for (int i = 0; i < 8; i++) sc[i >> 2][u][i & 3] = 0.f;
                mma16816(sc[0][u], qp[0], qp[1], qp[2], qp[3], kf[0][u][0], kf[0][u][1]);
                mma16816(sc[1][u], q1l, q1h, qp[8], qp[9], kf[1][u][0], kf[1][u][1]);
            }
#pragma unroll
            for (int u = 0; u < 3; u++) {
                mma16816(sc[0][u], qp[4], qp[5], q0l, q0h, kf[0][u][2], kf[0][u][3]);
                mma16816(sc[1][u], qp[10], qp[11], qp[12], qp[13], kf[1][u][2], kf[1][u][3]);
            }
            float e[2][2][2], mx[2][2], sm[2][2];
#pragma unroll
            for (int hd = 0; hd < 2; hd++) {
                e[hd][0][0] = (up0 ? sc[hd][0][0] : sc[hd][1][0]) * fs[0][0];
                e[hd][0][1] = (up1 ? sc[hd][0][1] : sc[hd][1][1]) * fs[0][1];
                e[hd][1][0] = (up0 ? sc[hd][1][2] : sc[hd][2][2]) * fs[1][0];
                e[hd][1][1] = (up1 ? sc[hd][1][3] : sc[hd][2][3]) * fs[1][1];
                if (edge && up0) e[hd][0][0] = -1e30f;
                if (edge && up1) e[hd][0][1] = -1e30f;
                mx[hd][0] = fmaxf(e[hd][0][0], e[hd][0][1]);
                mx[hd][1] = fmaxf(e[hd][1][0], e[hd][1][1]);
            }
#pragma unroll
            for (int o = 1; o <= 2; o <<= 1)
#pragma unroll
                for (int i = 0; i < 4; i++) mx[i >> 1][i & 1] = fmaxf(mx[i >> 1][i & 1], __shfl_xor_sync(0xffffffffu, mx[i >> 1][i & 1], o));
            uint32_t pp[2][2];
#pragma unroll
            for (int i = 0; i < 4; i++) {
                const float p0 = ex2(e[i >> 1][i & 1][0] - mx[i >> 1][i & 1]), p1 = ex2(e[i >> 1][i & 1][1] - mx[i >> 1][i & 1]);
                pp[i >> 1][i & 1] = pack2(p0 * rk[i & 1][0], p1 * rk[i & 1][1]);
                sm[i >> 1][i & 1] = p0 + p1;
            }
            float ov[2][4][4];
#pragma unroll
            for (int hd = 0; hd < 2; hd++)
#pragma unroll
                for (int n = 0; n < 4; n++) {
                    ov[hd][n][0] = ov[hd][n][1] = ov[hd][n][2] = ov[hd][n][3] = 0.f;
                    mma16816(ov[hd][n], pp[hd][0] & mk, 0u, pp[hd][0] & ~mk, pp[hd][1] & mk, vf[hd][n >> 1][2 * (n & 1)], vf[hd][n >> 1][2 * (n & 1) + 1]);
                }
#pragma unroll
            for (int hd = 0; hd < 2; hd++)
#pragma unroll
                for (int n = 0; n < 4; n++) mma1688(ov[hd][n], 0u, pp[hd][1] & ~mk, vf[hd][2][n]);
            sched_fence();
            bar_sync<1, 256>();
            TS0(18);
            g1_wait(ATT_STEP); g1_mma(ATT_STEP % 6);
            sched_fence();
#pragma unroll
            for (int o = 1; o <= 2; o <<= 1)
#pragma unroll
                for (int i = 0; i < 4; i++) sm[i >> 1][i & 1] += __shfl_xor_sync(0xffffffffu, sm[i >> 1][i & 1], o);
            const uint32_t oa = sb + OFF_OST + (warp * 16 + (lane & 15)) * 128;
            uint32_t op[16];
            op[14] = op[15] = 0;
#pragma unroll
            for (int i = 0; i < 4; i++) sm[i >> 1][i & 1] = rcp(sm[i >> 1][i & 1]);
            asm volatile("" : "+f"(sm[0][0]), "+f"(sm[0][1]), "+f"(sm[1][0]), "+f"(sm[1][1])::"memory");
            g1_step(ATT_STEP + 1);
#pragma unroll
            for (int n = 0; n < 7; n++) {
                const bool hb = n > 3 || (n == 3 && tq >= 2);
#pragma unroll
                for (int h = 0; h < 2; h++) {
                    const float r = hb ? sm[1][h] : sm[0][h];
                    const float x0 = hb ? ov[1][n >= 3 ? n - 3 : 0][2 * h] : ov[0][n <= 3 ? n : 0][2 * h];
                    const float x1 = hb ? ov[1][n >= 3 ? n - 3 : 0][2 * h + 1] : ov[0][n <= 3 ? n : 0][2 * h + 1];
                    op[2 * n + h] = pack2(x0 * r, x1 * r);
                }
            }
#pragma unroll
            for (int n = 0; n < 4; n++) stsm4(oa + (((2 * n + (lane >> 4)) ^ (lane & 7)) << 4), op[4 * n], op[4 * n + 1], op[4 * n + 2], op[4 * n + 3]);
            __syncwarp();
            release(bar + 8 * B_OST);
            TS0(20);
            bl = ldg_u16(b2 + orow); bh = ldg_u16(b2 + orow + 8);
        }
        if (ATT_STEP + 3 == 16 - NS1) g1_step(ATT_STEP + 2);
        else g1_steps(g1 ? ATT_STEP + 2 : 16 - NS1, 16 - NS1);
        const uint32_t peer = z ^ 1;
        gate_wait(wg);
        g1_steps(g1 ? 16 - NS1 : 16, 16);
        gate_open(wg);
        mbar_wait_cluster(bar + 8 * B_FREE, 0);
        wg_wait<0>();
        pin(a1);
        TSW(6);
        if (g1) {
            send_half(a1, mapa(sb + OFF_RECV1 + wg * 7168, peer), mapa(bar + 8 * (B_RECV1 + wg), peer), t, 1);
            release(bar + 8 * (B_EMPTY + 3));
            uint32_t p[14];
            mbar_wait_cluster(bar + 8 * (B_RECV1 + wg), 0);
            TSW(8);
            recv_half(p, sb + OFF_RECV1 + wg * 7168, t);
#pragma unroll
            for (int i = 0; i < 14; i++) p[i] = pack2(gelu_tanh(a1[2 * i] + bf_lo(p[i])), gelu_tanh(a1[2 * i + 1] + bf_hi(p[i])));
            const uint32_t dst = sb + OFF_UST + wg * 7168 + w4 * 256 + (lane & 15) * 16;
#pragma unroll
            for (int n = 0; n < 3; n++) stsm4(dst + (2 * n + (lane >> 4)) * 1024, p[4 * n], p[4 * n + 1], p[4 * n + 2], p[4 * n + 3]);
            stsm2(dst + 6144, p[12], p[13]);
            __syncwarp();
            release(bar + 8 * (B_UST + wg));
        }
        TSW(9);
        float a2[56];
        {
            const uint32_t s = slot(r_o);
            mbar_wait(bar + 8 * (B_FULL + s), phase(r_o));
            uint32_t xr[4][4];
#pragma unroll
            for (int k = 0; k < 4; k++) ldsm4(xa[k] + s * 16384, xr[k]);
            if (z) bl = bh = xr[3][0] = xr[3][1] = xr[3][2] = xr[3][3] = 0;
#pragma unroll
            for (int i = 0; i < 56; i++) {
                a2[i] = bf_lo((i & 2) ? bh : bl);
                if (i < 32) a2[i] += (i & 1) ? bf_hi(xr[i >> 3][(i >> 1) & 3]) : bf_lo(xr[i >> 3][(i >> 1) & 3]);
            }
            pin(a2);
        }
#pragma unroll 1
        for (uint32_t r = r_o + 1; r < r_u; r++) {
            const uint32_t s = slot(r);
            mbar_wait(bar + 8 * (B_FULL + s), phase(r));
            TS0(64 + 16 + r - r_o);
            wg_fence();
#pragma unroll
            for (int k = 0; k < 4; k++) wgmma_n112<0, H_SW, H_U>(a2, dA + s * 1024 + k * 2, dU + s * 896 + k * 16);
            wg_commit();
            wg_wait<1>();
            release(bar + 8 * (B_EMPTY + slot(r - 1)));
        }
        wg_wait<0>();
        release(bar + 8 * (B_EMPTY + slot(r_u - 1)));
        TSW(10);
#pragma unroll 1
        for (uint32_t r = r_u; r < r_u + 14; r++) {
            const uint32_t s = slot(r);
            gate_wait(wg && r == r_u + 14 - NS2);
            mbar_wait(bar + 8 * (B_FULL + s), phase(r));
            TS0(85 + r - r_u);
            wg_fence();
#pragma unroll
            for (int k = 0; k < 4; k++) wgmma_n112<1, H_SW, H_U>(a2, dA + s * 1024 + k * 128, dU + s * 896 + k * 16);
            wg_commit();
            wg_wait<1>();
            mbar_arrive_if0(bar + 8 * (B_EMPTY + slot(r - 1)), lane | (r == r_u));
        }
        gate_open(wg);
        mbar_wait_cluster(bar + 8 * B_UDONE, 0);
        wg_wait<0>();
        pin(a2);
        TSW(11);
        {
            const uint32_t rbuf = mapa(sb + OFF_RECV2 + wg * 8192 + t * 16, peer) - (z ? 0 : 2048), rbar = mapa(bar + 8 * (B_RECV2 + wg), peer);
#pragma unroll
            for (int i = 3; i >= 0; i--) send8(a2 + 24 + 8 * i, rbuf + i * 2048, rbar, i | z);
            mbar_wait_cluster(bar + 8 * (B_RECV2 + wg), 0);
            TSW(12);
            const uint32_t dst = sb + OFF_OUT + wg * 8192 + (w4 * 16 + (lane & 15)) * 128;
#pragma unroll
            for (int i = 0; i < 4; i++) {
                uint32_t u[4];
                asm volatile("ld.shared.v4.b32 {%0,%1,%2,%3}, [%4];" : "=r"(u[0]), "=r"(u[1]), "=r"(u[2]), "=r"(u[3]) : "r"(sb + OFF_RECV2 + wg * 8192 + i * 2048 + t * 16) : "memory");
#pragma unroll
                for (int e = 0; e < 4; e++) u[e] = pack2(a2[8 * i + 2 * e] + bf_lo(u[e]), a2[8 * i + 2 * e + 1] + bf_hi(u[e]));
                stsm4(dst + (((2 * i + (lane >> 4)) ^ (lane & 7)) << 4), u[0], u[1], u[2], u[3]);
            }
            bar_sync_id(2 + wg, 128);
            if (w4 == 0 && elect()) {
                fence_async_smem();
                tma2d_store(&mp.out[z], sb + OFF_OUT + wg * 8192, j * 112 + z * 64, q * 128 + wg * 64);
                bulk_commit();
                bulk_wait_read();
            }
        }
        TSW(13);
    } else if (warp < 12) {
        asm volatile("setmaxnreg.dec.sync.aligned.u32 96;");
        const int hw = warp - 8, t = tid & 127;
        while (clock32() - t_in < DLY1) {}
        if (wline < 9408 && !wfirst) l2_prefetch(reinterpret_cast<const uint8_t*>(wqkv) + wline * 128);
        uint8_t* cells = scr + G_HALO + ((R * 8 + P) * 2 + z) * 3584 + min(t, 111) * 16;
        cell_put(cells, 0, 0, 0);
        cell_put(cells + 1792, 0, 0, 0);
        const unsigned e1 = epoch();
        {
            const int st = R & ~ROTM, ch = z * 12 + lane % 12, rp = lane / 12;
            mbar_wait(bar + 8 * (B_FULLQ + st), 0);
            TSH(47);
            if (lane < 24) {
                float cs[8] = {0.f, 0.f, 0.f, 0.f, 0.f, 0.f, 0.f, 0.f};
                const uint32_t wa = sb + OFF_B + ((WSLOT >> (4 * st)) & 7) * 24576 + (hw >> 1) * 12288 + (ch >> 3) * 4096 + (hw & 1) * 2048 + rp * 1024;
#pragma unroll
                for (int r = 0; r < 8; r++) {
                    uint32_t u[4];
                    asm volatile("ld.shared.v4.b32 {%0,%1,%2,%3}, [%4];" : "=r"(u[0]), "=r"(u[1]), "=r"(u[2]), "=r"(u[3]) : "r"(wa + r * 128 + (((ch ^ r) & 7) << 4)) : "memory");
#pragma unroll
                    for (int e = 0; e < 4; e++) { cs[2 * e] += bf_lo(u[e]); cs[2 * e + 1] += bf_hi(u[e]); }
                }
                float4* part = reinterpret_cast<float4*>(smem + OFF_CSP + hw * 768 + lane * 32);
                part[0] = make_float4(cs[0], cs[1], cs[2], cs[3]);
                part[1] = make_float4(cs[4], cs[5], cs[6], cs[7]);
            }
            bar_sync<12, 128>();
            TSH(45);
            if (t < (st < 2 ? 2 : 1)) asm volatile("mbarrier.arrive.shared::cluster.b64 _, [%0];" ::"r"(mapa(bar + 8 * (B_EMPTYQ + st), z ^ t)) : "memory");
            if (t < 48 && R < 7) {
                const float2* p = reinterpret_cast<const float2*>(smem + OFF_CSP) + t;
                float2 a = p[0];
#pragma unroll
                for (int i = 1; i < 8; i++) { const float2 v = p[48 * i]; a.x += v.x; a.y += v.y; }
                cell_put(scr + G_CS + (P * 7 + R) * 1536 + (z * 48 + t) * 16, __float_as_uint(a.x), __float_as_uint(a.y), e1);
            }
            TSH(43);
        }
        mbar_wait(bar + 8 * (B_FULLQ + GATHER), 0);
        {
            const bool cw = hw < 3;
            const uint8_t* src = cw ? scr + G_CS + P * 7 * 1536 + (hw * 32 + (P & 1) * 4 + min(lane, 27)) * 16 : scr + G_STATS + (z * 1024 + R * 128 - 8) * 16;
            uint32_t a[7], d[7], bad;
            do {
                bad = 0;
#pragma unroll
                for (int i = 0; i < 7; i++) bad |= cell_get(src + (cw ? i * 1536 : max(min(lane + 32 * i, 135), R ? 0 : 8) * 16), a[i], d[i], e1);
            } while (bad);
            if (cw) {
                float2 sum = make_float2(0.f, 0.f);
#pragma unroll
                for (int i = 0; i < 7; i++) { sum.x += __uint_as_float(a[i]); sum.y += __uint_as_float(d[i]); }
                reinterpret_cast<float2*>(smem + OFF_CS)[hw * 28 + min(lane, 27)] = sum;
            } else {
#pragma unroll
                for (int i = 0; i < 5; i++) reinterpret_cast<uint2*>(smem + OFF_STATS)[min(lane + 32 * i, 135)] = make_uint2(a[i], d[i]);
            }
            __syncwarp();
            mbar_arrive_if0(bar + 8 * B_AUX, lane);
            TSH(41);
        }
        {
            uint2* kv = reinterpret_cast<uint2*>(smem + OFF_K) + min(t, 111);
            mbar_wait(bar + 8 * B_QKV, 0);
            uint2 k2 = kv[1792], v2 = kv[1792 + (OFF_V - OFF_K) / 8];
            cell_put(cells, k2.x, k2.y, e1);
            cell_put(cells + 1792, v2.x, v2.y, e1);
            k2 = v2 = make_uint2(0, 0);
            if (R > 0) while (cell_get(cells - 16 * 3584, k2.x, k2.y, e1) | cell_get(cells - 16 * 3584 + 1792, v2.x, v2.y, e1)) {}
            kv[0] = k2;
            kv[(OFF_V - OFF_K) / 8] = v2;
            __syncwarp();
            mbar_arrive_if0(bar + 8 * B_HALO, lane);
            TSH(40);
        }
        if (hw == 2) {
            if (elect()) {
                auto tell_peer = [&](int i) {
                    asm volatile("mbarrier.arrive.relaxed.cluster.shared::cluster.b64 _, [%0];" ::"r"(mapa(bar + 8 * i, z ^ 1)) : "memory");
                };
                mbar_wait(bar + 8 * B_OST, 0);
                tell_peer(B_FREE);
                fence_async_smem();
                tma2d_store(&mp.ost, sb + OFF_OST, z * 64, P * 1024 + R * 128);
                bulk_commit();
                bulk_wait_all();
                red_relaxed(ctr + C_O + (R * 2 + (P >> 2)) * 32);
                TS(21);
                tell_peer(B_UDONE);
            }
        } else if (hw < 2 && g1) {
            if (elect()) {
                const int ub = 2 * q + hw, zz = ub >= 14 ? 1 : 0;
                uint8_t* ud = scr + G_BIMG + ((8 + ub) * 4 + j) * BLK;
                mbar_wait(bar + 8 * (B_UST + hw), 0);
                fence_async_smem();
                bulk_store(ud + ((7 * z + 1 + 6 * zz) % 14) * 1024, sb + OFF_UST + hw * 7168 + 1024, 6144);
                bulk_store(ud + (7 * z + 6 * zz) * 1024, sb + OFF_UST + hw * 7168, 1024);
                bulk_commit();
                bulk_wait_all();
                red_relaxed(ctr + C_U + ((j * 2 + zz) * 2 + hw) * 32);
                TS(22 + hw);
                mbar_arrive(bar + 8 * B_UDONE);
            }
        }
    } else {
        asm volatile("setmaxnreg.dec.sync.aligned.u32 32;");
        auto wait_free = [&](uint32_t r, uint32_t first) {
            const uint32_t a = r < 6 ? B_EMPTYQ + ((first >> (4 * r)) & 7) : B_EMPTY + slot(r);
            mbar_wait(bar + 8 * a, r < 6 ? 0 : phase(r) ^ 1);
        };
        if (warp == 12) {
            TS(48);
            if (elect()) {
#pragma unroll 1
                for (int kb = 0; kb < 7; kb++) {
                    if (kb == 1) while (clock32() - t_in < DLY2) {}
                    if (kb >= QDEPTH) mbar_wait(bar + 8 * (B_FULLQ + kb - QDEPTH), 0);
                    if (kb >= 5) mbar_wait(bar + 8 * (B_EMPTYQ + kb - 5), 0);
                    if (kb > 0) x_load(kb);
                    tma3d_mc(sb + OFF_B + ((WSLOT >> (4 * kb)) & 7) * 24576 + z * 12288, &mp.wqkv, (P * 56) & ~15, krow(kb) + z * 32, 0, bar + 8 * (B_FULLQ + kb));
                }
                TS(50);
                ld_relaxed(ctr + C_O + ((q & ~1) + z) * 32);
                mbar_wait(bar + 8 * B_LNFREE, 0);
                if (!g1) {
                    const int ic = (q - 14) * 8 + j * 2 + z, rot = ic >> 3;
                    mbar_wait(bar + 8 * (B_EMPTYQ + 2), 0);
                    mbar_expect(bar + 8 * B_LN, 2 * BLK);
#pragma unroll 1
                    for (int i = 0; i < 2; i++) tma3d(sb + OFF_A + i * BLK, &mp.wo, 0, (ic >> 1) * 56, (z * 2 + i) * 14, bar + 8 * B_LN);
                    mbar_wait(bar + 8 * B_LN, 0);
#pragma unroll 1
                    for (int i = 0; i < 2; i++) {
                        uint8_t* dst = scr + G_BIMG + (ic * 2 + i) * BLK;
                        bulk_store(dst + rot * 6144, sb + OFF_A + i * BLK, 8192);
                        bulk_store(dst + (rot ^ 1) * 8192, sb + OFF_A + i * BLK + 8192, 6144);
                    }
                    bulk_commit();
                    bulk_wait_all();
                    red_relaxed(ctr + C_WO);
                    TS(44);
                }
#pragma unroll 1
                for (uint32_t r = 0; r < r_o; r++) {
                    const uint32_t s = slot(r), fb = bar + 8 * (B_FULL + s);
                    wait_free(r, 0x654320u);
                    mbar_expect(fb, 16384);
                    tma3d(sb + OFF_A + s * 16384, &mp.w1, 0, z * 1024 + r * 64, 2 * q, fb);
                    TS(99 + r);
                }
#pragma unroll 1
                for (uint32_t r = r_o; r < r_u; r++) {
                    const uint32_t s = slot(r), fb = bar + 8 * (B_FULL + s);
                    if (r == r_o + 1) { poll_slow(ctr + C_O + ((q & ~1) + z) * 32, epoch() * 8); fence_async_global(); TS(32); }
                    wait_free(r, 0x654320u);
                    mbar_expect(fb, 16384);
                    if (r == r_o) tma2d(sb + OFF_A + s * 16384, &mp.xn, j * 112 + z * 64, q * 128, fb);
                    else tma2d(sb + OFF_A + s * 16384, &mp.old_, 0, (4 * z + r - r_o - 1) * S_ + q * 128, fb);
                    TS(99 + 16 + r - r_o);
                }
#pragma unroll 1
                for (uint32_t i = 0; i < 14; i++) {
                    const uint32_t r = r_u + i, s = slot(r), fb = bar + 8 * (B_FULL + s);
                    wait_free(r, 0x654320u);
                    mbar_expect(fb, 16384);
                    tma3d(sb + OFF_A + s * 16384, &mp.w2, 0, (14 * z + (i < 7 ? 2 * i : 2 * i - 13)) * 64, 2 * q, fb);
                    TS(99 + 21 + i);
                }
            }
        } else if (warp == 13) {
            if (elect()) {
                const unsigned e1 = epoch();
                ld_relaxed(ctr + C_WO);
                ld_relaxed(ctr + C_U + (j * 2 + z) * 64);
                ld_relaxed(ctr + C_U + (j * 2 + z) * 64 + 32);
                auto run = [&](uint32_t r0, uint32_t n, const uint8_t* src, uint32_t stride, uint32_t ts) {
#pragma unroll 1
                    for (uint32_t r = r0; r < r0 + n; r++, src += stride) {
                        const uint32_t s = slot(r), fb = bar + 8 * (B_FULL + s);
                        wait_free(r, 0x644332u);
                        mbar_expect(fb, BLK);
                        bulk_load(sb + OFF_B + s * BLK, src, BLK, fb);
                        TS(ts + r - r0);
                    }
                };
#pragma unroll 1
                for (int ph = g1 ? 0 : 1; ph < 4; ph++) {
                    if (ph == 0) {
                        mbar_wait(bar + 8 * B_LN, 0);
                    } else if (ph == 1) {
                        wait_free(r_o, 0x644332u);
                        mbar_arrive(bar + 8 * (B_FULL + slot(r_o)));
                        poll_slow(ctr + C_WO, e1 * 16);
                    } else {
                        poll(ctr + C_U + ((j * 2 + z) * 2 + ph - 2) * 32, e1 * 14);
                    }
                    fence_async_global();
                    TS(ph == 0 ? 33 : ph == 2 ? 34 : ph == 3 ? 35 : 63);
                    const uint8_t* src = ph == 0 ? scr + G_HIMG + (64 * z + j) * BLK : scr + G_BIMG + ((ph == 1 ? 4 * z : 6 + 14 * z + ph) * 4 + j) * BLK;
                    const uint32_t off = ph == 1 ? 1 : 7 * ph - 9;
                    run(ph == 0 ? 0 : r_o + off, ph == 0 ? 16 : ph == 1 ? 4 : 7, src, ph < 2 ? 4 * BLK : 8 * BLK, 134 + (ph == 0 ? 0 : 16 + off));
                }
            }
        } else if (warp == 14) {
            unsigned* lnc = ctr + C_LN + 32 * (c & 7);
            const unsigned e1 = (ld_relaxed(lnc) >> 7) + 1;
            if (lane == 0) {
                *reinterpret_cast<volatile unsigned*>(smem + OFF_EP) = e1;
                mbar_arrive(bar + 8 * B_EP);
                TS(36);
            }
            bar_sync<10, 288>();
            if (elect()) {
                fence_async_smem();
                TS(42);
                tma4d_store(&mp.hst, sb + OFF_A, 0, 0, b & 3, b & ~3);
                bulk_commit();
            }
            __syncwarp();
            if (lane < 16) {
                const uint2 v = reinterpret_cast<const uint2*>(smem + OFF_LNST)[lane];
                cell_put(scr + G_STATS + ((lane & 1) * 1024 + 8 * b + (lane >> 1)) * 16, v.x, v.y, e1);
            }
            bulk_wait_all();
            __syncwarp();
            if (lane < 8) red_relaxed(ctr + C_LN + 32 * lane);
            if (lane == 0) {
                mbar_arrive(bar + 8 * B_LNFREE);
                TS(37);
                if (g1) {
                    poll(lnc, e1 * 128);
                    mbar_arrive(bar + 8 * B_LN);
                }
            }
        } else {
            if (elect()) {
#pragma unroll 1
                for (int i = 2; i < 12; i++) asm volatile("prefetch.tensormap [%0];" ::"l"(reinterpret_cast<const CUtensorMap*>(&mp) + i) : "memory");
            }
            __syncwarp();
#pragma unroll 1
            for (int i = 0; i < PF_N; i++) {
                while (clock32() - t_in < PF_T0 + i * PF_DT) __nanosleep(32);
                const int k = i - 16;
                if (k >= 0) l2_prefetch(w2 + (size_t)(((b >> 6) * 14 + (k < 7 ? 2 * k : 2 * k - 13)) * 64 + (b & 63)) * S_ + lane * 64);
                else if (lane < 28) l2_prefetch(w1 + (size_t)((b >> 6) * 1024 + i * 64 + (b & 63)) * 1792 + lane * 64);
            }
            if (elect()) {
                mbar_watch(bar + 8 * B_RECV2);
                mbar_watch(bar + 8 * (B_RECV2 + 1));
            }
        }
    }
}

typedef CUresult (*EncodeFn)(CUtensorMap*, CUtensorMapDataType, cuuint32_t, void*, const cuuint64_t*, const cuuint64_t*, const cuuint32_t*,
                             const cuuint32_t*, CUtensorMapInterleave, CUtensorMapSwizzle, CUtensorMapL2promotion, CUtensorMapFloatOOBfill);

void encode(EncodeFn fn, CUtensorMap* m, const void* p, int rank, const cuuint64_t* dims, const cuuint64_t* strides, const cuuint32_t* box, bool swz) {
    const cuuint32_t es[4] = {1, 1, 1, 1};
    fn(m, CU_TENSOR_MAP_DATA_TYPE_BFLOAT16, rank, const_cast<void*>(p), dims, strides, box, es, CU_TENSOR_MAP_INTERLEAVE_NONE,
       swz ? CU_TENSOR_MAP_SWIZZLE_128B : CU_TENSOR_MAP_SWIZZLE_NONE, CU_TENSOR_MAP_L2_PROMOTION_L2_128B, CU_TENSOR_MAP_FLOAT_OOB_FILL_NONE);
}

}

extern "C" void kernel_launch(void* const* d_in, const int* in_sizes, int n_in, void* d_out, int out_size) {
    const __nv_bfloat16* x = (const __nv_bfloat16*)d_in[0];
    const __nv_bfloat16* wqkv = (const __nv_bfloat16*)d_in[1];
    const __nv_bfloat16* wo = (const __nv_bfloat16*)d_in[2];
    const __nv_bfloat16* w1 = (const __nv_bfloat16*)d_in[4];
    const __nv_bfloat16* b1 = (const __nv_bfloat16*)d_in[5];
    const __nv_bfloat16* w2 = (const __nv_bfloat16*)d_in[6];
    const __nv_bfloat16* b2 = (const __nv_bfloat16*)d_in[7];

    void* fp = nullptr;
    cudaDriverEntryPointQueryResult qr;
    cudaGetDriverEntryPoint("cuTensorMapEncodeTiled", &fp, cudaEnableDefault, &qr);
    EncodeFn fn = (EncodeFn)fp;
    void* sp = nullptr;
    cudaGetSymbolAddress(&sp, g_scratch);
    uint8_t* scr = (uint8_t*)sp;
    void *o = scr + G_O, *himg = scr + G_HIMG;

    Maps mp;
    { cuuint64_t d[3] = {64, 2048, 7}, s[2] = {896, 128}; cuuint32_t bx[3] = {64, 16, 7}; encode(fn, &mp.xl, x, 3, d, s, bx, true); }
    { cuuint64_t d[2] = {896, 1024}, s[1] = {1792}; cuuint32_t bx[2] = {64, 128}; encode(fn, &mp.x, x, 2, d, s, bx, true); }
    { cuuint64_t d[3] = {448, 448, 3}, s[2] = {2688, 896}; cuuint32_t bx[3] = {64, 32, 3}; encode(fn, &mp.wqkv, wqkv, 3, d, s, bx, true); }
    { cuuint64_t d[3] = {64, 2048, 28}, s[2] = {3584, 128}; cuuint32_t bx[3] = {64, 64, 2}; encode(fn, &mp.w1, w1, 3, d, s, bx, true); }
    { cuuint64_t d[3] = {64, 1792, 32}, s[2] = {4096, 128}; cuuint32_t bx[3] = {64, 64, 2}; encode(fn, &mp.w2, w2, 3, d, s, bx, true); }
    { cuuint64_t d[4] = {64, 28, 4, 128}, s[3] = {128, 3584, BLK}; cuuint32_t bx[4] = {64, 28, 1, 4}; encode(fn, &mp.hst, himg, 4, d, s, bx, false); }
    { cuuint64_t d[2] = {448, 2048}, s[1] = {896}; cuuint32_t bx[2] = {64, 128}; encode(fn, &mp.xn, x, 2, d, s, bx, true); }
    { cuuint64_t d[2] = {64, 8 * 2048}, s[1] = {128}; cuuint32_t bx[2] = {64, 128}; encode(fn, &mp.old_, o, 2, d, s, bx, true); }
    { cuuint64_t d[2] = {128, 8 * 1024}, s[1] = {256}; cuuint32_t bx[2] = {64, 128}; encode(fn, &mp.ost, o, 2, d, s, bx, true); }
    { cuuint64_t d[2] = {448, 2048}, s[1] = {896}; cuuint32_t bx[2] = {64, 64}; encode(fn, &mp.out[0], d_out, 2, d, s, bx, true); }
    { cuuint64_t d[2] = {448, 2048}, s[1] = {896}; cuuint32_t bx[2] = {48, 64}; encode(fn, &mp.out[1], d_out, 2, d, s, bx, true); }
    { cuuint64_t d[3] = {8, 448, 56}, s[2] = {896, 16}; cuuint32_t bx[3] = {8, 64, 14}; encode(fn, &mp.wo, wo, 3, d, s, bx, false); }

    cudaFuncSetAttribute(fused_kernel, cudaFuncAttributeMaxDynamicSharedMemorySize, SMEM_BYTES);
    fused_kernel<<<128, 512, SMEM_BYTES>>>(x, wqkv, b1, b2, scr, w1, mp, w2);
}
```

```cpp
#include <cuda_runtime.h>
#include <cuda.h>
#include <cuda_bf16.h>
#include <stdint.h>

namespace {

constexpr int S_ = 2048, D_ = 448;
constexpr uint32_t BLK = 14336;

constexpr uint32_t G_HIMG = 0;
constexpr uint32_t G_BIMG = G_HIMG + 32 * 4 * BLK;
constexpr uint32_t G_O = G_BIMG + 36 * 4 * BLK;
constexpr uint32_t G_STATS = G_O + 8 * S_ * 128;
constexpr uint32_t G_CS = G_STATS + S_ * 16;
constexpr uint32_t G_HALO = G_CS + 8 * 4 * 2048;
constexpr uint32_t G_CTR = G_HALO + 128 * 3584;
constexpr uint32_t G_END = G_CTR + 1312 * 4;
__device__ __align__(1024) uint8_t g_scratch[G_END];

constexpr int C_LN = 0, C_WO = 256, C_O = 288, C_U = 800;

#define TSX(sel, id)
#define TS(id)
#define TS0(id)
#define TSH(id)
#define TSW(id)
#define TG(id)

#define POLL_NS 200
#define QDEPTH 3
#define DLY1 1200
#define DLY2 1800
#define GATHER 3
#define PFW 0
#define PF_N 0
#define PF_T0 2800
#define PF_DT 320
#define NS1 4
#define NS2 4
#define NE 2
#define NP 2
constexpr uint32_t OFF_A = 0;
constexpr uint32_t OFF_B = 98304;
constexpr uint32_t OFF_X = 184320;
constexpr uint32_t OFF_K = 196608;
constexpr uint32_t OFF_V = OFF_K + 9 * 896;
constexpr uint32_t OFF_OST = OFF_X, OFF_RECV2 = OFF_X, OFF_RECV1 = OFF_X + 16384, OFF_UST = OFF_X + 30720, OFF_OUT = OFF_X + 16384;
constexpr uint32_t OFF_CSB = 221184;
constexpr uint32_t OFF_ONES = OFF_CSB + 3072;
constexpr uint32_t OFF_STATS = OFF_ONES + 512;
constexpr uint32_t OFF_LNX = OFF_STATS + 1088;
constexpr uint32_t OFF_LNST = 229376;
constexpr uint32_t OFF_EP = OFF_LNST + 128;
constexpr uint32_t OFF_BAR = OFF_EP + 16;
constexpr uint32_t OFF_TS = OFF_BAR + 8 * 44;
constexpr uint32_t SMEM_BYTES = OFF_TS;

enum : int {
    B_FULLQ = 0, B_LNIN = 7, B_EMPTYQ = 8, B_FULL = 15, B_EMPTY = 21, B_AUX = 27, B_QKV = 28, B_HALO = 29, B_FREE = 30,
    B_RECV1 = 31, B_RECV2 = 33, B_UST = 35, B_EP = 37, B_OST = 38, B_LNFREE = 39, B_LN = 40, B_UDONE = 41, B_NONE = 42, B_COUNT = 43
};
constexpr uint32_t XSLOT = 0x5432154u;
constexpr uint32_t WSLOT = 0x3421034u;
#define ATT_STEP 10

__device__ __forceinline__ uint32_t smem_u32(const void* p) { return (uint32_t)__cvta_generic_to_shared(p); }
__device__ __forceinline__ void mbar_init(uint32_t a, int c) { asm volatile("mbarrier.init.shared::cta.b64 [%0], %1;" ::"r"(a), "r"(c) : "memory"); }
__device__ __forceinline__ void mbar_expect(uint32_t a, uint32_t b) { asm volatile("mbarrier.arrive.expect_tx.shared::cta.b64 _, [%0], %1;" ::"r"(a), "r"(b) : "memory"); }
__device__ __forceinline__ void mbar_arrive(uint32_t a) { asm volatile("mbarrier.arrive.shared::cta.b64 _, [%0];" ::"r"(a) : "memory"); }
__device__ __forceinline__ void mbar_arrive_if0(uint32_t a, uint32_t sel) {
    asm volatile("{\n.reg .pred p;\nsetp.eq.u32 p, %1, 0;\n@p mbarrier.arrive.shared::cta.b64 _, [%0];\n}" ::"r"(a), "r"(sel) : "memory");
}
__device__ __forceinline__ void mbar_wait(uint32_t a, uint32_t parity) {
    asm volatile("{\n.reg .pred p;\nW0:\nmbarrier.try_wait.parity.shared::cta.b64 p, [%0], %1;\n@!p bra W0;\n}\n" ::"r"(a), "r"(parity) : "memory");
}
__device__ __forceinline__ void mbar_wait_cluster(uint32_t a, uint32_t parity) {
    asm volatile("{\n.reg .pred p;\nW0:\nmbarrier.try_wait.parity.acquire.cluster.shared::cta.b64 p, [%0], %1;\n@!p bra W0;\n}\n" ::"r"(a), "r"(parity) : "memory");
}
__device__ __forceinline__ void mbar_watch(uint32_t a) {
    asm volatile(
        "{\n.reg .pred p;\n.reg .u32 n;\nmov.u32 n, 0;\n"
        "W0:\nmbarrier.try_wait.parity.shared::cta.b64 p, [%0], 0;\n@p bra W1;\n"
        "add.u32 n, n, 1;\nsetp.lt.u32 p, n, 4194304;\n@p bra W0;\ntrap;\nW1:\n}\n" ::"r"(a) : "memory");
}
__device__ __forceinline__ bool elect() {
    uint32_t r;
    asm volatile("{\n.reg .pred p;\nelect.sync _|p, 0xffffffff;\nselp.u32 %0, 1, 0, p;\n}" : "=r"(r));
    return r;
}
__device__ __forceinline__ uint32_t mapa(uint32_t a, uint32_t cta) { uint32_t r; asm("mapa.shared::cluster.u32 %0, %1, %2;" : "=r"(r) : "r"(a), "r"(cta)); return r; }
__device__ __forceinline__ void tma2d(uint32_t dst, const CUtensorMap* m, int c0, int c1, uint32_t bar) {
    asm volatile("cp.async.bulk.tensor.2d.shared::cluster.global.mbarrier::complete_tx::bytes [%0], [%1, {%3, %4}], [%2];" ::"r"(dst), "l"(m), "r"(bar), "r"(c0), "r"(c1) : "memory");
}
__device__ __forceinline__ void tma3d(uint32_t dst, const CUtensorMap* m, int c0, int c1, int c2, uint32_t bar) {
    asm volatile("cp.async.bulk.tensor.3d.shared::cluster.global.mbarrier::complete_tx::bytes [%0], [%1, {%3, %4, %5}], [%2];" ::"r"(dst), "l"(m), "r"(bar), "r"(c0), "r"(c1), "r"(c2) : "memory");
}
__device__ __forceinline__ void tma3d_mc(uint32_t dst, const CUtensorMap* m, int c0, int c1, int c2, uint32_t bar) {
    asm volatile("cp.async.bulk.tensor.3d.shared::cluster.global.mbarrier::complete_tx::bytes.multicast::cluster [%0], [%1, {%3, %4, %5}], [%2], %6;"
                 ::"r"(dst), "l"(m), "r"(bar), "r"(c0), "r"(c1), "r"(c2), "h"((uint16_t)3) : "memory");
}
__device__ __forceinline__ void tma2d_store(const CUtensorMap* m, uint32_t src, int c0, int c1) {
    asm volatile("cp.async.bulk.tensor.2d.global.shared::cta.bulk_group [%0, {%2, %3}], [%1];" ::"l"(m), "r"(src), "r"(c0), "r"(c1) : "memory");
}
__device__ __forceinline__ void tma4d_store(const CUtensorMap* m, uint32_t src, int c0, int c1, int c2, int c3) {
    asm volatile("cp.async.bulk.tensor.4d.global.shared::cta.bulk_group [%0, {%2, %3, %4, %5}], [%1];" ::"l"(m), "r"(src), "r"(c0), "r"(c1), "r"(c2), "r"(c3) : "memory");
}
__device__ __forceinline__ void bulk_load(uint32_t dst, const void* src, uint32_t bytes, uint32_t bar) {
    asm volatile("cp.async.bulk.shared::cluster.global.mbarrier::complete_tx::bytes [%0], [%1], %2, [%3];" ::"r"(dst), "l"(src), "r"(bytes), "r"(bar) : "memory");
}
__device__ __forceinline__ void bulk_store(void* dst, uint32_t src, uint32_t bytes) {
    asm volatile("cp.async.bulk.global.shared::cta.bulk_group [%0], [%1], %2;" ::"l"(dst), "r"(src), "r"(bytes) : "memory");
}
__device__ __forceinline__ void bulk_commit() { asm volatile("cp.async.bulk.commit_group;" ::: "memory"); }
__device__ __forceinline__ void bulk_wait_all() { asm volatile("cp.async.bulk.wait_group 0;" ::: "memory"); }
__device__ __forceinline__ void bulk_wait_read() { asm volatile("cp.async.bulk.wait_group.read 0;" ::: "memory"); }
__device__ __forceinline__ void l2_prefetch(const void* p) { asm volatile("prefetch.global.L2 [%0];" ::"l"(p)); }
__device__ __forceinline__ void fence_async_smem() { asm volatile("fence.proxy.async.shared::cta;" ::: "memory"); }
__device__ __forceinline__ void fence_async_global() { asm volatile("fence.proxy.async.global;" ::: "memory"); }
__device__ __forceinline__ void red_relaxed(unsigned* p) { asm volatile("red.relaxed.gpu.global.add.u32 [%0], 1;" ::"l"(p) : "memory"); }
__device__ __forceinline__ unsigned ld_relaxed(const unsigned* p) { unsigned v; asm volatile("ld.relaxed.gpu.global.u32 %0, [%1];" : "=r"(v) : "l"(p) : "memory"); return v; }
__device__ __forceinline__ bool ctr_done(unsigned v, unsigned target) { return ((v - target) & 0x1FFFFFFu) == 0; }
__device__ __forceinline__ void poll(const unsigned* p, unsigned target) { while (!ctr_done(ld_relaxed(p), target)) {} }
__device__ __forceinline__ void poll_slow(const unsigned* p, unsigned target) { while (!ctr_done(ld_relaxed(p), target)) __nanosleep(POLL_NS); }
__device__ __forceinline__ void cell_put(void* p, uint32_t a, uint32_t b, uint32_t tag) {
    asm volatile("st.relaxed.gpu.global.v4.b32 [%0], {%1, %3, %2, %3};" ::"l"(p), "r"(a), "r"(b), "r"(tag) : "memory");
}
__device__ __forceinline__ uint32_t cell_get(const void* p, uint32_t& a, uint32_t& b, uint32_t tag) {
    uint32_t t0, t1;
    asm volatile("ld.relaxed.gpu.global.v4.b32 {%0, %1, %2, %3}, [%4];" : "=r"(a), "=r"(t0), "=r"(b), "=r"(t1) : "l"(p) : "memory");
    return (t0 ^ tag) | (t1 ^ tag);
}
template <int ID, int N> __device__ __forceinline__ void bar_sync() { asm volatile("bar.sync %0, %1;" ::"n"(ID), "n"(N) : "memory"); }
__device__ __forceinline__ void bar_sync_id(int id, int n) { asm volatile("bar.sync %0, %1;" ::"r"(id), "r"(n) : "memory"); }
__device__ __forceinline__ void gate_wait(uint32_t on) { asm volatile("{\n.reg .pred p;\nsetp.ne.u32 p, %0, 0;\n@p bar.sync 4, 256;\n}" ::"r"(on) : "memory"); }
__device__ __forceinline__ void gate_open(uint32_t off) { asm volatile("{\n.reg .pred p;\nsetp.eq.u32 p, %0, 0;\n@p bar.arrive 4, 256;\n}" ::"r"(off) : "memory"); }
__device__ __forceinline__ uint32_t clock32() { uint32_t c; asm volatile("mov.u32 %0, %%clock;" : "=r"(c)::"memory"); return c; }
__device__ __forceinline__ void wg_fence() { asm volatile("wgmma.fence.sync.aligned;" ::: "memory"); }
__device__ __forceinline__ void wg_commit() { asm volatile("wgmma.commit_group.sync.aligned;" ::: "memory"); }
template <int N> __device__ __forceinline__ void wg_wait() { asm volatile("wgmma.wait_group.sync.aligned %0;" ::"n"(N) : "memory"); }
template <int LO = 0, int HI = 56, int N> __device__ __forceinline__ void pin(float (&a)[N]) {
#pragma unroll
    for (int i = LO; i < (HI < N ? HI : N); i++) asm volatile("" : "+f"(a[i])::"memory");
}
__device__ __forceinline__ uint32_t ldg_u16(const void* p) {
    uint32_t v;
    asm volatile("ld.global.nc.u16 %0, [%1];" : "=r"(v) : "l"(p) : "memory");
    return v;
}
__device__ __forceinline__ uint32_t pack2(float lo, float hi) { uint32_t r; asm("cvt.rn.bf16x2.f32 %0, %1, %2;" : "=r"(r) : "f"(hi), "f"(lo)); return r; }
__device__ __forceinline__ float bf_lo(uint32_t v) { return __uint_as_float(v << 16); }
__device__ __forceinline__ float bf_hi(uint32_t v) { return __uint_as_float(v & 0xFFFF0000u); }
__device__ __forceinline__ uint32_t split2(float x) { return pack2(x, x - bf_lo(pack2(x, 0.f))); }
__device__ __forceinline__ void stsm4(uint32_t a, uint32_t r0, uint32_t r1, uint32_t r2, uint32_t r3) {
    asm volatile("stmatrix.sync.aligned.m8n8.x4.shared.b16 [%0], {%1, %2, %3, %4};" ::"r"(a), "r"(r0), "r"(r1), "r"(r2), "r"(r3) : "memory");
}
__device__ __forceinline__ void stsm2(uint32_t a, uint32_t r0, uint32_t r1) {
    asm volatile("stmatrix.sync.aligned.m8n8.x2.shared.b16 [%0], {%1, %2};" ::"r"(a), "r"(r0), "r"(r1) : "memory");
}
__device__ __forceinline__ void ldsm4(uint32_t a, uint32_t (&r)[4]) {
    asm volatile("ldmatrix.sync.aligned.m8n8.x4.shared.b16 {%0, %1, %2, %3}, [%4];" : "=r"(r[0]), "=r"(r[1]), "=r"(r[2]), "=r"(r[3]) : "r"(a) : "memory");
}
__device__ __forceinline__ void ldsm4t(uint32_t a, uint32_t (&r)[4]) {
    asm volatile("ldmatrix.sync.aligned.m8n8.x4.trans.shared.b16 {%0, %1, %2, %3}, [%4];" : "=r"(r[0]), "=r"(r[1]), "=r"(r[2]), "=r"(r[3]) : "r"(a) : "memory");
}
__device__ __forceinline__ void mma16816(float (&c)[4], uint32_t a0, uint32_t a1, uint32_t a2, uint32_t a3, uint32_t b0, uint32_t b1) {
    asm volatile("mma.sync.aligned.m16n8k16.row.col.f32.bf16.bf16.f32 {%0,%1,%2,%3}, {%4,%5,%6,%7}, {%8,%9}, {%0,%1,%2,%3};"
                 : "+f"(c[0]), "+f"(c[1]), "+f"(c[2]), "+f"(c[3]) : "r"(a0), "r"(a1), "r"(a2), "r"(a3), "r"(b0), "r"(b1));
}
__device__ __forceinline__ void mma1688(float (&c)[4], uint32_t a0, uint32_t a1, uint32_t b0) {
    asm volatile("mma.sync.aligned.m16n8k8.row.col.f32.bf16.bf16.f32 {%0,%1,%2,%3}, {%4,%5}, {%6}, {%0,%1,%2,%3};"
                 : "+f"(c[0]), "+f"(c[1]), "+f"(c[2]), "+f"(c[3]) : "r"(a0), "r"(a1), "r"(b0));
}
__device__ __forceinline__ uint32_t desc_lo(uint32_t addr, uint32_t lbo) { return ((addr & 0x3FFFF) >> 4) | ((lbo >> 4) << 16); }
constexpr uint32_t H_SW = (1024 >> 4) | (1u << 30), H_H = 128 >> 4, H_U = 1024 >> 4;
__device__ __forceinline__ float ex2(float x) { float r; asm("ex2.approx.ftz.f32 %0, %1;" : "=f"(r) : "f"(x)); return r; }
__device__ __forceinline__ float rsq(float x) { float r; asm("rsqrt.approx.ftz.f32 %0, %1;" : "=f"(r) : "f"(x)); return r; }
__device__ __forceinline__ float rcp(float x) { float r; asm("rcp.approx.ftz.f32 %0, %1;" : "=f"(r) : "f"(x)); return r; }
__device__ __forceinline__ float gelu_tanh(float x) {
    float y = x * fmaf(x * x, 0.0356774081363f, 0.7978845608029f), t;
    asm("tanh.approx.f32 %0, %1;" : "=f"(t) : "f"(y));
    float hx = 0.5f * x;
    return fmaf(hx, t, hx);
}

template <uint32_t HB, int TB>
__device__ __forceinline__ void wgmma_n56_rs(float (&d)[28], const uint32_t (&a)[4], uint32_t lb, int scale_d) {
    asm volatile("{\n.reg .pred p;\n.reg .b64 db;\nsetp.ne.b32 p, %33, 0;\nmov.b64 db, {%32, %34};\n"
        "wgmma.mma_async.sync.aligned.m64n56k16.f32.bf16.bf16 "
        "{%0, %1, %2, %3, %4, %5, %6, %7, %8, %9, %10, %11, %12, %13, %14, %15, %16, %17, %18, %19, %20, %21, %22, %23, %24, %25, %26, %27}, "
        "{%28, %29, %30, %31}, db, p, 1, 1, %35;\n}\n"
        : "+f"(d[0]), "+f"(d[1]), "+f"(d[2]), "+f"(d[3]), "+f"(d[4]), "+f"(d[5]), "+f"(d[6]), "+f"(d[7]), "+f"(d[8]), "+f"(d[9]), "+f"(d[10]), "+f"(d[11]), "+f"(d[12]), "+f"(d[13]), "+f"(d[14]), "+f"(d[15]), "+f"(d[16]), "+f"(d[17]), "+f"(d[18]), "+f"(d[19]), "+f"(d[20]), "+f"(d[21]), "+f"(d[22]), "+f"(d[23]), "+f"(d[24]), "+f"(d[25]), "+f"(d[26]), "+f"(d[27])
        : "r"(a[0]), "r"(a[1]), "r"(a[2]), "r"(a[3]), "r"(lb), "r"(scale_d), "n"(HB), "n"(TB));
}
template <int TA, uint32_t HA, uint32_t HB>
__device__ __forceinline__ void wgmma_n112(float (&d)[56], uint32_t la, uint32_t lb, int scale_d = 1) {
    asm volatile("{\n.reg .b64 da, db;\n.reg .pred p;\nsetp.ne.b32 p, %61, 0;\nmov.b64 da, {%56, %59};\nmov.b64 db, {%57, %60};\n"
        "wgmma.mma_async.sync.aligned.m64n112k16.f32.bf16.bf16 "
        "{%0, %1, %2, %3, %4, %5, %6, %7, %8, %9, %10, %11, %12, %13, %14, %15, %16, %17, %18, %19, %20, %21, %22, %23, %24, %25, %26, %27, %28, %29, %30, %31, %32, %33, %34, %35, %36, %37, %38, %39, %40, %41, %42, %43, %44, %45, %46, %47, %48, %49, %50, %51, %52, %53, %54, %55}, "
        "da, db, p, 1, 1, %58, 1;\n}\n"
        : "+f"(d[0]), "+f"(d[1]), "+f"(d[2]), "+f"(d[3]), "+f"(d[4]), "+f"(d[5]), "+f"(d[6]), "+f"(d[7]), "+f"(d[8]), "+f"(d[9]), "+f"(d[10]), "+f"(d[11]), "+f"(d[12]), "+f"(d[13]), "+f"(d[14]), "+f"(d[15]), "+f"(d[16]), "+f"(d[17]), "+f"(d[18]), "+f"(d[19]), "+f"(d[20]), "+f"(d[21]), "+f"(d[22]), "+f"(d[23]), "+f"(d[24]), "+f"(d[25]), "+f"(d[26]), "+f"(d[27]), "+f"(d[28]), "+f"(d[29]), "+f"(d[30]), "+f"(d[31]), "+f"(d[32]), "+f"(d[33]), "+f"(d[34]), "+f"(d[35]), "+f"(d[36]), "+f"(d[37]), "+f"(d[38]), "+f"(d[39]), "+f"(d[40]), "+f"(d[41]), "+f"(d[42]), "+f"(d[43]), "+f"(d[44]), "+f"(d[45]), "+f"(d[46]), "+f"(d[47]), "+f"(d[48]), "+f"(d[49]), "+f"(d[50]), "+f"(d[51]), "+f"(d[52]), "+f"(d[53]), "+f"(d[54]), "+f"(d[55])
        : "r"(la), "r"(lb), "n"(TA), "n"(HA), "n"(HB), "r"(scale_d));
}
template <int TA, uint32_t HA, uint32_t HB>
__device__ __forceinline__ void wgmma_n8(float (&d)[4], uint32_t la, uint32_t lb, int scale_d = 1) {
    asm volatile("{\n.reg .b64 da, db;\n.reg .pred p;\nsetp.ne.b32 p, %9, 0;\nmov.b64 da, {%4, %7};\nmov.b64 db, {%5, %8};\n"
        "wgmma.mma_async.sync.aligned.m64n8k16.f32.bf16.bf16 "
        "{%0, %1, %2, %3}, "
        "da, db, p, 1, 1, %6, 1;\n}\n"
        : "+f"(d[0]), "+f"(d[1]), "+f"(d[2]), "+f"(d[3])
        : "r"(la), "r"(lb), "n"(TA), "n"(HA), "n"(HB), "r"(scale_d));
}

__device__ __forceinline__ void send8(const float* a, uint32_t rbuf, uint32_t rbar, uint32_t on) {
    asm volatile("{\n.reg .pred p;\nsetp.ne.u32 p, %6, 0;\n@p st.async.weak.shared::cluster.mbarrier::complete_tx::bytes.v4.b32 [%0], {%1,%2,%3,%4}, [%5];\n}"
                 ::"r"(rbuf), "r"(pack2(a[0], a[1])), "r"(pack2(a[2], a[3])), "r"(pack2(a[4], a[5])), "r"(pack2(a[6], a[7])), "r"(rbar), "r"(on) : "memory");
}
__device__ __forceinline__ void send_half(const float (&a)[56], uint32_t rbuf, uint32_t rbar, int t, uint32_t on) {
#pragma unroll
    for (int i = 0; i < 3; i++) send8(a + 28 + 8 * i, rbuf + i * 2048 + t * 16, rbar, on);
    asm volatile("{\n.reg .pred p;\nsetp.ne.u32 p, %4, 0;\n@p st.async.weak.shared::cluster.mbarrier::complete_tx::bytes.v2.b32 [%0], {%1,%2}, [%3];\n}"
                 ::"r"(rbuf + 6144 + t * 8), "r"(pack2(a[52], a[53])), "r"(pack2(a[54], a[55])), "r"(rbar), "r"(on) : "memory");
}
__device__ __forceinline__ void recv_half(uint32_t (&p)[14], uint32_t buf, int t) {
#pragma unroll
    for (int i = 0; i < 3; i++)
        asm volatile("ld.shared.v4.b32 {%0,%1,%2,%3}, [%4];" : "=r"(p[4 * i]), "=r"(p[4 * i + 1]), "=r"(p[4 * i + 2]), "=r"(p[4 * i + 3]) : "r"(buf + i * 2048 + t * 16) : "memory");
    asm volatile("ld.shared.v2.b32 {%0,%1}, [%2];" : "=r"(p[12]), "=r"(p[13]) : "r"(buf + 6144 + t * 8) : "memory");
}

struct Maps { CUtensorMap xl, x, wqkv, hst, w1, w2, xn, old_, ost, out[2], wo; };

__global__ void __cluster_dims__(2, 1, 1) __launch_bounds__(512, 1)
fused_kernel(const __nv_bfloat16* __restrict__ x, const __nv_bfloat16* __restrict__ wqkv,
             const __nv_bfloat16* __restrict__ b1, const __nv_bfloat16* __restrict__ b2, uint8_t* __restrict__ scr,
             const __nv_bfloat16* __restrict__ w1, const __grid_constant__ Maps mp, const __nv_bfloat16* __restrict__ w2) {
    extern __shared__ __align__(1024) uint8_t smem[];
    const uint32_t sb = smem_u32(smem);
    const uint32_t bar = sb + OFF_BAR;
    const int tid = threadIdx.x, lane = tid & 31;
    const int b = blockIdx.x, z = b & 1, c = b >> 1;
    unsigned* const ctr = reinterpret_cast<unsigned*>(scr + G_CTR);
    if (tid < 112) l2_prefetch(reinterpret_cast<const uint8_t*>(x) + (b * 112 + tid) * 128);
    const int wline = (tid & 127) * 128 + b;
    const bool wfirst = ((wline / 1344) & 1) == 0;
    if (PFW && (tid >> 7) == 1 && wline < 9408 && wfirst) l2_prefetch(reinterpret_cast<const uint8_t*>(wqkv) + wline * 128);
    const uint32_t t_in = clock32();
    TS0(0);
    TG(60);
    const int warp = __shfl_sync(0xffffffffu, tid >> 5, 0);
    int q, j;
    if (c < 4) { q = 15; j = c; } else if (c < 36) { q = (c - 4) & 7; j = (c - 4) >> 3; } else { q = 8 + (c - 36) % 7; j = (c - 36) / 7; }
    const bool g1 = q < 14;
    const int R = q < 8 ? q : q == 15 ? 2 : q < 10 ? q - 8 : q - 7, P = (q >> 3) * 4 + j;
    auto krow = [&](int kb) { const int k = kb + (R & 6); return (k >= 7 ? k - 7 : k) * 64; };
    auto x_load = [&](int kb) {
        mbar_expect(bar + 8 * (B_FULLQ + kb), 40960);
        tma2d(sb + OFF_A + ((XSLOT >> (4 * kb)) & 7) * 16384, &mp.x, z * D_ + krow(kb), R * 128, bar + 8 * (B_FULLQ + kb));
    };
    if (warp == 12 && elect()) {
#pragma unroll
        for (int i = B_FULLQ; i < B_EMPTYQ; i++) mbar_init(bar + 8 * i, 1);
        mbar_expect(bar + 8 * B_LNIN, BLK);
        tma3d(sb + OFF_A, &mp.xl, 0, 16 * b, 0, bar + 8 * B_LNIN);
        x_load(0);
        TS(15);
    }
    if (warp == 13 && elect()) {
#pragma unroll
        for (int i = B_EMPTYQ; i < B_COUNT; i++)
            mbar_init(bar + 8 * i, i < B_EMPTYQ + 2 ? 24 : i < B_FULL ? 8
                                   : i < B_EMPTY ? 2 : i == B_UDONE ? (g1 ? 3 : 1) : (i < B_AUX || i == B_NONE || i == B_OST) ? 8 : i == B_HALO ? 12
                                   : (i == B_UST || i == B_UST + 1 || i == B_AUX) ? 4 : 1);
#pragma unroll
        for (int i = B_RECV1; i < B_UST; i++) mbar_expect(bar + 8 * i, i < B_RECV2 ? 7168 : 8192 - 2048 * z);
    }
    asm volatile("fence.mbarrier_init.release.cluster;" ::: "memory");
    __syncwarp();
    asm volatile("barrier.cluster.arrive.relaxed.aligned;\nbarrier.cluster.wait.aligned;" ::: "memory");
    auto slot = [](uint32_t r) { return r - 6 * ((r * 43) >> 8); };
    auto phase = [](uint32_t r) { return ((r * 43) >> 8) & 1; };
    const uint32_t r_o = g1 ? 16 : 0, r_u = r_o + 5;
    auto epoch = [&]() { mbar_wait(bar + 8 * B_EP, 0); return *reinterpret_cast<volatile unsigned*>(smem + OFF_EP); };

    if (warp < 8) {
        const int wg = warp >> 2, w4 = warp & 3, t = tid & 127, g = lane >> 2, tq = lane & 3;
        asm volatile("setmaxnreg.inc.sync.aligned.u32 208;");
        uint32_t xa[4];
#pragma unroll
        for (int k = 0; k < 4; k++) xa[k] = sb + OFF_A + (warp * 16 + (lane & 15)) * 128 + (((2 * k + (lane >> 4)) ^ (lane & 7)) << 4);
        {
            const int rg = warp & 1, jq = warp >> 1;
            uint32_t r[4][4], la[4], ha[4], ex = sb + OFF_LNX + (rg * 8 + g) * 32;
#pragma unroll
            for (int i = 0; i < 4; i++) {
                const int cg = 14 * jq + 4 * i + ((lane >> 3) & (i < 3 ? 3 : 1));
                la[i] = sb + OFF_A + (cg >> 3) * 2048 + rg * 1024 + (lane & 7) * 128 + (((cg ^ lane) & 7) << 4);
                int pos = 4 * i + (lane >> 3) + (b >= 64 ? 7 : 0);
                if (pos >= 14) pos -= 14;
                ha[i] = sb + OFF_A + jq * 3584 + rg * 1792 + (lane & 7) * 16 + pos * 128;
                asm volatile("" : "+r"(la[i]), "+r"(ha[i]), "+r"(xa[i]), "+r"(ex));
            }
            TS0(46);
            mbar_wait(bar + 8 * B_LNIN, 0);
            TS0(16);
#pragma unroll
            for (int i = 0; i < 4; i++) ldsm4(la[i], r[i]);
            float rs[4] = {0.f, 0.f, 0.f, 0.f}, v[28];
#pragma unroll
            for (int i = 0; i < 3; i++) mma16816(rs, r[i][0], r[i][1], r[i][2], r[i][3], 0x3F803F80u, 0x3F803F80u);
            mma1688(rs, r[3][0], r[3][1], 0x3F803F80u);
            const float mq = (rs[0] + rs[2]) * (1.f / 112);
#pragma unroll
            for (int n = 0; n < 14; n++) { v[2 * n] = bf_lo(r[n >> 2][n & 3]) - mq; v[2 * n + 1] = bf_hi(r[n >> 2][n & 3]) - mq; }
#pragma unroll
            for (int n = 0; n < 28; n++) rs[n & 3] = n < 4 ? v[n] * v[n] : fmaf(v[n], v[n], rs[n & 3]);
            float m2 = (rs[0] + rs[1]) + (rs[2] + rs[3]);
            m2 += __shfl_xor_sync(0xffffffffu, m2, 1);
            m2 += __shfl_xor_sync(0xffffffffu, m2, 2);
            asm volatile("st.shared.v2.f32 [%0], {%1, %2};" ::"r"(ex + jq * 8), "f"(mq), "f"(m2) : "memory");
            bar_sync<1, 256>();
            float4 e0, e1;
            asm volatile("ld.shared.v4.f32 {%0,%1,%2,%3}, [%4];" : "=f"(e0.x), "=f"(e0.y), "=f"(e0.z), "=f"(e0.w) : "r"(ex) : "memory");
            asm volatile("ld.shared.v4.f32 {%0,%1,%2,%3}, [%4];" : "=f"(e1.x), "=f"(e1.y), "=f"(e1.z), "=f"(e1.w) : "r"(ex + 16) : "memory");
            const float mean = 0.25f * ((e0.x + e0.z) + (e1.x + e1.z));
            const float d0 = e0.x - mean, d1 = e0.z - mean, d2 = e1.x - mean, d3 = e1.z - mean;
            const float var = ((e0.y + e0.w) + (e1.y + e1.w)) * (1.f / D_) + 0.25f * (fmaf(d0, d0, d1 * d1) + fmaf(d2, d2, d3 * d3));
            const float r1 = rsq(var + 1e-5f);
            const float sc = r1 * rsq(var * r1 * r1 + 1e-5f), of = (mq - mean) * sc;
#pragma unroll
            for (int n = 0; n < 14; n++) r[n >> 2][n & 3] = pack2(fmaf(v[2 * n], sc, of), fmaf(v[2 * n + 1], sc, of));
#pragma unroll
            for (int i = 0; i < 3; i++) stsm4(ha[i], r[i][0], r[i][1], r[i][2], r[i][3]);
            stsm2(ha[3], r[3][0], r[3][1]);
            *reinterpret_cast<uint2*>(smem + OFF_LNST + (rg * 8 + g) * 8) = make_uint2(__float_as_uint(r1), split2(-mean));
            TS0(24);
            asm volatile("bar.arrive 10, 288;" ::: "memory");
        }
        float a1[56];
        uint32_t bl, bh, cl, ch;
        uint32_t qp[14], kp[14];
        const uint32_t ka = sb + OFF_K + warp * 896 + (lane & 7) * 112 + (lane >> 3) * 16;
        const uint32_t va = sb + OFF_V + (warp * 16 + (lane & 15)) * 112 + (lane >> 4) * 16;
        const uint32_t dA = desc_lo(sb + OFF_A + wg * 8192, 16), dH = desc_lo(sb + OFF_B, 1792), dU = desc_lo(sb + OFF_B, 128);
        auto release = [&](uint32_t a) { mbar_arrive_if0(a, lane); };
        auto sched_fence = [&]() { mbar_wait(bar + 8 * B_LNIN, 0); };
        uint32_t rel = bar + 8 * (B_EMPTYQ + 6);
        auto g1_run = [&](uint32_t r0, uint32_t r1) {
#pragma unroll 1
            for (uint32_t r = g1 ? r0 : r1; r < r1; r++) {
                const uint32_t s = slot(r);
                mbar_wait(bar + 8 * (B_FULL + s), phase(r));
                TS0(64 + r);
                wg_fence();
#pragma unroll
                for (int k = 0; k < 4; k++) wgmma_n112<1, H_SW, H_H>(a1, dA + s * 1024 + k * 128, dH + s * 896 + k * 224, k ? 1 : r);
                wg_commit();
                wg_wait<1>();
                release(rel);
                rel = bar + 8 * (B_EMPTY + s);
            }
        };
        auto drain = [&]() { wg_wait<0>(); release(rel); rel = bar + 8 * B_NONE; };
        {
            float aq0[28], aq1[28], aq2[28];
            const uint32_t dW = desc_lo(sb + OFF_B + (P & 1) * 16, 16);
            uint32_t xf[2][4][4];
            const uint32_t rq = mapa(bar + 8 * (B_EMPTYQ - 1), z ^ 1);
            auto stage = [&](int kb, uint32_t (&f)[4][4]) {
                TS0(178 + kb);
                mbar_wait(bar + 8 * (B_FULLQ + kb), 0);
                TS0(170 + kb);
                const uint32_t sh = 4 * kb;
#pragma unroll
                for (int k = 0; k < 4; k++) ldsm4(xa[k] + ((XSLOT >> sh) & 7) * 16384, f[k]);
                const uint32_t d0 = dW + ((WSLOT >> sh) & 7) * 1536;
                wg_fence();
#pragma unroll
                for (int k = 0; k < 4; k++) {
                    const uint32_t d = d0 + (k >> 1) * 768 + (k & 1) * 128;
                    const int sc = k > 0 ? 1 : kb;
                    wgmma_n56_rs<H_SW, 1>(aq0, f[k], d, sc);
                    wgmma_n56_rs<H_SW, 1>(aq1, f[k], d + 256, sc);
                    wgmma_n56_rs<H_SW, 1>(aq2, f[k], d + 512, sc);
                }
                wg_commit();
                wg_wait<1>();
                mbar_arrive_if0(bar + 8 * (B_EMPTYQ + kb - 1), lane | (kb < 1));
                asm volatile("{\n.reg .pred p;\nsetp.eq.u32 p, %1, 0;\n@p mbarrier.arrive.shared::cluster.b64 _, [%0];\n}"
                             ::"r"(rq + 8 * kb), "r"(lane | ((uint32_t)(kb - 1) > 1)) : "memory");
            };
            stage(0, xf[0]);
#pragma unroll 1
            for (int kb = 1; kb < 7; kb += 2) {
                stage(kb, xf[1]);
                stage(kb + 1, xf[0]);
            }
            TS0(2);
            mbar_wait(bar + 8 * B_AUX, 0);
            {
                uint32_t (&f)[4] = xf[1][0];
                const uint32_t* mt = reinterpret_cast<const uint32_t*>(smem + OFF_STATS) + (warp * 16 + g + 8) * 2 + 1;
                const uint32_t sel = tq == 0 ? 0x1010 : tq == 1 ? 0x3232 : 0x4444;
                f[0] = __byte_perm(mt[0], 0, sel); f[1] = __byte_perm(mt[16], 0, sel); f[2] = f[3] = 0;
                asm volatile("" : "+r"(f[0]), "+r"(f[1]), "+r"(f[2]), "+r"(f[3])::"memory");
                const uint32_t d = desc_lo(sb + OFF_CSB + (P & 1) * 128, 0);
                wg_fence();
                wgmma_n56_rs<H_H, 0>(aq1, f, d + 64, 1);
                wgmma_n56_rs<H_H, 0>(aq2, f, d + 128, 1);
                wgmma_n56_rs<H_H, 0>(aq0, f, d, 1);
                wg_commit();
            }
            g1_run(0, wg ? 0 : NE);
            drain();
            pin(aq0); pin(aq1); pin(aq2);
            TSW(3);
            mbar_wait(bar + 8 * (B_EMPTYQ + 5), 0);
#pragma unroll
            for (int i = 0; i < 14; i++) { kp[i] = pack2(aq1[2 * i], aq1[2 * i + 1]); qp[i] = pack2(aq2[2 * i], aq2[2 * i + 1]); }
            stsm4(ka + 896, kp[1], kp[3], kp[5], kp[7]);
            stsm4(ka + 896 + 48, kp[7], kp[9], kp[11], kp[13]);
#pragma unroll
            for (int n = 0; n < 3; n++) stsm4(va + 896 + n * 32, qp[4 * n], qp[4 * n + 1], qp[4 * n + 2], qp[4 * n + 3]);
            stsm2(va + 896 + 96, qp[12], qp[13]);
            __syncwarp();
            mbar_arrive_if0(bar + 8 * B_QKV, tid - 224);
            release(bar + 8 * B_HALO);
#pragma unroll
            for (int i = 0; i < 14; i++) qp[i] = pack2(aq0[2 * i], aq0[2 * i + 1]);
            TSW(4);
        }
        g1_run(wg ? 0 : NE, ATT_STEP);
        {
            uint32_t kf[2][3][4], vf[2][3][4];
            const bool up0 = 2 * tq > g, up1 = 2 * tq + 1 > g, edge = (R | warp) == 0;
            float rk[2][2], fs[2][2];
#pragma unroll
            for (int i = 0; i < 4; i++) {
                const float* st = reinterpret_cast<const float*>(smem + OFF_STATS) + (warp * 16 + (i >> 1) * 8) * 2;
                rk[i >> 1][i & 1] = st[(2 * tq + (i & 1) + (((i & 1) ? up1 : up0) ? 0 : 8)) * 2];
                fs[i >> 1][i & 1] = rk[i >> 1][i & 1] * (st[(g + 8) * 2] * (0.18898223650461362f * 1.4426950408889634f));
            }
            mbar_wait(bar + 8 * B_HALO, 0);
#pragma unroll
            for (int hd = 0; hd < 2; hd++) {
                ldsm4(ka + hd * 48, kf[hd][0]);
#pragma unroll
                for (int i = 0; i < 4; i++) { kf[hd][1][i] = kp[6 * hd + 2 * i]; kf[hd][2][i] = kp[6 * hd + 2 * i + 1]; }
                ldsm4t(va + hd * 48, vf[hd][0]); ldsm4t(va + hd * 48 + 32, vf[hd][1]);
                ldsm4t(ka + (OFF_V - OFF_K) + warp * 896 + hd * 48 + 1792, vf[hd][2]);
            }
            const uint32_t q0l = tq < 2 ? qp[6] : 0, q0h = tq < 2 ? qp[7] : 0, q1l = tq < 2 ? 0 : qp[6], q1h = tq < 2 ? 0 : qp[7];
            const uint32_t mk = (up0 ? 0xFFFFu : 0u) | (up1 ? 0xFFFF0000u : 0u);
            drain();
            sched_fence();
            TS0(19);
            float sc[2][3][4];
#pragma unroll
            for (int u = 0; u < 3; u++) {
#pragma unroll
                for (int i = 0; i < 8; i++) sc[i >> 2][u][i & 3] = 0.f;
                mma16816(sc[0][u], qp[0], qp[1], qp[2], qp[3], kf[0][u][0], kf[0][u][1]);
                mma16816(sc[1][u], q1l, q1h, qp[8], qp[9], kf[1][u][0], kf[1][u][1]);
            }
#pragma unroll
            for (int u = 0; u < 3; u++) {
                mma16816(sc[0][u], qp[4], qp[5], q0l, q0h, kf[0][u][2], kf[0][u][3]);
                mma16816(sc[1][u], qp[10], qp[11], qp[12], qp[13], kf[1][u][2], kf[1][u][3]);
            }
            float e[2][2][2], mx[2][2], sm[2][2];
#pragma unroll
            for (int hd = 0; hd < 2; hd++) {
                e[hd][0][0] = (up0 ? sc[hd][0][0] : sc[hd][1][0]) * fs[0][0];
                e[hd][0][1] = (up1 ? sc[hd][0][1] : sc[hd][1][1]) * fs[0][1];
                e[hd][1][0] = (up0 ? sc[hd][1][2] : sc[hd][2][2]) * fs[1][0];
                e[hd][1][1] = (up1 ? sc[hd][1][3] : sc[hd][2][3]) * fs[1][1];
                if (edge && up0) e[hd][0][0] = -1e30f;
                if (edge && up1) e[hd][0][1] = -1e30f;
                mx[hd][0] = fmaxf(e[hd][0][0], e[hd][0][1]);
                mx[hd][1] = fmaxf(e[hd][1][0], e[hd][1][1]);
            }
#pragma unroll
            for (int o = 1; o <= 2; o <<= 1)
#pragma unroll
                for (int i = 0; i < 4; i++) mx[i >> 1][i & 1] = fmaxf(mx[i >> 1][i & 1], __shfl_xor_sync(0xffffffffu, mx[i >> 1][i & 1], o));
            uint32_t pp[2][2];
#pragma unroll
            for (int i = 0; i < 4; i++) {
                const float p0 = ex2(e[i >> 1][i & 1][0] - mx[i >> 1][i & 1]), p1 = ex2(e[i >> 1][i & 1][1] - mx[i >> 1][i & 1]);
                pp[i >> 1][i & 1] = pack2(p0 * rk[i & 1][0], p1 * rk[i & 1][1]);
                sm[i >> 1][i & 1] = p0 + p1;
            }
            float ov[2][4][4];
#pragma unroll
            for (int hd = 0; hd < 2; hd++)
#pragma unroll
                for (int n = 0; n < 4; n++) {
                    ov[hd][n][0] = ov[hd][n][1] = ov[hd][n][2] = ov[hd][n][3] = 0.f;
                    mma16816(ov[hd][n], pp[hd][0] & mk, 0u, pp[hd][0] & ~mk, pp[hd][1] & mk, vf[hd][n >> 1][2 * (n & 1)], vf[hd][n >> 1][2 * (n & 1) + 1]);
                }
#pragma unroll
            for (int hd = 0; hd < 2; hd++)
#pragma unroll
                for (int n = 0; n < 4; n++) mma1688(ov[hd][n], 0u, pp[hd][1] & ~mk, vf[hd][2][n]);
            sched_fence();
            bar_sync<1, 256>();
            TS0(18);
            g1_run(ATT_STEP, wg ? ATT_STEP + NP : ATT_STEP);
#pragma unroll
            for (int o = 1; o <= 2; o <<= 1)
#pragma unroll
                for (int i = 0; i < 4; i++) sm[i >> 1][i & 1] += __shfl_xor_sync(0xffffffffu, sm[i >> 1][i & 1], o);
            const uint32_t oa = sb + OFF_OST + (warp * 16 + (lane & 15)) * 128;
            uint32_t op[16];
            op[14] = op[15] = 0;
#pragma unroll
            for (int i = 0; i < 4; i++) sm[i >> 1][i & 1] = rcp(sm[i >> 1][i & 1]);
#pragma unroll
            for (int n = 0; n < 7; n++) {
                const bool hb = n > 3 || (n == 3 && tq >= 2);
#pragma unroll
                for (int h = 0; h < 2; h++) {
                    const float r = hb ? sm[1][h] : sm[0][h];
                    const float x0 = hb ? ov[1][n >= 3 ? n - 3 : 0][2 * h] : ov[0][n <= 3 ? n : 0][2 * h];
                    const float x1 = hb ? ov[1][n >= 3 ? n - 3 : 0][2 * h + 1] : ov[0][n <= 3 ? n : 0][2 * h + 1];
                    op[2 * n + h] = pack2(x0 * r, x1 * r);
                }
            }
#pragma unroll
            for (int n = 0; n < 4; n++) stsm4(oa + (((2 * n + (lane >> 4)) ^ (lane & 7)) << 4), op[4 * n], op[4 * n + 1], op[4 * n + 2], op[4 * n + 3]);
            __syncwarp();
            release(bar + 8 * B_OST);
            TSW(5);
            const int row = q * 128 + warp * 16 + g;
            bl = ldg_u16(b2 + row); bh = ldg_u16(b2 + row + 8);
            cl = ldg_u16(b1 + (g1 ? row : 0)); ch = ldg_u16(b1 + (g1 ? row : 0) + 8);
        }
        const uint32_t peer = z ^ 1;
        uint32_t rs = wg ? ATT_STEP + NP : ATT_STEP;
        if (ATT_STEP + NP < 16 - NS1) { g1_run(rs, wg ? 16 - NS1 : rs); rs = wg ? 16 - NS1 : rs; }
        drain();
        gate_wait(wg);
        g1_run(rs, 16);
        gate_open(wg);
        mbar_wait_cluster(bar + 8 * B_FREE, 0);
        drain();
        pin(a1);
        TSW(6);
        send_half(a1, mapa(sb + OFF_RECV1 + wg * 7168, peer), mapa(bar + 8 * (B_RECV1 + wg), peer), t, g1);
        float a2[56];
        {
            const uint32_t s = slot(r_o);
            mbar_wait(bar + 8 * (B_FULL + s), phase(r_o));
            uint32_t xr[4][4];
#pragma unroll
            for (int k = 0; k < 4; k++) ldsm4(xa[k] + s * 16384, xr[k]);
            if (z) bl = bh = xr[3][0] = xr[3][1] = xr[3][2] = xr[3][3] = 0;
#pragma unroll
            for (int i = 0; i < 56; i++) {
                a2[i] = bf_lo((i & 2) ? bh : bl);
                if (i < 32) a2[i] += (i & 1) ? bf_hi(xr[i >> 3][(i >> 1) & 3]) : bf_lo(xr[i >> 3][(i >> 1) & 3]);
            }
            pin(a2);
            release(bar + 8 * (B_EMPTY + s));
#pragma unroll
            for (int i = 0; i < 28; i++) a1[i] += bf_lo((i & 2) ? ch : cl);
            pin<0, 28>(a1);
        }
        if (g1) {
            uint32_t p[14];
            mbar_wait_cluster(bar + 8 * (B_RECV1 + wg), 0);
            TSW(8);
            recv_half(p, sb + OFF_RECV1 + wg * 7168, t);
#pragma unroll
            for (int i = 0; i < 14; i++) p[i] = pack2(gelu_tanh(a1[2 * i] + bf_lo(p[i])), gelu_tanh(a1[2 * i + 1] + bf_hi(p[i])));
            const uint32_t dst = sb + OFF_UST + wg * 7168 + w4 * 256 + (lane & 15) * 16;
#pragma unroll
            for (int n = 0; n < 3; n++) stsm4(dst + (2 * n + (lane >> 4)) * 1024, p[4 * n], p[4 * n + 1], p[4 * n + 2], p[4 * n + 3]);
            stsm2(dst + 6144, p[12], p[13]);
            __syncwarp();
            release(bar + 8 * (B_UST + wg));
        }
        TSW(9);
#pragma unroll 1
        for (uint32_t r = r_o + 1; r < r_u; r++) {
            const uint32_t s = slot(r);
            mbar_wait(bar + 8 * (B_FULL + s), phase(r));
            TS0(64 + 16 + r - r_o);
            wg_fence();
#pragma unroll
            for (int k = 0; k < 4; k++) wgmma_n112<0, H_SW, H_U>(a2, dA + s * 1024 + k * 2, dU + s * 896 + k * 16);
            wg_commit();
            wg_wait<1>();
            release(rel);
            rel = bar + 8 * (B_EMPTY + s);
        }
        drain();
        TSW(10);
#pragma unroll 1
        for (uint32_t r = r_u; r < r_u + 14; r++) {
            const uint32_t s = slot(r);
            gate_wait(wg && r == r_u + 14 - NS2);
            mbar_wait(bar + 8 * (B_FULL + s), phase(r));
            TS0(85 + r - r_u);
            wg_fence();
#pragma unroll
            for (int k = 0; k < 4; k++) wgmma_n112<1, H_SW, H_U>(a2, dA + s * 1024 + k * 128, dU + s * 896 + k * 16);
            wg_commit();
            wg_wait<1>();
            release(rel);
            rel = bar + 8 * (B_EMPTY + s);
        }
        gate_open(wg);
        mbar_wait_cluster(bar + 8 * B_UDONE, 0);
        wg_wait<0>();
        pin(a2);
        TSW(11);
        {
            const uint32_t rbuf = mapa(sb + OFF_RECV2 + wg * 8192 + t * 16, peer) - (z ? 0 : 2048), rbar = mapa(bar + 8 * (B_RECV2 + wg), peer);
#pragma unroll
            for (int i = 3; i >= 0; i--) send8(a2 + 24 + 8 * i, rbuf + i * 2048, rbar, i | z);
            mbar_wait_cluster(bar + 8 * (B_RECV2 + wg), 0);
            TSW(12);
            const uint32_t dst = sb + OFF_OUT + wg * 8192 + (w4 * 16 + (lane & 15)) * 128;
#pragma unroll
            for (int i = 0; i < 4; i++) {
                uint32_t u[4];
                asm volatile("ld.shared.v4.b32 {%0,%1,%2,%3}, [%4];" : "=r"(u[0]), "=r"(u[1]), "=r"(u[2]), "=r"(u[3]) : "r"(sb + OFF_RECV2 + wg * 8192 + i * 2048 + t * 16) : "memory");
#pragma unroll
                for (int e = 0; e < 4; e++) u[e] = pack2(a2[8 * i + 2 * e] + bf_lo(u[e]), a2[8 * i + 2 * e + 1] + bf_hi(u[e]));
                stsm4(dst + (((2 * i + (lane >> 4)) ^ (lane & 7)) << 4), u[0], u[1], u[2], u[3]);
            }
            bar_sync_id(2 + wg, 128);
            if (w4 == 0 && elect()) {
                fence_async_smem();
                tma2d_store(&mp.out[z], sb + OFF_OUT + wg * 8192, j * 112 + z * 64, q * 128 + wg * 64);
                bulk_commit();
                bulk_wait_read();
            }
        }
        TSW(13);
    } else if (warp < 12) {
        asm volatile("setmaxnreg.dec.sync.aligned.u32 64;");
        const int hw = warp - 8, t = tid & 127;
        while (clock32() - t_in < DLY1) {}
        if (wline < 9408 && !wfirst) l2_prefetch(reinterpret_cast<const uint8_t*>(wqkv) + wline * 128);
        uint8_t* cscell = scr + G_CS + ((P * 8 + R) * 2 + z) * 512 + (t >> 2) * 16;
        if ((lane & 3) == 0) cell_put(cscell, 0, 0, 0);
        uint8_t* cells = scr + G_HALO + ((R * 8 + P) * 2 + z) * 3584 + min(t, 111) * 16;
        cell_put(cells, 0, 0, 0);
        cell_put(cells + 1792, 0, 0, 0);
        reinterpret_cast<uint32_t*>(smem + OFF_ONES)[t] = t < 64 ? 0x3F803F80u : 0;
        fence_async_smem();
        bar_sync<12, 128>();
        const unsigned e1 = epoch();
        {
            const uint32_t da = desc_lo(sb + OFF_B + min((R & 1) * 2 + z, 2) * 4096, 16), db = desc_lo(sb + OFF_ONES, 128);
            float c0[4];
            mbar_wait(bar + 8 * B_FULLQ, 0);
            mbar_wait(bar + 8 * (B_FULLQ + 1), 0);
            TSH(47);
            wg_fence();
#pragma unroll
            for (int k = 0; k < 8; k++)
                wgmma_n8<1, H_SW, H_H>(c0, da + ((WSLOT >> (k & 4)) & 7) * 1536 + (k & 2) * 384 + (k & 1) * 128, db + (k >= 4 && R >= 6 ? 16 : 0), k);
            wg_commit();
            wg_wait<0>();
            pin(c0);
            if ((lane & 3) == 0) cell_put(cscell, __float_as_uint(c0[0]), __float_as_uint(c0[2]), e1);
            if (lane < 4) asm volatile("mbarrier.arrive.shared::cluster.b64 _, [%0];" ::"r"(mapa(bar + 8 * (B_EMPTYQ + (lane >> 1)), lane & 1)) : "memory");
            TSH(43);
        }
        mbar_wait(bar + 8 * (B_FULLQ + GATHER), 0);
        TSH(39);
        {
            const bool cw = hw < 3;
            const uint8_t* src = cw ? scr + G_CS + P * 8192 + t * 16 : scr + G_STATS + (z * 1024 + R * 128 + lane) * 16;
            uint32_t a[5], d[5], bad;
            do {
                bad = 0;
#pragma unroll
                for (int i = 0; i < 4; i++) bad |= cell_get(src + i * (cw ? 2048 : 512), a[i], d[i], e1);
                if (t >= 120) bad |= cell_get(src - (R ? 512 : 0), a[4], d[4], e1);
            } while (bad);
            TSH(45);
            if (cw) {
                uint4* cb = reinterpret_cast<uint4*>(smem + OFF_CSB) + (t >> 3) * 16 + (t & 7);
                const uint32_t lo = split2((__uint_as_float(a[0]) + __uint_as_float(a[1])) + (__uint_as_float(a[2]) + __uint_as_float(a[3])));
                const uint32_t hi = split2((__uint_as_float(d[0]) + __uint_as_float(d[1])) + (__uint_as_float(d[2]) + __uint_as_float(d[3])));
                cb[0] = make_uint4(lo, lo, 0, 0);
                cb[8] = make_uint4(hi, hi, 0, 0);
            } else {
                uint2* st = reinterpret_cast<uint2*>(smem + OFF_STATS) + lane;
#pragma unroll
                for (int i = 0; i < 4; i++) st[8 + 32 * i] = make_uint2(a[i], d[i]);
                if (t >= 120) st[-24] = make_uint2(a[4], d[4]);
            }
            fence_async_smem();
            __syncwarp();
            mbar_arrive_if0(bar + 8 * B_AUX, lane);
            TSH(41);
        }
        {
            uint2* kv = reinterpret_cast<uint2*>(smem + OFF_K) + min(t, 111);
            mbar_wait(bar + 8 * B_QKV, 0);
            uint2 k2 = kv[896], v2 = kv[1792 + (OFF_V - OFF_K) / 8];
            cell_put(cells, k2.x, k2.y, e1);
            cell_put(cells + 1792, v2.x, v2.y, e1);
            k2 = v2 = make_uint2(0, 0);
            if (R > 0) while (cell_get(cells - 16 * 3584, k2.x, k2.y, e1) | cell_get(cells - 16 * 3584 + 1792, v2.x, v2.y, e1)) {}
            kv[0] = k2;
            kv[(OFF_V - OFF_K) / 8] = v2;
            __syncwarp();
            mbar_arrive_if0(bar + 8 * B_HALO, lane);
            TSH(40);
        }
        if (hw == 2) {
            if (elect()) {
                auto tell_peer = [&](int i) {
                    asm volatile("mbarrier.arrive.relaxed.cluster.shared::cluster.b64 _, [%0];" ::"r"(mapa(bar + 8 * i, z ^ 1)) : "memory");
                };
                mbar_wait(bar + 8 * B_OST, 0);
                tell_peer(B_FREE);
                fence_async_smem();
                tma2d_store(&mp.ost, sb + OFF_OST, z * 64, P * 1024 + R * 128);
                bulk_commit();
                bulk_wait_all();
                red_relaxed(ctr + C_O + (R * 2 + (P >> 2)) * 32);
                TS(21);
                tell_peer(B_UDONE);
            }
        } else if (hw < 2 && g1) {
            if (elect()) {
                const int ub = 2 * q + hw, zz = ub >= 14 ? 1 : 0;
                uint8_t* ud = scr + G_BIMG + ((8 + ub) * 4 + j) * BLK;
                mbar_wait(bar + 8 * (B_UST + hw), 0);
                fence_async_smem();
                bulk_store(ud + ((7 * z + 1 + 6 * zz) % 14) * 1024, sb + OFF_UST + hw * 7168 + 1024, 6144);
                bulk_store(ud + (7 * z + 6 * zz) * 1024, sb + OFF_UST + hw * 7168, 1024);
                bulk_commit();
                bulk_wait_all();
                red_relaxed(ctr + C_U + ((j * 2 + zz) * 2 + hw) * 32);
                TS(22 + hw);
                mbar_arrive(bar + 8 * B_UDONE);
            }
        }
    } else {
        asm volatile("setmaxnreg.dec.sync.aligned.u32 32;");
        auto wait_free = [&](uint32_t r, uint32_t first) {
            const uint32_t a = r < 6 ? B_EMPTYQ + ((first >> (4 * r)) & 7) : B_EMPTY + slot(r);
            mbar_wait(bar + 8 * a, r < 6 ? 0 : phase(r) ^ 1);
        };
        if (warp == 12) {
            TS(14);
            if (elect()) {
#pragma unroll 1
                for (int kb = 0; kb < 7; kb++) {
                    if (kb == 1) while (clock32() - t_in < DLY2) {}
                    if (kb >= QDEPTH) mbar_wait(bar + 8 * (B_FULLQ + kb - QDEPTH), 0);
                    if (kb >= 5) mbar_wait(bar + 8 * (B_EMPTYQ + kb - 5), 0);
                    if (kb > 0) x_load(kb);
                    tma3d_mc(sb + OFF_B + ((WSLOT >> (4 * kb)) & 7) * 24576 + z * 12288, &mp.wqkv, (P * 56) & ~15, krow(kb) + z * 32, 0, bar + 8 * (B_FULLQ + kb));
                }
                TS(17);
                ld_relaxed(ctr + C_O + ((q & ~1) + z) * 32);
                mbar_wait(bar + 8 * B_LNFREE, 0);
                if (!g1) {
                    const int ic = (q - 14) * 8 + j * 2 + z, rot = ic >> 3;
                    mbar_wait(bar + 8 * (B_EMPTYQ + 2), 0);
                    mbar_expect(bar + 8 * B_LN, 2 * BLK);
#pragma unroll 1
                    for (int i = 0; i < 2; i++) tma3d(sb + OFF_A + i * BLK, &mp.wo, 0, (ic >> 1) * 56, (z * 2 + i) * 14, bar + 8 * B_LN);
                    mbar_wait(bar + 8 * B_LN, 0);
#pragma unroll 1
                    for (int i = 0; i < 2; i++) {
                        uint8_t* dst = scr + G_BIMG + (ic * 2 + i) * BLK;
                        bulk_store(dst + rot * 6144, sb + OFF_A + i * BLK, 8192);
                        bulk_store(dst + (rot ^ 1) * 8192, sb + OFF_A + i * BLK + 8192, 6144);
                    }
                    bulk_commit();
                    bulk_wait_all();
                    red_relaxed(ctr + C_WO);
                    TS(44);
                }
#pragma unroll 1
                for (uint32_t r = 0; r < r_o; r++) {
                    const uint32_t s = slot(r), fb = bar + 8 * (B_FULL + s);
                    wait_free(r, 0x654320u);
                    mbar_expect(fb, 16384);
                    tma3d(sb + OFF_A + s * 16384, &mp.w1, 0, z * 1024 + r * 64, 2 * q, fb);
                    TS(99 + r);
                }
#pragma unroll 1
                for (uint32_t r = r_o; r < r_u; r++) {
                    const uint32_t s = slot(r), fb = bar + 8 * (B_FULL + s);
                    if (r == r_o + 1) { poll_slow(ctr + C_O + ((q & ~1) + z) * 32, epoch() * 8); fence_async_global(); TS(32); }
                    wait_free(r, 0x654320u);
                    mbar_expect(fb, 16384);
                    if (r == r_o) tma2d(sb + OFF_A + s * 16384, &mp.xn, j * 112 + z * 64, q * 128, fb);
                    else tma2d(sb + OFF_A + s * 16384, &mp.old_, 0, (4 * z + r - r_o - 1) * S_ + q * 128, fb);
                    TS(99 + 16 + r - r_o);
                }
#pragma unroll 1
                for (uint32_t i = 0; i < 14; i++) {
                    const uint32_t r = r_u + i, s = slot(r), fb = bar + 8 * (B_FULL + s);
                    wait_free(r, 0x654320u);
                    mbar_expect(fb, 16384);
                    tma3d(sb + OFF_A + s * 16384, &mp.w2, 0, (14 * z + (i < 7 ? 2 * i : 2 * i - 13)) * 64, 2 * q, fb);
                    TS(99 + 21 + i);
                }
            }
        } else if (warp == 13) {
            if (elect()) {
                const unsigned e1 = epoch();
                ld_relaxed(ctr + C_WO);
                ld_relaxed(ctr + C_U + (j * 2 + z) * 64);
                ld_relaxed(ctr + C_U + (j * 2 + z) * 64 + 32);
                auto run = [&](uint32_t r0, uint32_t n, const uint8_t* src, uint32_t stride, uint32_t ts) {
#pragma unroll 1
                    for (uint32_t r = r0; r < r0 + n; r++, src += stride) {
                        const uint32_t s = slot(r), fb = bar + 8 * (B_FULL + s);
                        wait_free(r, 0x644332u);
                        mbar_expect(fb, BLK);
                        bulk_load(sb + OFF_B + s * BLK, src, BLK, fb);
                        TS(ts + r - r0);
                    }
                };
#pragma unroll 1
                for (int ph = g1 ? 0 : 1; ph < 4; ph++) {
                    if (ph == 0) {
                        mbar_wait(bar + 8 * B_LN, 0);
                    } else if (ph == 1) {
                        wait_free(r_o, 0x644332u);
                        mbar_arrive(bar + 8 * (B_FULL + slot(r_o)));
                        poll_slow(ctr + C_WO, e1 * 16);
                    } else {
                        poll(ctr + C_U + ((j * 2 + z) * 2 + ph - 2) * 32, e1 * 14);
                    }
                    fence_async_global();
                    TS(ph == 0 ? 33 : ph == 2 ? 34 : ph == 3 ? 35 : 63);
                    const uint8_t* src = ph == 0 ? scr + G_HIMG + (64 * z + j) * BLK : scr + G_BIMG + ((ph == 1 ? 4 * z : 6 + 14 * z + ph) * 4 + j) * BLK;
                    const uint32_t off = ph == 1 ? 1 : 7 * ph - 9;
                    run(ph == 0 ? 0 : r_o + off, ph == 0 ? 16 : ph == 1 ? 4 : 7, src, ph < 2 ? 4 * BLK : 8 * BLK, 134 + (ph == 0 ? 0 : 16 + off));
                }
            }
        } else if (warp == 14) {
            unsigned* lnc = ctr + C_LN + 32 * (c & 7);
            uint8_t* stcell = scr + G_STATS + ((lane & 1) * 1024 + 8 * b + (lane >> 1)) * 16;
            if (lane < 16) cell_put(stcell, 0, 0, 0);
            const unsigned e1 = (ld_relaxed(lnc) >> 7) + 1;
            if (lane == 0) {
                *reinterpret_cast<volatile unsigned*>(smem + OFF_EP) = e1;
                mbar_arrive(bar + 8 * B_EP);
                TS(36);
            }
            bar_sync<10, 288>();
            if (elect()) {
                fence_async_smem();
                TS(42);
                tma4d_store(&mp.hst, sb + OFF_A, 0, 0, b & 3, b & ~3);
                bulk_commit();
            }
            __syncwarp();
            if (lane < 16) {
                const uint2 v = reinterpret_cast<const uint2*>(smem + OFF_LNST)[lane];
                cell_put(stcell, v.x, v.y, e1);
            }
            bulk_wait_all();
            __syncwarp();
            if (lane < 8) red_relaxed(ctr + C_LN + 32 * lane);
            if (lane == 0) {
                mbar_arrive(bar + 8 * B_LNFREE);
                TS(37);
                if (g1) {
                    poll(lnc, e1 * 128);
                    mbar_arrive(bar + 8 * B_LN);
                }
            }
        } else {
            if (elect()) {
#pragma unroll 1
                for (int i = 2; i < 12; i++) asm volatile("prefetch.tensormap [%0];" ::"l"(reinterpret_cast<const CUtensorMap*>(&mp) + i) : "memory");
            }
            __syncwarp();
#pragma unroll 1
            for (int i = 0; i < PF_N; i++) {
                while (clock32() - t_in < PF_T0 + i * PF_DT) __nanosleep(32);
                const int k = i - 16;
                if (k >= 0) l2_prefetch(w2 + (size_t)(((b >> 6) * 14 + (k < 7 ? 2 * k : 2 * k - 13)) * 64 + (b & 63)) * S_ + lane * 64);
                else if (lane < 28) l2_prefetch(w1 + (size_t)((b >> 6) * 1024 + i * 64 + (b & 63)) * 1792 + lane * 64);
            }
            if (elect()) {
                mbar_watch(bar + 8 * B_RECV2);
                mbar_watch(bar + 8 * (B_RECV2 + 1));
            }
        }
    }
}

typedef CUresult (*EncodeFn)(CUtensorMap*, CUtensorMapDataType, cuuint32_t, void*, const cuuint64_t*, const cuuint64_t*, const cuuint32_t*,
                             const cuuint32_t*, CUtensorMapInterleave, CUtensorMapSwizzle, CUtensorMapL2promotion, CUtensorMapFloatOOBfill);

void encode(EncodeFn fn, CUtensorMap* m, const void* p, int rank, const cuuint64_t* dims, const cuuint64_t* strides, const cuuint32_t* box, bool swz) {
    const cuuint32_t es[4] = {1, 1, 1, 1};
    fn(m, CU_TENSOR_MAP_DATA_TYPE_BFLOAT16, rank, const_cast<void*>(p), dims, strides, box, es, CU_TENSOR_MAP_INTERLEAVE_NONE,
       swz ? CU_TENSOR_MAP_SWIZZLE_128B : CU_TENSOR_MAP_SWIZZLE_NONE, CU_TENSOR_MAP_L2_PROMOTION_L2_128B, CU_TENSOR_MAP_FLOAT_OOB_FILL_NONE);
}

}

extern "C" void kernel_launch(void* const* d_in, const int* in_sizes, int n_in, void* d_out, int out_size) {
    const __nv_bfloat16* x = (const __nv_bfloat16*)d_in[0];
    const __nv_bfloat16* wqkv = (const __nv_bfloat16*)d_in[1];
    const __nv_bfloat16* wo = (const __nv_bfloat16*)d_in[2];
    const __nv_bfloat16* w1 = (const __nv_bfloat16*)d_in[4];
    const __nv_bfloat16* b1 = (const __nv_bfloat16*)d_in[5];
    const __nv_bfloat16* w2 = (const __nv_bfloat16*)d_in[6];
    const __nv_bfloat16* b2 = (const __nv_bfloat16*)d_in[7];

    void* fp = nullptr;
    cudaDriverEntryPointQueryResult qr;
    cudaGetDriverEntryPoint("cuTensorMapEncodeTiled", &fp, cudaEnableDefault, &qr);
    EncodeFn fn = (EncodeFn)fp;
    void* sp = nullptr;
    cudaGetSymbolAddress(&sp, g_scratch);
    uint8_t* scr = (uint8_t*)sp;
    void *o = scr + G_O, *himg = scr + G_HIMG;

    Maps mp;
    { cuuint64_t d[3] = {64, 2048, 7}, s[2] = {896, 128}; cuuint32_t bx[3] = {64, 16, 7}; encode(fn, &mp.xl, x, 3, d, s, bx, true); }
    { cuuint64_t d[2] = {896, 1024}, s[1] = {1792}; cuuint32_t bx[2] = {64, 128}; encode(fn, &mp.x, x, 2, d, s, bx, true); }
    { cuuint64_t d[3] = {448, 448, 3}, s[2] = {2688, 896}; cuuint32_t bx[3] = {64, 32, 3}; encode(fn, &mp.wqkv, wqkv, 3, d, s, bx, true); }
    { cuuint64_t d[3] = {64, 2048, 28}, s[2] = {3584, 128}; cuuint32_t bx[3] = {64, 64, 2}; encode(fn, &mp.w1, w1, 3, d, s, bx, true); }
    { cuuint64_t d[3] = {64, 1792, 32}, s[2] = {4096, 128}; cuuint32_t bx[3] = {64, 64, 2}; encode(fn, &mp.w2, w2, 3, d, s, bx, true); }
    { cuuint64_t d[4] = {64, 28, 4, 128}, s[3] = {128, 3584, BLK}; cuuint32_t bx[4] = {64, 28, 1, 4}; encode(fn, &mp.hst, himg, 4, d, s, bx, false); }
    { cuuint64_t d[2] = {448, 2048}, s[1] = {896}; cuuint32_t bx[2] = {64, 128}; encode(fn, &mp.xn, x, 2, d, s, bx, true); }
    { cuuint64_t d[2] = {64, 8 * 2048}, s[1] = {128}; cuuint32_t bx[2] = {64, 128}; encode(fn, &mp.old_, o, 2, d, s, bx, true); }
    { cuuint64_t d[2] = {128, 8 * 1024}, s[1] = {256}; cuuint32_t bx[2] = {64, 128}; encode(fn, &mp.ost, o, 2, d, s, bx, true); }
    { cuuint64_t d[2] = {448, 2048}, s[1] = {896}; cuuint32_t bx[2] = {64, 64}; encode(fn, &mp.out[0], d_out, 2, d, s, bx, true); }
    { cuuint64_t d[2] = {448, 2048}, s[1] = {896}; cuuint32_t bx[2] = {48, 64}; encode(fn, &mp.out[1], d_out, 2, d, s, bx, true); }
    { cuuint64_t d[3] = {8, 448, 56}, s[2] = {896, 16}; cuuint32_t bx[3] = {8, 64, 14}; encode(fn, &mp.wo, wo, 3, d, s, bx, false); }

    cudaFuncSetAttribute(fused_kernel, cudaFuncAttributeMaxDynamicSharedMemorySize, SMEM_BYTES);
    fused_kernel<<<128, 512, SMEM_BYTES>>>(x, wqkv, b1, b2, scr, w1, mp, w2);
}
```

```cpp
#include <cuda_runtime.h>
#include <cuda.h>
#include <cuda_bf16.h>
#include <stdint.h>

namespace {

constexpr int S_ = 2048, D_ = 448;
constexpr uint32_t BLK = 14336;

constexpr uint32_t G_HIMG = 0;
constexpr uint32_t G_BIMG = G_HIMG + 32 * 4 * BLK;
constexpr uint32_t G_O = G_BIMG + 36 * 4 * BLK;
constexpr uint32_t G_STATS = G_O + 8 * S_ * 128;
constexpr uint32_t G_CS = G_STATS + S_ * 16;
constexpr uint32_t G_HALO = G_CS + 8 * 4 * 2048;
constexpr uint32_t G_CTR = G_HALO + 128 * 3584;
constexpr uint32_t G_END = G_CTR + (192 + 16 * 32) * 4;
__device__ __align__(1024) uint8_t g_scratch[G_END];

constexpr int C_LN = 0, C_WO = 32, C_U = 64, C_O = 192;

#define TSX(sel, id)
#define TS(id)
#define TS0(id)
#define TSH(id)
#define TSW(id)
#define TG(id)

#define TSD(id)
#define QDEPTH 3
#define SPIN
#define ROT 6
#define KS 3
#define QUNROLL 1
#define DLY0 0
#define DLY1 1600
#define DLY2 2000
#define GATHER 3
#define PFW 0
#define PF_N 0
#define PF_T0 13500
#define PF_DT 350
#define NS1 5
#define NS2 4
#define NE 2
#define NP 1
constexpr uint32_t OFF_A = 0;
constexpr uint32_t OFF_B = 98304;
constexpr uint32_t OFF_X = 184320;
constexpr uint32_t OFF_K = 196608;
constexpr uint32_t OFF_V = OFF_K + 9 * 896;
constexpr uint32_t OFF_OST = OFF_X, OFF_RECV2 = OFF_X, OFF_RECV1 = OFF_X + 16384, OFF_UST = OFF_X + 30720, OFF_OUT = OFF_X + 16384;
constexpr uint32_t OFF_CSB = 221184;
constexpr uint32_t OFF_ONES = OFF_CSB + 3072;
constexpr uint32_t OFF_STATS = OFF_ONES + 512;
constexpr uint32_t OFF_LNX = OFF_STATS + 1088;
constexpr uint32_t OFF_LNST = 229376;
constexpr uint32_t OFF_EP = OFF_LNST + 128;
constexpr uint32_t OFF_BAR = OFF_EP + 16;
constexpr uint32_t OFF_TS = OFF_BAR + 8 * 46;
constexpr uint32_t SMEM_BYTES = OFF_TS;

enum : int {
    B_FULLQ = 0, B_LNIN = 7, B_EMPTYQ = 8, B_FULL = 15, B_EMPTY = 21, B_AUX = 27, B_QKV = 28, B_HALO = 29, B_FREE = 30,
    B_RECV1 = 31, B_RECV2 = 33, B_UST = 35, B_EP = 37, B_OST = 38, B_LNFREE = 39, B_UDONE = 40, B_NONE = 41, B_GO = 42, B_COUNT = 46
};
constexpr int kQUnroll = QUNROLL;
constexpr uint32_t XSLOT = 0x5432154u;
constexpr uint32_t WSLOT = 0x3421034u;
#define ATT_STEP 10

__device__ __forceinline__ uint32_t smem_u32(const void* p) { return (uint32_t)__cvta_generic_to_shared(p); }
__device__ __forceinline__ void mbar_init(uint32_t a, int c) { asm volatile("mbarrier.init.shared::cta.b64 [%0], %1;" ::"r"(a), "r"(c) : "memory"); }
__device__ __forceinline__ void mbar_expect(uint32_t a, uint32_t b) { asm volatile("mbarrier.arrive.expect_tx.shared::cta.b64 _, [%0], %1;" ::"r"(a), "r"(b) : "memory"); }
__device__ __forceinline__ void mbar_arrive(uint32_t a) { asm volatile("mbarrier.arrive.shared::cta.b64 _, [%0];" ::"r"(a) : "memory"); }
__device__ __forceinline__ void mbar_arrive_if0(uint32_t a, uint32_t sel) {
    asm volatile("{\n.reg .pred p;\nsetp.eq.u32 p, %1, 0;\n@p mbarrier.arrive.shared::cta.b64 _, [%0];\n}" ::"r"(a), "r"(sel) : "memory");
}
__device__ __forceinline__ void mbar_wait(uint32_t a, uint32_t parity) {
    asm volatile("{\n.reg .pred p;\nW0:\nmbarrier.try_wait.parity.shared::cta.b64 p, [%0], %1;\n@!p bra W0;\n}\n" ::"r"(a), "r"(parity) : "memory");
}
__device__ __forceinline__ void mbar_wait_cluster(uint32_t a, uint32_t parity) {
    asm volatile("{\n.reg .pred p;\nW0:\nmbarrier.try_wait.parity.acquire.cluster.shared::cta.b64 p, [%0], %1;\n@!p bra W0;\n}\n" ::"r"(a), "r"(parity) : "memory");
}
__device__ __forceinline__ void mbar_watch(uint32_t a) {
    asm volatile(
        "{\n.reg .pred p;\n.reg .u32 n;\nmov.u32 n, 0;\n"
        "W0:\nmbarrier.try_wait.parity.shared::cta.b64 p, [%0], 0;\n@p bra W1;\n"
        "add.u32 n, n, 1;\nsetp.lt.u32 p, n, 4194304;\n@p bra W0;\ntrap;\nW1:\n}\n" ::"r"(a) : "memory");
}
__device__ __forceinline__ bool elect() {
    uint32_t r;
    asm volatile("{\n.reg .pred p;\nelect.sync _|p, 0xffffffff;\nselp.u32 %0, 1, 0, p;\n}" : "=r"(r));
    return r;
}
__device__ __forceinline__ uint32_t mapa(uint32_t a, uint32_t cta) { uint32_t r; asm("mapa.shared::cluster.u32 %0, %1, %2;" : "=r"(r) : "r"(a), "r"(cta)); return r; }
__device__ __forceinline__ void tma2d(uint32_t dst, const CUtensorMap* m, int c0, int c1, uint32_t bar) {
    asm volatile("cp.async.bulk.tensor.2d.shared::cluster.global.mbarrier::complete_tx::bytes [%0], [%1, {%3, %4}], [%2];" ::"r"(dst), "l"(m), "r"(bar), "r"(c0), "r"(c1) : "memory");
}
__device__ __forceinline__ void tma3d(uint32_t dst, const CUtensorMap* m, int c0, int c1, int c2, uint32_t bar) {
    asm volatile("cp.async.bulk.tensor.3d.shared::cluster.global.mbarrier::complete_tx::bytes [%0], [%1, {%3, %4, %5}], [%2];" ::"r"(dst), "l"(m), "r"(bar), "r"(c0), "r"(c1), "r"(c2) : "memory");
}
__device__ __forceinline__ void tma3d_mc(uint32_t dst, const CUtensorMap* m, int c0, int c1, int c2, uint32_t bar) {
    asm volatile("cp.async.bulk.tensor.3d.shared::cluster.global.mbarrier::complete_tx::bytes.multicast::cluster [%0], [%1, {%3, %4, %5}], [%2], %6;"
                 ::"r"(dst), "l"(m), "r"(bar), "r"(c0), "r"(c1), "r"(c2), "h"((uint16_t)3) : "memory");
}
__device__ __forceinline__ void tma2d_store(const CUtensorMap* m, uint32_t src, int c0, int c1) {
    asm volatile("cp.async.bulk.tensor.2d.global.shared::cta.bulk_group [%0, {%2, %3}], [%1];" ::"l"(m), "r"(src), "r"(c0), "r"(c1) : "memory");
}
__device__ __forceinline__ void tma4d_store(const CUtensorMap* m, uint32_t src, int c0, int c1, int c2, int c3) {
    asm volatile("cp.async.bulk.tensor.4d.global.shared::cta.bulk_group [%0, {%2, %3, %4, %5}], [%1];" ::"l"(m), "r"(src), "r"(c0), "r"(c1), "r"(c2), "r"(c3) : "memory");
}
__device__ __forceinline__ void bulk_load(uint32_t dst, const void* src, uint32_t bytes, uint32_t bar) {
    asm volatile("cp.async.bulk.shared::cluster.global.mbarrier::complete_tx::bytes [%0], [%1], %2, [%3];" ::"r"(dst), "l"(src), "r"(bytes), "r"(bar) : "memory");
}
__device__ __forceinline__ void bulk_store(void* dst, uint32_t src, uint32_t bytes) {
    asm volatile("cp.async.bulk.global.shared::cta.bulk_group [%0], [%1], %2;" ::"l"(dst), "r"(src), "r"(bytes) : "memory");
}
__device__ __forceinline__ void bulk_commit() { asm volatile("cp.async.bulk.commit_group;" ::: "memory"); }
__device__ __forceinline__ void bulk_wait_all() { asm volatile("cp.async.bulk.wait_group 0;" ::: "memory"); }
__device__ __forceinline__ void bulk_wait_read() { asm volatile("cp.async.bulk.wait_group.read 0;" ::: "memory"); }
__device__ __forceinline__ void l2_prefetch(const void* p) { asm volatile("prefetch.global.L2 [%0];" ::"l"(p)); }
__device__ __forceinline__ void fence_async_smem() { asm volatile("fence.proxy.async.shared::cta;" ::: "memory"); }
__device__ __forceinline__ void fence_async_global() { asm volatile("fence.proxy.async.global;" ::: "memory"); }
__device__ __forceinline__ void red_relaxed(unsigned* p) { asm volatile("red.relaxed.gpu.global.add.u32 [%0], 1;" ::"l"(p) : "memory"); }
__device__ __forceinline__ unsigned ld_relaxed(const unsigned* p) { unsigned v; asm volatile("ld.relaxed.gpu.global.u32 %0, [%1];" : "=r"(v) : "l"(p) : "memory"); return v; }
__device__ __forceinline__ bool ctr_done(unsigned v, unsigned target) { return ((v - target) & 0x1FFFFFFu) == 0; }
__device__ __forceinline__ uint32_t clock32() { uint32_t c; asm volatile("mov.u32 %0, %%clock;" : "=r"(c)::"memory"); return c; }
__device__ __forceinline__ void poll(const unsigned* p, unsigned target) { while (!ctr_done(ld_relaxed(p), target)) {} }
__device__ __forceinline__ void cell_put(void* p, uint32_t a, uint32_t b, uint32_t tag) {
    asm volatile("st.relaxed.gpu.global.v4.b32 [%0], {%1, %3, %2, %3};" ::"l"(p), "r"(a), "r"(b), "r"(tag) : "memory");
}
__device__ __forceinline__ uint32_t cell_get(const void* p, uint32_t& a, uint32_t& b, uint32_t tag) {
    uint32_t t0, t1;
    asm volatile("ld.relaxed.gpu.global.v4.b32 {%0, %1, %2, %3}, [%4];" : "=r"(a), "=r"(t0), "=r"(b), "=r"(t1) : "l"(p) : "memory");
    return (t0 ^ tag) | (t1 ^ tag);
}
template <int ID, int N> __device__ __forceinline__ void bar_sync() { asm volatile("bar.sync %0, %1;" ::"n"(ID), "n"(N) : "memory"); }
__device__ __forceinline__ void bar_sync_id(int id, int n) { asm volatile("bar.sync %0, %1;" ::"r"(id), "r"(n) : "memory"); }
__device__ __forceinline__ void gate_wait(uint32_t on) { asm volatile("{\n.reg .pred p;\nsetp.ne.u32 p, %0, 0;\n@p bar.sync 4, 256;\n}" ::"r"(on) : "memory"); }
__device__ __forceinline__ void gate_open(uint32_t off) { asm volatile("{\n.reg .pred p;\nsetp.eq.u32 p, %0, 0;\n@p bar.arrive 4, 256;\n}" ::"r"(off) : "memory"); }
__device__ __forceinline__ void wg_fence() { asm volatile("wgmma.fence.sync.aligned;" ::: "memory"); }
__device__ __forceinline__ void wg_commit() { asm volatile("wgmma.commit_group.sync.aligned;" ::: "memory"); }
template <int N> __device__ __forceinline__ void wg_wait() { asm volatile("wgmma.wait_group.sync.aligned %0;" ::"n"(N) : "memory"); }
template <int LO = 0, int HI = 56, int N> __device__ __forceinline__ void pin(float (&a)[N]) {
#pragma unroll
    for (int i = LO; i < (HI < N ? HI : N); i++) asm volatile("" : "+f"(a[i])::"memory");
}
__device__ __forceinline__ uint32_t ldg_u16(const void* p) {
    uint32_t v;
    asm volatile("ld.global.nc.u16 %0, [%1];" : "=r"(v) : "l"(p) : "memory");
    return v;
}
__device__ __forceinline__ uint32_t pack2(float lo, float hi) { uint32_t r; asm("cvt.rn.bf16x2.f32 %0, %1, %2;" : "=r"(r) : "f"(hi), "f"(lo)); return r; }
__device__ __forceinline__ float bf_lo(uint32_t v) { return __uint_as_float(v << 16); }
__device__ __forceinline__ float bf_hi(uint32_t v) { return __uint_as_float(v & 0xFFFF0000u); }
__device__ __forceinline__ uint32_t split2(float x) { return pack2(x, x - bf_lo(pack2(x, 0.f))); }
__device__ __forceinline__ void stsm4(uint32_t a, uint32_t r0, uint32_t r1, uint32_t r2, uint32_t r3) {
    asm volatile("stmatrix.sync.aligned.m8n8.x4.shared.b16 [%0], {%1, %2, %3, %4};" ::"r"(a), "r"(r0), "r"(r1), "r"(r2), "r"(r3) : "memory");
}
__device__ __forceinline__ void stsm2(uint32_t a, uint32_t r0, uint32_t r1) {
    asm volatile("stmatrix.sync.aligned.m8n8.x2.shared.b16 [%0], {%1, %2};" ::"r"(a), "r"(r0), "r"(r1) : "memory");
}
__device__ __forceinline__ void ldsm4(uint32_t a, uint32_t (&r)[4]) {
    asm volatile("ldmatrix.sync.aligned.m8n8.x4.shared.b16 {%0, %1, %2, %3}, [%4];" : "=r"(r[0]), "=r"(r[1]), "=r"(r[2]), "=r"(r[3]) : "r"(a) : "memory");
}
__device__ __forceinline__ void ldsm4t(uint32_t a, uint32_t (&r)[4]) {
    asm volatile("ldmatrix.sync.aligned.m8n8.x4.trans.shared.b16 {%0, %1, %2, %3}, [%4];" : "=r"(r[0]), "=r"(r[1]), "=r"(r[2]), "=r"(r[3]) : "r"(a) : "memory");
}
__device__ __forceinline__ void mma16816(float (&c)[4], uint32_t a0, uint32_t a1, uint32_t a2, uint32_t a3, uint32_t b0, uint32_t b1) {
    asm volatile("mma.sync.aligned.m16n8k16.row.col.f32.bf16.bf16.f32 {%0,%1,%2,%3}, {%4,%5,%6,%7}, {%8,%9}, {%0,%1,%2,%3};"
                 : "+f"(c[0]), "+f"(c[1]), "+f"(c[2]), "+f"(c[3]) : "r"(a0), "r"(a1), "r"(a2), "r"(a3), "r"(b0), "r"(b1));
}
__device__ __forceinline__ void mma1688(float (&c)[4], uint32_t a0, uint32_t a1, uint32_t b0) {
    asm volatile("mma.sync.aligned.m16n8k8.row.col.f32.bf16.bf16.f32 {%0,%1,%2,%3}, {%4,%5}, {%6}, {%0,%1,%2,%3};"
                 : "+f"(c[0]), "+f"(c[1]), "+f"(c[2]), "+f"(c[3]) : "r"(a0), "r"(a1), "r"(b0));
}
__device__ __forceinline__ uint32_t desc_lo(uint32_t addr, uint32_t lbo) { return ((addr & 0x3FFFF) >> 4) | ((lbo >> 4) << 16); }
constexpr uint32_t H_SW = (1024 >> 4) | (1u << 30), H_H = 128 >> 4, H_U = 1024 >> 4;
__device__ __forceinline__ float ex2(float x) { float r; asm("ex2.approx.ftz.f32 %0, %1;" : "=f"(r) : "f"(x)); return r; }
__device__ __forceinline__ float rsq(float x) { float r; asm("rsqrt.approx.ftz.f32 %0, %1;" : "=f"(r) : "f"(x)); return r; }
__device__ __forceinline__ float rcp(float x) { float r; asm("rcp.approx.ftz.f32 %0, %1;" : "=f"(r) : "f"(x)); return r; }
__device__ __forceinline__ float gelu_tanh(float x) {
    float y = x * fmaf(x * x, 0.0356774081363f, 0.7978845608029f), t;
    asm("tanh.approx.f32 %0, %1;" : "=f"(t) : "f"(y));
    float hx = 0.5f * x;
    return fmaf(hx, t, hx);
}

template <uint32_t HB, int TB>
__device__ __forceinline__ void wgmma_n56_rs(float (&d)[28], const uint32_t (&a)[4], uint32_t lb, int scale_d) {
    asm volatile("{\n.reg .pred p;\n.reg .b64 db;\nsetp.ne.b32 p, %33, 0;\nmov.b64 db, {%32, %34};\n"
        "wgmma.mma_async.sync.aligned.m64n56k16.f32.bf16.bf16 "
        "{%0, %1, %2, %3, %4, %5, %6, %7, %8, %9, %10, %11, %12, %13, %14, %15, %16, %17, %18, %19, %20, %21, %22, %23, %24, %25, %26, %27}, "
        "{%28, %29, %30, %31}, db, p, 1, 1, %35;\n}\n"
        : "+f"(d[0]), "+f"(d[1]), "+f"(d[2]), "+f"(d[3]), "+f"(d[4]), "+f"(d[5]), "+f"(d[6]), "+f"(d[7]), "+f"(d[8]), "+f"(d[9]), "+f"(d[10]), "+f"(d[11]), "+f"(d[12]), "+f"(d[13]), "+f"(d[14]), "+f"(d[15]), "+f"(d[16]), "+f"(d[17]), "+f"(d[18]), "+f"(d[19]), "+f"(d[20]), "+f"(d[21]), "+f"(d[22]), "+f"(d[23]), "+f"(d[24]), "+f"(d[25]), "+f"(d[26]), "+f"(d[27])
        : "r"(a[0]), "r"(a[1]), "r"(a[2]), "r"(a[3]), "r"(lb), "r"(scale_d), "n"(HB), "n"(TB));
}
template <int TA, uint32_t HA, uint32_t HB>
__device__ __forceinline__ void wgmma_n112(float (&d)[56], uint32_t la, uint32_t lb, int scale_d = 1) {
    asm volatile("{\n.reg .b64 da, db;\n.reg .pred p;\nsetp.ne.b32 p, %61, 0;\nmov.b64 da, {%56, %59};\nmov.b64 db, {%57, %60};\n"
        "wgmma.mma_async.sync.aligned.m64n112k16.f32.bf16.bf16 "
        "{%0, %1, %2, %3, %4, %5, %6, %7, %8, %9, %10, %11, %12, %13, %14, %15, %16, %17, %18, %19, %20, %21, %22, %23, %24, %25, %26, %27, %28, %29, %30, %31, %32, %33, %34, %35, %36, %37, %38, %39, %40, %41, %42, %43, %44, %45, %46, %47, %48, %49, %50, %51, %52, %53, %54, %55}, "
        "da, db, p, 1, 1, %58, 1;\n}\n"
        : "+f"(d[0]), "+f"(d[1]), "+f"(d[2]), "+f"(d[3]), "+f"(d[4]), "+f"(d[5]), "+f"(d[6]), "+f"(d[7]), "+f"(d[8]), "+f"(d[9]), "+f"(d[10]), "+f"(d[11]), "+f"(d[12]), "+f"(d[13]), "+f"(d[14]), "+f"(d[15]), "+f"(d[16]), "+f"(d[17]), "+f"(d[18]), "+f"(d[19]), "+f"(d[20]), "+f"(d[21]), "+f"(d[22]), "+f"(d[23]), "+f"(d[24]), "+f"(d[25]), "+f"(d[26]), "+f"(d[27]), "+f"(d[28]), "+f"(d[29]), "+f"(d[30]), "+f"(d[31]), "+f"(d[32]), "+f"(d[33]), "+f"(d[34]), "+f"(d[35]), "+f"(d[36]), "+f"(d[37]), "+f"(d[38]), "+f"(d[39]), "+f"(d[40]), "+f"(d[41]), "+f"(d[42]), "+f"(d[43]), "+f"(d[44]), "+f"(d[45]), "+f"(d[46]), "+f"(d[47]), "+f"(d[48]), "+f"(d[49]), "+f"(d[50]), "+f"(d[51]), "+f"(d[52]), "+f"(d[53]), "+f"(d[54]), "+f"(d[55])
        : "r"(la), "r"(lb), "n"(TA), "n"(HA), "n"(HB), "r"(scale_d));
}
template <int TA, uint32_t HA, uint32_t HB>
__device__ __forceinline__ void wgmma_n8(float (&d)[4], uint32_t la, uint32_t lb, int scale_d = 1) {
    asm volatile("{\n.reg .b64 da, db;\n.reg .pred p;\nsetp.ne.b32 p, %9, 0;\nmov.b64 da, {%4, %7};\nmov.b64 db, {%5, %8};\n"
        "wgmma.mma_async.sync.aligned.m64n8k16.f32.bf16.bf16 "
        "{%0, %1, %2, %3}, "
        "da, db, p, 1, 1, %6, 1;\n}\n"
        : "+f"(d[0]), "+f"(d[1]), "+f"(d[2]), "+f"(d[3])
        : "r"(la), "r"(lb), "n"(TA), "n"(HA), "n"(HB), "r"(scale_d));
}

__device__ __forceinline__ void send8(const float* a, uint32_t rbuf, uint32_t rbar, uint32_t on) {
    asm volatile("{\n.reg .pred p;\nsetp.ne.u32 p, %6, 0;\n@p st.async.weak.shared::cluster.mbarrier::complete_tx::bytes.v4.b32 [%0], {%1,%2,%3,%4}, [%5];\n}"
                 ::"r"(rbuf), "r"(pack2(a[0], a[1])), "r"(pack2(a[2], a[3])), "r"(pack2(a[4], a[5])), "r"(pack2(a[6], a[7])), "r"(rbar), "r"(on) : "memory");
}
__device__ __forceinline__ void send_half(const float (&a)[56], uint32_t rbuf, uint32_t rbar, int t, uint32_t on) {
#pragma unroll
    for (int i = 0; i < 3; i++) send8(a + 28 + 8 * i, rbuf + i * 2048 + t * 16, rbar, on);
    asm volatile("{\n.reg .pred p;\nsetp.ne.u32 p, %4, 0;\n@p st.async.weak.shared::cluster.mbarrier::complete_tx::bytes.v2.b32 [%0], {%1,%2}, [%3];\n}"
                 ::"r"(rbuf + 6144 + t * 8), "r"(pack2(a[52], a[53])), "r"(pack2(a[54], a[55])), "r"(rbar), "r"(on) : "memory");
}
__device__ __forceinline__ void recv_half(uint32_t (&p)[14], uint32_t buf, int t) {
#pragma unroll
    for (int i = 0; i < 3; i++)
        asm volatile("ld.shared.v4.b32 {%0,%1,%2,%3}, [%4];" : "=r"(p[4 * i]), "=r"(p[4 * i + 1]), "=r"(p[4 * i + 2]), "=r"(p[4 * i + 3]) : "r"(buf + i * 2048 + t * 16) : "memory");
    asm volatile("ld.shared.v2.b32 {%0,%1}, [%2];" : "=r"(p[12]), "=r"(p[13]) : "r"(buf + 6144 + t * 8) : "memory");
}

struct Maps { CUtensorMap xl, x, wqkv, hst, w1, w2, xn, old_, ost, out[2], wo; };

__global__ void __cluster_dims__(2, 1, 1) __launch_bounds__(512, 1)
fused_kernel(const __nv_bfloat16* __restrict__ x, const __nv_bfloat16* __restrict__ wqkv,
             const __nv_bfloat16* __restrict__ b1, const __nv_bfloat16* __restrict__ b2, uint8_t* __restrict__ scr,
             const __nv_bfloat16* __restrict__ w2, const __grid_constant__ Maps mp) {
    extern __shared__ __align__(1024) uint8_t smem[];
    const uint32_t sb = smem_u32(smem);
    const uint32_t bar = sb + OFF_BAR;
    const int tid = threadIdx.x, lane = tid & 31;
    const int b = blockIdx.x, z = b & 1, c = b >> 1;
    unsigned* const ctr = reinterpret_cast<unsigned*>(scr + G_CTR);
    if (tid < 112) l2_prefetch(reinterpret_cast<const uint8_t*>(x) + (b * 112 + tid) * 128);
    const int wline = (tid & 127) * 128 + b;
    const bool wfirst = ((wline / 1344) & ~ROT) == 0;
    if (PFW && (tid >> 7) == 1 && wline < 9408 && wfirst) l2_prefetch(reinterpret_cast<const uint8_t*>(wqkv) + wline * 128);
    const uint32_t t_in = clock32();
    TS0(0);
    TG(60);
    const int warp = __shfl_sync(0xffffffffu, tid >> 5, 0);
    int q, j;
    if (c < 4) { q = 15; j = c; } else if (c < 36) { q = (c - 4) & 7; j = (c - 4) >> 3; } else { q = 8 + (c - 36) % 7; j = (c - 36) / 7; }
    const bool g1 = q < 14;
    const int R = q < 8 ? q : q == 15 ? 2 : q < 10 ? q - 8 : q - 7, P = (q >> 3) * 4 + j;
    auto krow = [&](int kb) { const int k = kb + (R & ROT); return (k >= 7 ? k - 7 : k) * 64; };
    auto x_load = [&](int kb) {
        mbar_expect(bar + 8 * (B_FULLQ + kb), 40960);
        tma2d(sb + OFF_A + ((XSLOT >> (4 * kb)) & 7) * 16384, &mp.x, z * D_ + krow(kb), R * 128, bar + 8 * (B_FULLQ + kb));
    };
    if (warp == 12 && elect()) {
#pragma unroll
        for (int i = B_FULLQ; i < B_EMPTYQ; i++) mbar_init(bar + 8 * i, 1);
        mbar_expect(bar + 8 * B_LNIN, BLK);
        tma3d(sb + OFF_A, &mp.xl, 0, 16 * b, 0, bar + 8 * B_LNIN);
        x_load(0);
        TS(15);
    }
    if (warp == 13 && elect()) {
#pragma unroll
        for (int i = B_EMPTYQ; i < B_COUNT; i++)
            mbar_init(bar + 8 * i, i < B_FULL ? (i < B_EMPTYQ + 2 ? 16 : 8) + (((i - B_EMPTYQ) & ~1) == (R & 6 & ~ROT) ? 8 : 0)
                                   : i < B_EMPTY ? 2 : i == B_UDONE ? (g1 ? 3 : 1) : (i < B_AUX || i == B_NONE || i == B_OST) ? 8 : i == B_HALO ? 12
                                   : (i == B_UST || i == B_UST + 1 || i == B_AUX) ? 4 : 1);
#pragma unroll
        for (int i = B_RECV1; i < B_UST; i++) mbar_expect(bar + 8 * i, i < B_RECV2 ? 7168 : 8192 - 2048 * z);
    }
    asm volatile("fence.mbarrier_init.release.cluster;" ::: "memory");
    __syncwarp();
    asm volatile("barrier.cluster.arrive.relaxed.aligned;\nbarrier.cluster.wait.aligned;" ::: "memory");
    auto slot = [](uint32_t r) { return r - 6 * ((r * 43) >> 8); };
    auto phase = [](uint32_t r) { return ((r * 43) >> 8) & 1; };
    const uint32_t r_o = g1 ? 16 : 0, r_u = r_o + 5;
    auto epoch = [&]() { mbar_wait(bar + 8 * B_EP, 0); return *reinterpret_cast<volatile unsigned*>(smem + OFF_EP); };

    if (warp < 8) {
        const int wg = warp >> 2, w4 = warp & 3, t = tid & 127, g = lane >> 2, tq = lane & 3;
        asm volatile("setmaxnreg.inc.sync.aligned.u32 208;");
        uint32_t xa[4];
#pragma unroll
        for (int k = 0; k < 4; k++) xa[k] = sb + OFF_A + (warp * 16 + (lane & 15)) * 128 + (((2 * k + (lane >> 4)) ^ (lane & 7)) << 4);
        {
            const int rg = warp & 1, jq = warp >> 1;
            const uint32_t ex = sb + OFF_LNX + (rg * 8 + g) * 32, ew = ex + jq * 8, ls = sb + OFF_LNST + (rg * 8 + g) * 8;
            uint32_t r[4][4], la[4], ha[4], dep = ex | ew | ls;
#pragma unroll
            for (int i = 0; i < 4; i++) {
                const int cg = 14 * jq + 4 * i + ((lane >> 3) & (i < 3 ? 3 : 1));
                la[i] = sb + OFF_A + (cg >> 3) * 2048 + rg * 1024 + (lane & 7) * 128 + (((cg ^ lane) & 7) << 4);
                int pos = 4 * i + (lane >> 3) + (b >= 64 ? 7 : 0);
                if (pos >= 14) pos -= 14;
                ha[i] = sb + OFF_A + jq * 3584 + rg * 1792 + (lane & 7) * 16 + pos * 128;
                dep |= la[i] | ha[i] | xa[i];
            }
            TS0(46);
            mbar_wait(bar + 8 * B_LNIN, dep >> 31);
            TS0(16);
#pragma unroll
            for (int i = 0; i < 4; i++) ldsm4(la[i], r[i]);
            float rs[4] = {0.f, 0.f, 0.f, 0.f}, rt[4] = {0.f, 0.f, 0.f, 0.f}, sq[4], v[28];
            const float sh = bf_lo(__shfl_sync(0xffffffffu, r[0][0], lane & 28));
            mma16816(rs, r[0][0], r[0][1], r[0][2], r[0][3], 0x3F803F80u, 0x3F803F80u);
            mma16816(rt, r[1][0], r[1][1], r[1][2], r[1][3], 0x3F803F80u, 0x3F803F80u);
            mma16816(rs, r[2][0], r[2][1], r[2][2], r[2][3], 0x3F803F80u, 0x3F803F80u);
            mma1688(rt, r[3][0], r[3][1], 0x3F803F80u);
#pragma unroll
            for (int n = 0; n < 14; n++) { v[2 * n] = bf_lo(r[n >> 2][n & 3]) - sh; v[2 * n + 1] = bf_hi(r[n >> 2][n & 3]) - sh; }
#pragma unroll
            for (int n = 0; n < 28; n++) sq[n & 3] = n < 4 ? v[n] * v[n] : fmaf(v[n], v[n], sq[n & 3]);
            const float mq = ((rs[0] + rs[2]) + (rt[0] + rt[2])) * (1.f / 112), dq = mq - sh;
            float m2 = fmaf(-28.f * dq, dq, (sq[0] + sq[1]) + (sq[2] + sq[3]));
            m2 += __shfl_xor_sync(0xffffffffu, m2, 1);
            m2 += __shfl_xor_sync(0xffffffffu, m2, 2);
            asm volatile("st.shared.v2.f32 [%0], {%1, %2};" ::"r"(ew), "f"(mq), "f"(m2) : "memory");
            bar_sync<1, 256>();
            float4 e0, e1;
            asm volatile("ld.shared.v4.f32 {%0,%1,%2,%3}, [%4];" : "=f"(e0.x), "=f"(e0.y), "=f"(e0.z), "=f"(e0.w) : "r"(ex) : "memory");
            asm volatile("ld.shared.v4.f32 {%0,%1,%2,%3}, [%4];" : "=f"(e1.x), "=f"(e1.y), "=f"(e1.z), "=f"(e1.w) : "r"(ex + 16) : "memory");
            const float mean = 0.25f * ((e0.x + e0.z) + (e1.x + e1.z));
            const float d0 = e0.x - mean, d1 = e0.z - mean, d2 = e1.x - mean, d3 = e1.z - mean;
            const float var = fmaxf(((e0.y + e0.w) + (e1.y + e1.w)) * (1.f / D_) + 0.25f * (fmaf(d0, d0, d1 * d1) + fmaf(d2, d2, d3 * d3)), 0.f);
            const float r1 = rsq(var + 1e-5f), sc = rsq(fmaf(1e-5f, var + 1e-5f, var)), of = (sh - mean) * sc;
#pragma unroll
            for (int n = 0; n < 14; n++) r[n >> 2][n & 3] = pack2(fmaf(v[2 * n], sc, of), fmaf(v[2 * n + 1], sc, of));
#pragma unroll
            for (int i = 0; i < 3; i++) stsm4(ha[i], r[i][0], r[i][1], r[i][2], r[i][3]);
            stsm2(ha[3], r[3][0], r[3][1]);
            asm volatile("st.shared.v2.b32 [%0], {%1, %2};" ::"r"(ls), "r"(__float_as_uint(r1)), "r"(split2(-mean)) : "memory");
            TS0(24);
            asm volatile("bar.arrive 10, 288;" ::: "memory");
        }
        float a1[56];
        uint32_t bl, bh, cl, ch;
        uint32_t qp[14], kp[14];
        const uint32_t ka = sb + OFF_K + warp * 896 + (lane & 7) * 112 + (lane >> 3) * 16;
        const uint32_t va = sb + OFF_V + (warp * 16 + (lane & 15)) * 112 + (lane >> 4) * 16;
        const uint32_t dA = desc_lo(sb + OFF_A + wg * 8192, 16), dH = desc_lo(sb + OFF_B, 1792), dU = desc_lo(sb + OFF_B, 128);
        auto release = [&](uint32_t a) { mbar_arrive_if0(a, lane); };
        auto sched_fence = [&]() { mbar_wait(bar + 8 * B_LNIN, 0); };
        uint32_t rel = bar + 8 * (B_EMPTYQ + 6);
        auto g1_run = [&](uint32_t r0, uint32_t r1) {
#pragma unroll 1
            for (uint32_t r = g1 ? r0 : r1; r < r1; r++) {
                const uint32_t s = slot(r);
                mbar_wait(bar + 8 * (B_FULL + s), phase(r));
                TSD(64 + r);
                wg_fence();
#pragma unroll
                for (int k = 0; k < 4; k++) wgmma_n112<1, H_SW, H_H>(a1, dA + s * 1024 + k * 128, dH + s * 896 + k * 224, k ? 1 : r);
                wg_commit();
                wg_wait<1>();
                release(rel);
                rel = bar + 8 * (B_EMPTY + s);
            }
        };
        auto drain = [&]() { wg_wait<0>(); release(rel); rel = bar + 8 * B_NONE; };
        {
            float aq0[28], aq1[28], aq2[28];
            const uint32_t dW = desc_lo(sb + OFF_B + (P & 1) * 16, 16);
            uint32_t xf[2][4][4];
            const uint32_t rq = mapa(bar + 8 * (B_EMPTYQ - 1), z ^ 1);
            auto fetch = [&](int kb, uint32_t (&f)[4][4]) {
                TSD(178 + kb);
                mbar_wait(bar + 8 * (B_FULLQ + kb), 0);
                TSD(170 + kb);
#pragma unroll
                for (int k = 0; k < 4; k++) ldsm4(xa[k] + ((XSLOT >> (4 * kb)) & 7) * 16384, f[k]);
            };
            auto mma = [&](int kb, uint32_t (&f)[4][4], int k0, int k1) {
                const uint32_t d0 = dW + ((WSLOT >> (4 * kb)) & 7) * 1536;
                wg_fence();
#pragma unroll
                for (int k = k0; k < k1; k++) {
                    const uint32_t d = d0 + (k >> 1) * 768 + (k & 1) * 128;
                    const int sc = k > 0 ? 1 : kb;
                    wgmma_n56_rs<H_SW, 1>(aq0, f[k], d, sc);
                    wgmma_n56_rs<H_SW, 1>(aq1, f[k], d + 256, sc);
                    wgmma_n56_rs<H_SW, 1>(aq2, f[k], d + 512, sc);
                }
            };
            auto retire = [&](int kb) {
                wg_commit();
                wg_wait<1>();
                mbar_arrive_if0(bar + 8 * (B_EMPTYQ + kb - 1), lane | (kb < 1));
                asm volatile("{\n.reg .pred p;\nsetp.eq.u32 p, %1, 0;\n@p mbarrier.arrive.shared::cluster.b64 _, [%0];\n}"
                             ::"r"(rq + 8 * kb), "r"(lane | ((uint32_t)(kb - 1) > 1)) : "memory");
            };
            auto stage = [&](int kb, uint32_t (&f)[4][4], uint32_t (&n)[4][4]) {
                mma(kb, f, 0, KS);
                retire(kb);
                fetch(kb + 1, n);
                if (KS < 4) { mma(kb, f, KS, 4); wg_commit(); }
            };
            fetch(0, xf[0]);
#pragma unroll kQUnroll
            for (int kb = 0; kb < 6; kb += 2) {
                stage(kb, xf[0], xf[1]);
                stage(kb + 1, xf[1], xf[0]);
            }
            mma(6, xf[0], 0, KS);
            retire(6);
            TS0(2);
            mbar_wait(bar + 8 * B_AUX, 0);
            {
                uint32_t (&f)[4] = xf[1][0];
                const uint32_t* mt = reinterpret_cast<const uint32_t*>(smem + OFF_STATS) + (warp * 16 + g + 8) * 2 + 1;
                const uint32_t sel = tq == 0 ? 0x1010 : tq == 1 ? 0x3232 : 0x4444;
                f[0] = __byte_perm(mt[0], 0, sel); f[1] = __byte_perm(mt[16], 0, sel); f[2] = f[3] = 0;
                asm volatile("" : "+r"(f[0]), "+r"(f[1]), "+r"(f[2]), "+r"(f[3])::"memory");
                const uint32_t d = desc_lo(sb + OFF_CSB + (P & 1) * 128, 0);
                mma(6, xf[0], KS, 4);
                wgmma_n56_rs<H_H, 0>(aq1, f, d + 64, 1);
                wgmma_n56_rs<H_H, 0>(aq2, f, d + 128, 1);
                wgmma_n56_rs<H_H, 0>(aq0, f, d, 1);
                wg_commit();
            }
            g1_run(0, wg ? 0 : NE);
            drain();
            pin(aq0); pin(aq1); pin(aq2);
            TSW(3);
            mbar_wait(bar + 8 * (B_EMPTYQ + 5), 0);
#pragma unroll
            for (int i = 0; i < 14; i++) { kp[i] = pack2(aq1[2 * i], aq1[2 * i + 1]); qp[i] = pack2(aq2[2 * i], aq2[2 * i + 1]); }
            stsm4(ka + 896, kp[1], kp[3], kp[5], kp[7]);
            stsm4(ka + 896 + 48, kp[7], kp[9], kp[11], kp[13]);
#pragma unroll
            for (int n = 0; n < 3; n++) stsm4(va + 896 + n * 32, qp[4 * n], qp[4 * n + 1], qp[4 * n + 2], qp[4 * n + 3]);
            stsm2(va + 896 + 96, qp[12], qp[13]);
            __syncwarp();
            mbar_arrive_if0(bar + 8 * B_QKV, tid - 224);
            release(bar + 8 * B_HALO);
#pragma unroll
            for (int i = 0; i < 14; i++) qp[i] = pack2(aq0[2 * i], aq0[2 * i + 1]);
            TSW(4);
        }
        g1_run(wg ? 0 : NE, ATT_STEP);
        {
            uint32_t kf[2][3][4], vf[2][3][4];
            const bool up0 = 2 * tq > g, up1 = 2 * tq + 1 > g, edge = (R | warp) == 0;
            float rk[2][2], fs[2][2];
#pragma unroll
            for (int i = 0; i < 4; i++) {
                const float* st = reinterpret_cast<const float*>(smem + OFF_STATS) + (warp * 16 + (i >> 1) * 8) * 2;
                rk[i >> 1][i & 1] = st[(2 * tq + (i & 1) + (((i & 1) ? up1 : up0) ? 0 : 8)) * 2];
                fs[i >> 1][i & 1] = rk[i >> 1][i & 1] * (st[(g + 8) * 2] * (0.18898223650461362f * 1.4426950408889634f));
            }
            mbar_wait(bar + 8 * B_HALO, 0);
#pragma unroll
            for (int hd = 0; hd < 2; hd++) {
                ldsm4(ka + hd * 48, kf[hd][0]);
#pragma unroll
                for (int i = 0; i < 4; i++) { kf[hd][1][i] = kp[6 * hd + 2 * i]; kf[hd][2][i] = kp[6 * hd + 2 * i + 1]; }
                ldsm4t(va + hd * 48, vf[hd][0]); ldsm4t(va + hd * 48 + 32, vf[hd][1]);
                ldsm4t(ka + (OFF_V - OFF_K) + warp * 896 + hd * 48 + 1792, vf[hd][2]);
            }
            const uint32_t q0l = tq < 2 ? qp[6] : 0, q0h = tq < 2 ? qp[7] : 0, q1l = tq < 2 ? 0 : qp[6], q1h = tq < 2 ? 0 : qp[7];
            const uint32_t mk = (up0 ? 0xFFFFu : 0u) | (up1 ? 0xFFFF0000u : 0u);
            drain();
            sched_fence();
            TS0(19);
            float sc[2][3][4];
#pragma unroll
            for (int u = 0; u < 3; u++) {
#pragma unroll
                for (int i = 0; i < 8; i++) sc[i >> 2][u][i & 3] = 0.f;
                mma16816(sc[0][u], qp[0], qp[1], qp[2], qp[3], kf[0][u][0], kf[0][u][1]);
                mma16816(sc[1][u], q1l, q1h, qp[8], qp[9], kf[1][u][0], kf[1][u][1]);
            }
#pragma unroll
            for (int u = 0; u < 3; u++) {
                mma16816(sc[0][u], qp[4], qp[5], q0l, q0h, kf[0][u][2], kf[0][u][3]);
                mma16816(sc[1][u], qp[10], qp[11], qp[12], qp[13], kf[1][u][2], kf[1][u][3]);
            }
            float e[2][2][2], mx[2][2], sm[2][2];
#pragma unroll
            for (int hd = 0; hd < 2; hd++) {
                e[hd][0][0] = (up0 ? sc[hd][0][0] : sc[hd][1][0]) * fs[0][0];
                e[hd][0][1] = (up1 ? sc[hd][0][1] : sc[hd][1][1]) * fs[0][1];
                e[hd][1][0] = (up0 ? sc[hd][1][2] : sc[hd][2][2]) * fs[1][0];
                e[hd][1][1] = (up1 ? sc[hd][1][3] : sc[hd][2][3]) * fs[1][1];
                if (edge && up0) e[hd][0][0] = -1e30f;
                if (edge && up1) e[hd][0][1] = -1e30f;
                mx[hd][0] = fmaxf(e[hd][0][0], e[hd][0][1]);
                mx[hd][1] = fmaxf(e[hd][1][0], e[hd][1][1]);
            }
#pragma unroll
            for (int o = 1; o <= 2; o <<= 1)
#pragma unroll
                for (int i = 0; i < 4; i++) mx[i >> 1][i & 1] = fmaxf(mx[i >> 1][i & 1], __shfl_xor_sync(0xffffffffu, mx[i >> 1][i & 1], o));
            uint32_t pp[2][2];
#pragma unroll
            for (int i = 0; i < 4; i++) {
                const float p0 = ex2(e[i >> 1][i & 1][0] - mx[i >> 1][i & 1]), p1 = ex2(e[i >> 1][i & 1][1] - mx[i >> 1][i & 1]);
                pp[i >> 1][i & 1] = pack2(p0 * rk[i & 1][0], p1 * rk[i & 1][1]);
                sm[i >> 1][i & 1] = p0 + p1;
            }
            float ov[2][4][4];
#pragma unroll
            for (int hd = 0; hd < 2; hd++)
#pragma unroll
                for (int n = 0; n < 4; n++) {
                    ov[hd][n][0] = ov[hd][n][1] = ov[hd][n][2] = ov[hd][n][3] = 0.f;
                    mma16816(ov[hd][n], pp[hd][0] & mk, 0u, pp[hd][0] & ~mk, pp[hd][1] & mk, vf[hd][n >> 1][2 * (n & 1)], vf[hd][n >> 1][2 * (n & 1) + 1]);
                }
#pragma unroll
            for (int hd = 0; hd < 2; hd++)
#pragma unroll
                for (int n = 0; n < 4; n++) mma1688(ov[hd][n], 0u, pp[hd][1] & ~mk, vf[hd][2][n]);
            sched_fence();
            bar_sync<1, 256>();
            TS0(18);
            g1_run(ATT_STEP, wg ? ATT_STEP + NP : ATT_STEP);
#pragma unroll
            for (int o = 1; o <= 2; o <<= 1)
#pragma unroll
                for (int i = 0; i < 4; i++) sm[i >> 1][i & 1] += __shfl_xor_sync(0xffffffffu, sm[i >> 1][i & 1], o);
            const uint32_t oa = sb + OFF_OST + (warp * 16 + (lane & 15)) * 128;
            uint32_t op[16];
            op[14] = op[15] = 0;
#pragma unroll
            for (int i = 0; i < 4; i++) sm[i >> 1][i & 1] = rcp(sm[i >> 1][i & 1]);
#pragma unroll
            for (int n = 0; n < 7; n++) {
                const bool hb = n > 3 || (n == 3 && tq >= 2);
#pragma unroll
                for (int h = 0; h < 2; h++) {
                    const float r = hb ? sm[1][h] : sm[0][h];
                    const float x0 = hb ? ov[1][n >= 3 ? n - 3 : 0][2 * h] : ov[0][n <= 3 ? n : 0][2 * h];
                    const float x1 = hb ? ov[1][n >= 3 ? n - 3 : 0][2 * h + 1] : ov[0][n <= 3 ? n : 0][2 * h + 1];
                    op[2 * n + h] = pack2(x0 * r, x1 * r);
                }
            }
#pragma unroll
            for (int n = 0; n < 4; n++) stsm4(oa + (((2 * n + (lane >> 4)) ^ (lane & 7)) << 4), op[4 * n], op[4 * n + 1], op[4 * n + 2], op[4 * n + 3]);
            __syncwarp();
            release(bar + 8 * B_OST);
            TSW(5);
            const int row = q * 128 + warp * 16 + g;
            bl = ldg_u16(b2 + row); bh = ldg_u16(b2 + row + 8);
            cl = ldg_u16(b1 + (g1 ? row : 0)); ch = ldg_u16(b1 + (g1 ? row : 0) + 8);
        }
        const uint32_t peer = z ^ 1;
        uint32_t rs = wg ? ATT_STEP + NP : ATT_STEP;
        if (ATT_STEP + NP < 16 - NS1) { g1_run(rs, wg ? 16 - NS1 : rs); rs = wg ? 16 - NS1 : rs; }
        drain();
        gate_wait(wg);
        g1_run(rs, 16);
        gate_open(wg);
        mbar_wait_cluster(bar + 8 * B_FREE, 0);
        drain();
        pin(a1);
        TSW(6);
        send_half(a1, mapa(sb + OFF_RECV1 + wg * 7168, peer), mapa(bar + 8 * (B_RECV1 + wg), peer), t, g1);
        float a2[56];
        {
            const uint32_t s = slot(r_o);
            mbar_wait(bar + 8 * (B_FULL + s), phase(r_o));
            uint32_t xr[4][4];
#pragma unroll
            for (int k = 0; k < 4; k++) ldsm4(xa[k] + s * 16384, xr[k]);
            if (z) bl = bh = xr[3][0] = xr[3][1] = xr[3][2] = xr[3][3] = 0;
#pragma unroll
            for (int i = 0; i < 56; i++) {
                a2[i] = bf_lo((i & 2) ? bh : bl);
                if (i < 32) a2[i] += (i & 1) ? bf_hi(xr[i >> 3][(i >> 1) & 3]) : bf_lo(xr[i >> 3][(i >> 1) & 3]);
            }
            pin(a2);
            release(bar + 8 * (B_EMPTY + s));
#pragma unroll
            for (int i = 0; i < 28; i++) a1[i] += bf_lo((i & 2) ? ch : cl);
            pin<0, 28>(a1);
        }
        if (g1) {
            uint32_t p[14];
            mbar_wait_cluster(bar + 8 * (B_RECV1 + wg), 0);
            TSW(8);
            recv_half(p, sb + OFF_RECV1 + wg * 7168, t);
#pragma unroll
            for (int i = 0; i < 14; i++) p[i] = pack2(gelu_tanh(a1[2 * i] + bf_lo(p[i])), gelu_tanh(a1[2 * i + 1] + bf_hi(p[i])));
            const uint32_t dst = sb + OFF_UST + wg * 7168 + w4 * 256 + (lane & 15) * 16;
#pragma unroll
            for (int n = 0; n < 3; n++) stsm4(dst + (2 * n + (lane >> 4)) * 1024, p[4 * n], p[4 * n + 1], p[4 * n + 2], p[4 * n + 3]);
            stsm2(dst + 6144, p[12], p[13]);
            __syncwarp();
            release(bar + 8 * (B_UST + wg));
        }
        TSW(9);
#pragma unroll 1
        for (uint32_t r = r_o + 1; r < r_u; r++) {
            const uint32_t s = slot(r);
            mbar_wait(bar + 8 * (B_FULL + s), phase(r));
            TSD(64 + 16 + r - r_o);
            wg_fence();
#pragma unroll
            for (int k = 0; k < 4; k++) wgmma_n112<0, H_SW, H_U>(a2, dA + s * 1024 + k * 2, dU + s * 896 + k * 16);
            wg_commit();
            wg_wait<1>();
            release(rel);
            rel = bar + 8 * (B_EMPTY + s);
        }
        drain();
        TSW(10);
#pragma unroll 1
        for (uint32_t r = r_u; r < r_u + 14; r++) {
            const uint32_t s = slot(r);
            gate_wait(wg && r == r_u + 14 - NS2);
            mbar_wait(bar + 8 * (B_FULL + s), phase(r));
            TSD(85 + r - r_u);
            wg_fence();
#pragma unroll
            for (int k = 0; k < 4; k++) wgmma_n112<1, H_SW, H_U>(a2, dA + s * 1024 + k * 128, dU + s * 896 + k * 16);
            wg_commit();
            wg_wait<1>();
            release(rel);
            rel = bar + 8 * (B_EMPTY + s);
        }
        gate_open(wg);
        mbar_wait_cluster(bar + 8 * B_UDONE, 0);
        wg_wait<0>();
        pin(a2);
        TSW(11);
        {
            const uint32_t rbuf = mapa(sb + OFF_RECV2 + wg * 8192 + t * 16, peer) - (z ? 0 : 2048), rbar = mapa(bar + 8 * (B_RECV2 + wg), peer);
#pragma unroll
            for (int i = 3; i >= 0; i--) send8(a2 + 24 + 8 * i, rbuf + i * 2048, rbar, i | z);
            mbar_wait_cluster(bar + 8 * (B_RECV2 + wg), 0);
            TSW(12);
            const uint32_t dst = sb + OFF_OUT + wg * 8192 + (w4 * 16 + (lane & 15)) * 128;
#pragma unroll
            for (int i = 0; i < 4; i++) {
                uint32_t u[4];
                asm volatile("ld.shared.v4.b32 {%0,%1,%2,%3}, [%4];" : "=r"(u[0]), "=r"(u[1]), "=r"(u[2]), "=r"(u[3]) : "r"(sb + OFF_RECV2 + wg * 8192 + i * 2048 + t * 16) : "memory");
#pragma unroll
                for (int e = 0; e < 4; e++) u[e] = pack2(a2[8 * i + 2 * e] + bf_lo(u[e]), a2[8 * i + 2 * e + 1] + bf_hi(u[e]));
                stsm4(dst + (((2 * i + (lane >> 4)) ^ (lane & 7)) << 4), u[0], u[1], u[2], u[3]);
            }
            bar_sync_id(2 + wg, 128);
            if (w4 == 0 && elect()) {
                fence_async_smem();
                tma2d_store(&mp.out[z], sb + OFF_OUT + wg * 8192, j * 112 + z * 64, q * 128 + wg * 64);
                bulk_commit();
                bulk_wait_read();
            }
        }
        TSW(13);
    } else if (warp < 12) {
        asm volatile("setmaxnreg.dec.sync.aligned.u32 64;");
        const int hw = warp - 8, t = tid & 127;
        while (clock32() - t_in < DLY1) SPIN;
        if (wline < 9408 && !wfirst) l2_prefetch(reinterpret_cast<const uint8_t*>(wqkv) + wline * 128);
        uint8_t* cscell = scr + G_CS + ((P * 8 + R) * 2 + z) * 512 + (t >> 2) * 16;
        if ((lane & 3) == 0) cell_put(cscell, 0, 0, 0);
        uint8_t* cells = scr + G_HALO + ((R * 8 + P) * 2 + z) * 3584 + min(t, 111) * 16;
        cell_put(cells, 0, 0, 0);
        cell_put(cells + 1792, 0, 0, 0);
        reinterpret_cast<uint32_t*>(smem + OFF_ONES)[t] = t < 64 ? 0x3F803F80u : 0;
        fence_async_smem();
        bar_sync<12, 128>();
        const unsigned e1 = epoch();
        {
            const uint32_t da = desc_lo(sb + OFF_B + min((R & 1) * 2 + z, 2) * 4096, 16), db = desc_lo(sb + OFF_ONES, 128);
            float c0[4];
            const int st = R & 6 & ~ROT;
            mbar_wait(bar + 8 * (B_FULLQ + st), 0);
            mbar_wait(bar + 8 * (B_FULLQ + st + 1), 0);
            TSH(47);
            wg_fence();
#pragma unroll
            for (int k = 0; k < 8; k++)
                wgmma_n8<1, H_SW, H_H>(c0, da + ((WSLOT >> (4 * st + (k & 4))) & 7) * 1536 + (k & 2) * 384 + (k & 1) * 128, db + (k >= 4 && R >= 6 ? 16 : 0), k);
            wg_commit();
            wg_wait<0>();
            pin(c0);
            if ((lane & 3) == 0) cell_put(cscell, __float_as_uint(c0[0]), __float_as_uint(c0[2]), e1);
            if (lane < 4) asm volatile("mbarrier.arrive.shared::cluster.b64 _, [%0];" ::"r"(mapa(bar + 8 * (B_EMPTYQ + st + (lane >> 1)), lane & 1)) : "memory");
            TSH(43);
        }
        mbar_wait(bar + 8 * (B_FULLQ + GATHER), 0);
        TSH(39);
        {
            const bool cw = hw < 3;
            const uint8_t* src = cw ? scr + G_CS + P * 8192 + t * 16 : scr + G_STATS + (z * 1024 + R * 128 + lane) * 16;
            uint32_t a[5], d[5], bad;
            do {
                bad = 0;
#pragma unroll
                for (int i = 0; i < 4; i++) bad |= cell_get(src + i * (cw ? 2048 : 512), a[i], d[i], e1);
                if (t >= 120) bad |= cell_get(src - (R ? 512 : 0), a[4], d[4], e1);
            } while (bad);
            TSH(45);
            if (cw) {
                uint4* cb = reinterpret_cast<uint4*>(smem + OFF_CSB) + (t >> 3) * 16 + (t & 7);
                const uint32_t lo = split2((__uint_as_float(a[0]) + __uint_as_float(a[1])) + (__uint_as_float(a[2]) + __uint_as_float(a[3])));
                const uint32_t hi = split2((__uint_as_float(d[0]) + __uint_as_float(d[1])) + (__uint_as_float(d[2]) + __uint_as_float(d[3])));
                cb[0] = make_uint4(lo, lo, 0, 0);
                cb[8] = make_uint4(hi, hi, 0, 0);
            } else {
                uint2* st = reinterpret_cast<uint2*>(smem + OFF_STATS) + lane;
#pragma unroll
                for (int i = 0; i < 4; i++) st[8 + 32 * i] = make_uint2(a[i], d[i]);
                if (t >= 120) st[-24] = make_uint2(a[4], d[4]);
            }
            fence_async_smem();
            __syncwarp();
            mbar_arrive_if0(bar + 8 * B_AUX, lane);
            TSH(41);
        }
        {
            uint2* kv = reinterpret_cast<uint2*>(smem + OFF_K) + min(t, 111);
            mbar_wait(bar + 8 * B_QKV, 0);
            uint2 k2 = kv[896], v2 = kv[1792 + (OFF_V - OFF_K) / 8];
            cell_put(cells, k2.x, k2.y, e1);
            cell_put(cells + 1792, v2.x, v2.y, e1);
            k2 = v2 = make_uint2(0, 0);
            if (R > 0) while (cell_get(cells - 16 * 3584, k2.x, k2.y, e1) | cell_get(cells - 16 * 3584 + 1792, v2.x, v2.y, e1)) {}
            kv[0] = k2;
            kv[(OFF_V - OFF_K) / 8] = v2;
            __syncwarp();
            mbar_arrive_if0(bar + 8 * B_HALO, lane);
            TSH(40);
        }
        if (hw == 2) {
            auto tell_peer = [&](int i) {
                asm volatile("mbarrier.arrive.relaxed.cluster.shared::cluster.b64 _, [%0];" ::"r"(mapa(bar + 8 * i, z ^ 1)) : "memory");
            };
            mbar_wait(bar + 8 * B_OST, 0);
            if (elect()) {
                tell_peer(B_FREE);
                fence_async_smem();
                tma2d_store(&mp.ost, sb + OFF_OST, z * 64, P * 1024 + R * 128);
                bulk_commit();
                bulk_wait_all();
                red_relaxed(ctr + C_O + (R * 2 + (P >> 2)) * 32);
                tell_peer(B_UDONE);
                TS(21);
            }
        } else if (hw < 2 && g1) {
            const int ub = 2 * q + hw, zz = ub >= 14 ? 1 : 0;
            uint8_t* ud = scr + G_BIMG + ((8 + ub) * 4 + j) * BLK;
            mbar_wait(bar + 8 * (B_UST + hw), 0);
            if (elect()) {
                fence_async_smem();
                bulk_store(ud + ((7 * z + 1 + 6 * zz) % 14) * 1024, sb + OFF_UST + hw * 7168 + 1024, 6144);
                bulk_store(ud + (7 * z + 6 * zz) * 1024, sb + OFF_UST + hw * 7168, 1024);
                bulk_commit();
                bulk_wait_all();
                red_relaxed(ctr + C_U + (zz * 2 + hw) * 32);
                mbar_arrive(bar + 8 * B_UDONE);
                TS(22 + hw);
            }
        }
    } else {
        asm volatile("setmaxnreg.dec.sync.aligned.u32 32;");
        auto wait_free = [&](uint32_t r, uint32_t first) {
            const uint32_t a = r < 6 ? B_EMPTYQ + ((first >> (4 * r)) & 7) : B_EMPTY + slot(r);
            mbar_wait(bar + 8 * a, r < 6 ? 0 : phase(r) ^ 1);
        };
        if (warp == 12) {
            TS(14);
            if (elect()) {
#pragma unroll 1
                for (int kb = 0; kb < 7; kb++) {
                    if (kb < 2) while (clock32() - t_in < (kb ? DLY2 : DLY0)) SPIN;
                    if (kb >= QDEPTH) { mbar_wait(bar + 8 * (B_FULLQ + kb - QDEPTH), 0); TS(25 + kb - QDEPTH); }
                    if (kb >= 5) mbar_wait(bar + 8 * (B_EMPTYQ + kb - 5), 0);
                    if (kb > 0) x_load(kb);
                    tma3d_mc(sb + OFF_B + ((WSLOT >> (4 * kb)) & 7) * 24576 + z * 12288, &mp.wqkv, (P * 56) & ~15, krow(kb) + z * 32, 0, bar + 8 * (B_FULLQ + kb));
                }
                TS(17);
                ld_relaxed(ctr + C_O + ((q & ~1) + z) * 32);
                mbar_wait(bar + 8 * B_LNFREE, 0);
                if (!g1) {
                    const int ic = (q - 14) * 8 + j * 2 + z, rot = ic >> 3;
                    mbar_wait(bar + 8 * (B_EMPTYQ + 2), 0);
                    mbar_expect(bar + 8 * B_GO, 2 * BLK);
#pragma unroll 1
                    for (int i = 0; i < 2; i++) tma3d(sb + OFF_A + i * BLK, &mp.wo, 0, (ic >> 1) * 56, (z * 2 + i) * 14, bar + 8 * B_GO);
                    mbar_wait(bar + 8 * B_GO, 0);
#pragma unroll 1
                    for (int i = 0; i < 2; i++) {
                        uint8_t* dst = scr + G_BIMG + (ic * 2 + i) * BLK;
                        bulk_store(dst + rot * 6144, sb + OFF_A + i * BLK, 8192);
                        bulk_store(dst + (rot ^ 1) * 8192, sb + OFF_A + i * BLK + 8192, 6144);
                    }
                    bulk_commit();
                    bulk_wait_all();
                    red_relaxed(ctr + C_WO);
                    TS(44);
                }
#pragma unroll 1
                for (uint32_t r = 0; r < r_o; r++) {
                    const uint32_t s = slot(r), fb = bar + 8 * (B_FULL + s);
                    wait_free(r, 0x654320u);
                    mbar_expect(fb, 16384);
                    tma3d(sb + OFF_A + s * 16384, &mp.w1, 0, z * 1024 + r * 64, 2 * q, fb);
                    TS(99 + r);
                }
#pragma unroll 1
                for (uint32_t r = r_o; r < r_u; r++) {
                    const uint32_t s = slot(r), fb = bar + 8 * (B_FULL + s);
                    if (r == r_o + 1) { poll(ctr + C_O + ((q & ~1) + z) * 32, epoch() * 8); fence_async_global(); TS(32); }
                    wait_free(r, 0x654320u);
                    mbar_expect(fb, 16384);
                    if (r == r_o) tma2d(sb + OFF_A + s * 16384, &mp.xn, j * 112 + z * 64, q * 128, fb);
                    else tma2d(sb + OFF_A + s * 16384, &mp.old_, 0, (4 * z + r - r_o - 1) * S_ + q * 128, fb);
                    TS(99 + 16 + r - r_o);
                }
#pragma unroll 1
                for (uint32_t i = 0; i < 14; i++) {
                    const uint32_t r = r_u + i, s = slot(r), fb = bar + 8 * (B_FULL + s);
                    wait_free(r, 0x654320u);
                    mbar_expect(fb, 16384);
                    tma3d(sb + OFF_A + s * 16384, &mp.w2, 0, (14 * z + (i < 7 ? 2 * i : 2 * i - 13)) * 64, 2 * q, fb);
                    TS(99 + 21 + i);
                }
            }
        } else if (warp == 13) {
            if (elect()) {
#pragma unroll 1
                for (int ph = g1 ? 0 : 1; ph < 4; ph++) {
                    if (ph == 1) {
                        wait_free(r_o, 0x644332u);
                        mbar_arrive(bar + 8 * (B_FULL + slot(r_o)));
                    }
                    const uint8_t* src = ph == 0 ? scr + G_HIMG + (64 * z + j) * BLK : scr + G_BIMG + ((ph == 1 ? 4 * z : 6 + 14 * z + ph) * 4 + j) * BLK;
                    const uint32_t r0 = ph == 0 ? 0 : r_o + (ph == 1 ? 1 : 7 * ph - 9), r1 = r_o + (ph == 0 ? 0 : 7 * ph - 2);
#pragma unroll 1
                    for (uint32_t r = r0; r < r1; r++, src += ph < 2 ? 4 * BLK : 8 * BLK) {
                        const uint32_t s = slot(r), fb = bar + 8 * (B_FULL + s);
                        wait_free(r, 0x644332u);
                        mbar_expect(fb, BLK);
                        mbar_wait(bar + 8 * (B_GO + ph), 0);
                        bulk_load(sb + OFF_B + s * BLK, src, BLK, fb);
                        TS(134 + 16 + r - r_o);
                    }
                }
            }
        } else if (warp == 14) {
            uint8_t* stcell = scr + G_STATS + ((lane & 1) * 1024 + 8 * b + (lane >> 1)) * 16;
            if (lane < 16) cell_put(stcell, 0, 0, 0);
            const unsigned e1 = (ld_relaxed(ctr + C_LN) >> 7) + 1;
            if (lane == 0) {
                *reinterpret_cast<volatile unsigned*>(smem + OFF_EP) = e1;
                mbar_arrive(bar + 8 * B_EP);
                TS(36);
            }
            bar_sync<10, 288>();
            if (elect()) {
                fence_async_smem();
                TS(42);
                tma4d_store(&mp.hst, sb + OFF_A, 0, 0, b & 3, b & ~3);
                bulk_commit();
            }
            __syncwarp();
            if (lane < 16) {
                const uint2 v = reinterpret_cast<const uint2*>(smem + OFF_LNST)[lane];
                cell_put(stcell, v.x, v.y, e1);
            }
            bulk_wait_all();
            __syncwarp();
            if (lane == 0) {
                red_relaxed(ctr + C_LN);
                mbar_arrive(bar + 8 * B_LNFREE);
                TS(37);
                ld_relaxed(ctr + C_U + z * 64);
                ld_relaxed(ctr + C_U + z * 64 + 32);
#pragma unroll 1
                for (int ph = g1 ? 0 : 1; ph < 4; ph++) {
                    if (ph) mbar_wait(bar + 8 * (ph == 1 ? B_HALO : g1 ? B_UST : B_OST), 0);
                    poll(ctr + ph * 32 + (ph >> 1) * z * 64, e1 * (ph == 0 ? 128 : ph == 1 ? 16 : 56));
                    fence_async_global();
                    mbar_arrive(bar + 8 * (B_GO + ph));
                    TS(ph == 0 ? 33 : ph == 1 ? 63 : 32 + ph);
                }
            }
        } else {
            if (elect()) {
#pragma unroll 1
                for (int i = 2; i < 12; i++) asm volatile("prefetch.tensormap [%0];" ::"l"(reinterpret_cast<const CUtensorMap*>(&mp) + i) : "memory");
            }
            __syncwarp();
#pragma unroll 1
            for (int k = 0; k < PF_N; k++) {
                while (clock32() - t_in < PF_T0 + k * PF_DT) __nanosleep(32);
                l2_prefetch(w2 + (size_t)(((b >> 6) * 14 + (k < 7 ? 2 * k : 2 * k - 13)) * 64 + (b & 63)) * S_ + lane * 64);
            }
            if (elect()) {
                mbar_watch(bar + 8 * B_RECV2);
                mbar_watch(bar + 8 * (B_RECV2 + 1));
            }
        }
    }
}

typedef CUresult (*EncodeFn)(CUtensorMap*, CUtensorMapDataType, cuuint32_t, void*, const cuuint64_t*, const cuuint64_t*, const cuuint32_t*,
                             const cuuint32_t*, CUtensorMapInterleave, CUtensorMapSwizzle, CUtensorMapL2promotion, CUtensorMapFloatOOBfill);

void encode(EncodeFn fn, CUtensorMap* m, const void* p, int rank, const cuuint64_t* dims, const cuuint64_t* strides, const cuuint32_t* box, bool swz) {
    const cuuint32_t es[4] = {1, 1, 1, 1};
    fn(m, CU_TENSOR_MAP_DATA_TYPE_BFLOAT16, rank, const_cast<void*>(p), dims, strides, box, es, CU_TENSOR_MAP_INTERLEAVE_NONE,
       swz ? CU_TENSOR_MAP_SWIZZLE_128B : CU_TENSOR_MAP_SWIZZLE_NONE, CU_TENSOR_MAP_L2_PROMOTION_L2_128B, CU_TENSOR_MAP_FLOAT_OOB_FILL_NONE);
}

}

extern "C" void kernel_launch(void* const* d_in, const int* in_sizes, int n_in, void* d_out, int out_size) {
    const __nv_bfloat16* x = (const __nv_bfloat16*)d_in[0];
    const __nv_bfloat16* wqkv = (const __nv_bfloat16*)d_in[1];
    const __nv_bfloat16* wo = (const __nv_bfloat16*)d_in[2];
    const __nv_bfloat16* w1 = (const __nv_bfloat16*)d_in[4];
    const __nv_bfloat16* b1 = (const __nv_bfloat16*)d_in[5];
    const __nv_bfloat16* w2 = (const __nv_bfloat16*)d_in[6];
    const __nv_bfloat16* b2 = (const __nv_bfloat16*)d_in[7];

    void* fp = nullptr;
    cudaDriverEntryPointQueryResult qr;
    cudaGetDriverEntryPoint("cuTensorMapEncodeTiled", &fp, cudaEnableDefault, &qr);
    EncodeFn fn = (EncodeFn)fp;
    void* sp = nullptr;
    cudaGetSymbolAddress(&sp, g_scratch);
    uint8_t* scr = (uint8_t*)sp;
    void *o = scr + G_O, *himg = scr + G_HIMG;

    Maps mp;
    { cuuint64_t d[3] = {64, 2048, 7}, s[2] = {896, 128}; cuuint32_t bx[3] = {64, 16, 7}; encode(fn, &mp.xl, x, 3, d, s, bx, true); }
    { cuuint64_t d[2] = {896, 1024}, s[1] = {1792}; cuuint32_t bx[2] = {64, 128}; encode(fn, &mp.x, x, 2, d, s, bx, true); }
    { cuuint64_t d[3] = {448, 448, 3}, s[2] = {2688, 896}; cuuint32_t bx[3] = {64, 32, 3}; encode(fn, &mp.wqkv, wqkv, 3, d, s, bx, true); }
    { cuuint64_t d[3] = {64, 2048, 28}, s[2] = {3584, 128}; cuuint32_t bx[3] = {64, 64, 2}; encode(fn, &mp.w1, w1, 3, d, s, bx, true); }
    { cuuint64_t d[3] = {64, 1792, 32}, s[2] = {4096, 128}; cuuint32_t bx[3] = {64, 64, 2}; encode(fn, &mp.w2, w2, 3, d, s, bx, true); }
    { cuuint64_t d[4] = {64, 28, 4, 128}, s[3] = {128, 3584, BLK}; cuuint32_t bx[4] = {64, 28, 1, 4}; encode(fn, &mp.hst, himg, 4, d, s, bx, false); }
    { cuuint64_t d[2] = {448, 2048}, s[1] = {896}; cuuint32_t bx[2] = {64, 128}; encode(fn, &mp.xn, x, 2, d, s, bx, true); }
    { cuuint64_t d[2] = {64, 8 * 2048}, s[1] = {128}; cuuint32_t bx[2] = {64, 128}; encode(fn, &mp.old_, o, 2, d, s, bx, true); }
    { cuuint64_t d[2] = {128, 8 * 1024}, s[1] = {256}; cuuint32_t bx[2] = {64, 128}; encode(fn, &mp.ost, o, 2, d, s, bx, true); }
    { cuuint64_t d[2] = {448, 2048}, s[1] = {896}; cuuint32_t bx[2] = {64, 64}; encode(fn, &mp.out[0], d_out, 2, d, s, bx, true); }
    { cuuint64_t d[2] = {448, 2048}, s[1] = {896}; cuuint32_t bx[2] = {48, 64}; encode(fn, &mp.out[1], d_out, 2, d, s, bx, true); }
    { cuuint64_t d[3] = {8, 448, 56}, s[2] = {896, 16}; cuuint32_t bx[3] = {8, 64, 14}; encode(fn, &mp.wo, wo, 3, d, s, bx, false); }

    cudaFuncSetAttribute(fused_kernel, cudaFuncAttributeMaxDynamicSharedMemorySize, SMEM_BYTES);
    fused_kernel<<<128, 512, SMEM_BYTES>>>(x, wqkv, b1, b2, scr, w2, mp);
}
```

```cpp
#include <cuda_runtime.h>
#include <cuda.h>
#include <cuda_bf16.h>
#include <stdint.h>

namespace {

constexpr int S_ = 2048, D_ = 448;
constexpr uint32_t BLK = 14336;

constexpr uint32_t G_HIMG = 0;
constexpr uint32_t G_BIMG = G_HIMG + 32 * 4 * BLK;
constexpr uint32_t G_O = G_BIMG + 36 * 4 * BLK;
constexpr uint32_t G_STATS = G_O + 8 * S_ * 128;
constexpr uint32_t G_CS = G_STATS + S_ * 16;
constexpr uint32_t G_HALO = G_CS + 8 * 4 * 2048;
constexpr uint32_t G_CTR = G_HALO + 128 * 3584;
constexpr uint32_t G_END = G_CTR + (192 + 16 * 32) * 4;
__device__ __align__(1024) uint8_t g_scratch[G_END];

constexpr int C_LN = 0, C_WO = 32, C_U = 64, C_O = 192;

#define TSX(sel, id)
#define TS(id)
#define TS0(id)
#define TSH(id)
#define TSW(id)
#define TG(id)

#define TSD(id)
#define QDEPTH 3
#define SPIN
#define ROT 6
#define KS 3
#define QUNROLL 1
#define DLY0 0
#define DLY1 1600
#define DLY2 2000
#define GATHER 3
#define PFW 0
#define NS1 5
#define NS2 4
#define NE 2
#define PRE0 8
#define PRE1 5
#define STG 1
#define NQ 0
#define GIN 1
constexpr uint32_t OFF_A = 0;
constexpr uint32_t OFF_B = 98304;
constexpr uint32_t OFF_X = 184320;
constexpr uint32_t OFF_K = 196608;
constexpr uint32_t OFF_V = OFF_K + 9 * 896;
constexpr uint32_t OFF_OST = OFF_X, OFF_RECV2 = OFF_X, OFF_RECV1 = OFF_X + 16384, OFF_UST = OFF_X + 30720, OFF_OUT = OFF_X + 16384;
constexpr uint32_t OFF_CSB = 221184;
constexpr uint32_t OFF_ONES = OFF_CSB + 3072;
constexpr uint32_t OFF_STATS = OFF_ONES + 512;
constexpr uint32_t OFF_LNX = OFF_STATS + 1024;
constexpr uint32_t OFF_RSTD = OFF_LNX + 512;
constexpr uint32_t OFF_LNST = 229376;
constexpr uint32_t OFF_EP = OFF_LNST + 128;
constexpr uint32_t OFF_BAR = OFF_EP + 16;
constexpr uint32_t OFF_TS = OFF_BAR + 8 * 48;
constexpr uint32_t SMEM_BYTES = OFF_TS;

enum : int {
    B_FULLQ = 0, B_LNIN = 7, B_EMPTYQ = 8, B_FULL = 15, B_EMPTY = 21, B_AUX = 27, B_QKV = 28, B_HALO = 29, B_FREE = 30,
    B_RECV1 = 31, B_RECV2 = 33, B_UST = 35, B_EP = 37, B_OST = 38, B_LNFREE = 39, B_UDONE = 40, B_NONE = 41, B_GO = 42, B_XR = 46, B_KV = 47, B_COUNT = 48
};
constexpr int kQUnroll = QUNROLL;
constexpr uint32_t XSLOT = 0x5432154u;
constexpr uint32_t WSLOT = 0x3421034u;
#define ATT_STEP 10

__device__ __forceinline__ uint32_t smem_u32(const void* p) { return (uint32_t)__cvta_generic_to_shared(p); }
__device__ __forceinline__ void mbar_init(uint32_t a, int c) { asm volatile("mbarrier.init.shared::cta.b64 [%0], %1;" ::"r"(a), "r"(c) : "memory"); }
__device__ __forceinline__ void mbar_expect(uint32_t a, uint32_t b) { asm volatile("mbarrier.arrive.expect_tx.shared::cta.b64 _, [%0], %1;" ::"r"(a), "r"(b) : "memory"); }
__device__ __forceinline__ void mbar_arrive(uint32_t a) { asm volatile("mbarrier.arrive.shared::cta.b64 _, [%0];" ::"r"(a) : "memory"); }
__device__ __forceinline__ void mbar_arrive_if0(uint32_t a, uint32_t sel) {
    asm volatile("{\n.reg .pred p;\nsetp.eq.u32 p, %1, 0;\n@p mbarrier.arrive.shared::cta.b64 _, [%0];\n}" ::"r"(a), "r"(sel) : "memory");
}
__device__ __forceinline__ void mbar_wait(uint32_t a, uint32_t parity) {
    asm volatile("{\n.reg .pred p;\nW0:\nmbarrier.try_wait.parity.shared::cta.b64 p, [%0], %1;\n@!p bra W0;\n}\n" ::"r"(a), "r"(parity) : "memory");
}
__device__ __forceinline__ void mbar_watch(uint32_t a) {
    asm volatile(
        "{\n.reg .pred p;\n.reg .u32 n;\nmov.u32 n, 0;\n"
        "W0:\nmbarrier.try_wait.parity.shared::cta.b64 p, [%0], 0;\n@p bra W1;\n"
        "add.u32 n, n, 1;\nsetp.lt.u32 p, n, 4194304;\n@p bra W0;\ntrap;\nW1:\n}\n" ::"r"(a) : "memory");
}
__device__ __forceinline__ bool elect() {
    uint32_t r;
    asm volatile("{\n.reg .pred p;\nelect.sync _|p, 0xffffffff;\nselp.u32 %0, 1, 0, p;\n}" : "=r"(r));
    return r;
}
__device__ __forceinline__ uint32_t mapa(uint32_t a, uint32_t cta) { uint32_t r; asm("mapa.shared::cluster.u32 %0, %1, %2;" : "=r"(r) : "r"(a), "r"(cta)); return r; }
__device__ __forceinline__ void tma2d(uint32_t dst, const CUtensorMap* m, int c0, int c1, uint32_t bar) {
    asm volatile("cp.async.bulk.tensor.2d.shared::cluster.global.mbarrier::complete_tx::bytes [%0], [%1, {%3, %4}], [%2];" ::"r"(dst), "l"(m), "r"(bar), "r"(c0), "r"(c1) : "memory");
}
__device__ __forceinline__ void tma3d(uint32_t dst, const CUtensorMap* m, int c0, int c1, int c2, uint32_t bar) {
    asm volatile("cp.async.bulk.tensor.3d.shared::cluster.global.mbarrier::complete_tx::bytes [%0], [%1, {%3, %4, %5}], [%2];" ::"r"(dst), "l"(m), "r"(bar), "r"(c0), "r"(c1), "r"(c2) : "memory");
}
__device__ __forceinline__ void tma3d_mc(uint32_t dst, const CUtensorMap* m, int c0, int c1, int c2, uint32_t bar) {
    asm volatile("cp.async.bulk.tensor.3d.shared::cluster.global.mbarrier::complete_tx::bytes.multicast::cluster [%0], [%1, {%3, %4, %5}], [%2], %6;"
                 ::"r"(dst), "l"(m), "r"(bar), "r"(c0), "r"(c1), "r"(c2), "h"((uint16_t)3) : "memory");
}
__device__ __forceinline__ void tma2d_store(const CUtensorMap* m, uint32_t src, int c0, int c1) {
    asm volatile("cp.async.bulk.tensor.2d.global.shared::cta.bulk_group [%0, {%2, %3}], [%1];" ::"l"(m), "r"(src), "r"(c0), "r"(c1) : "memory");
}
__device__ __forceinline__ void tma4d_store(const CUtensorMap* m, uint32_t src, int c0, int c1, int c2, int c3) {
    asm volatile("cp.async.bulk.tensor.4d.global.shared::cta.bulk_group [%0, {%2, %3, %4, %5}], [%1];" ::"l"(m), "r"(src), "r"(c0), "r"(c1), "r"(c2), "r"(c3) : "memory");
}
__device__ __forceinline__ void bulk_load(uint32_t dst, const void* src, uint32_t bytes, uint32_t bar) {
    asm volatile("cp.async.bulk.shared::cluster.global.mbarrier::complete_tx::bytes [%0], [%1], %2, [%3];" ::"r"(dst), "l"(src), "r"(bytes), "r"(bar) : "memory");
}
__device__ __forceinline__ void bulk_store(void* dst, uint32_t src, uint32_t bytes) {
    asm volatile("cp.async.bulk.global.shared::cta.bulk_group [%0], [%1], %2;" ::"l"(dst), "r"(src), "r"(bytes) : "memory");
}
__device__ __forceinline__ void bulk_commit() { asm volatile("cp.async.bulk.commit_group;" ::: "memory"); }
__device__ __forceinline__ void bulk_wait_all() { asm volatile("cp.async.bulk.wait_group 0;" ::: "memory"); }
__device__ __forceinline__ void bulk_wait_read() { asm volatile("cp.async.bulk.wait_group.read 0;" ::: "memory"); }
__device__ __forceinline__ void l2_prefetch(const void* p) { asm volatile("prefetch.global.L2 [%0];" ::"l"(p)); }
__device__ __forceinline__ void fence_async_smem() { asm volatile("fence.proxy.async.shared::cta;" ::: "memory"); }
__device__ __forceinline__ void fence_async_global() { asm volatile("fence.proxy.async.global;" ::: "memory"); }
__device__ __forceinline__ void red_relaxed(unsigned* p) { asm volatile("red.relaxed.gpu.global.add.u32 [%0], 1;" ::"l"(p) : "memory"); }
__device__ __forceinline__ unsigned ld_relaxed(const unsigned* p) { unsigned v; asm volatile("ld.relaxed.gpu.global.u32 %0, [%1];" : "=r"(v) : "l"(p) : "memory"); return v; }
__device__ __forceinline__ bool ctr_done(unsigned v, unsigned target) { return ((v - target) & 0x1FFFFFFu) == 0; }
__device__ __forceinline__ uint32_t clock32() { uint32_t c; asm volatile("mov.u32 %0, %%clock;" : "=r"(c)::"memory"); return c; }
__device__ __forceinline__ void poll(const unsigned* p, unsigned target) { while (!ctr_done(ld_relaxed(p), target)) {} }
__device__ __forceinline__ void cell_put(void* p, uint32_t a, uint32_t b, uint32_t tag) {
    asm volatile("st.relaxed.gpu.global.v4.b32 [%0], {%1, %3, %2, %3};" ::"l"(p), "r"(a), "r"(b), "r"(tag) : "memory");
}
__device__ __forceinline__ uint32_t cell_get(const void* p, uint32_t& a, uint32_t& b, uint32_t tag) {
    uint32_t t0, t1;
    asm volatile("ld.relaxed.gpu.global.v4.b32 {%0, %1, %2, %3}, [%4];" : "=r"(a), "=r"(t0), "=r"(b), "=r"(t1) : "l"(p) : "memory");
    return (t0 ^ tag) | (t1 ^ tag);
}
template <int ID, int N> __device__ __forceinline__ void bar_sync() { asm volatile("bar.sync %0, %1;" ::"n"(ID), "n"(N) : "memory"); }
__device__ __forceinline__ void bar_sync_id(int id, int n) { asm volatile("bar.sync %0, %1;" ::"r"(id), "r"(n) : "memory"); }
template <int ID = 4> __device__ __forceinline__ void gate_wait(uint32_t on) { asm volatile("{\n.reg .pred p;\nsetp.ne.u32 p, %0, 0;\n@p bar.sync %1, 256;\n}" ::"r"(on), "n"(ID) : "memory"); }
__device__ __forceinline__ void gate_open(uint32_t off) { asm volatile("{\n.reg .pred p;\nsetp.eq.u32 p, %0, 0;\n@p bar.arrive 4, 256;\n}" ::"r"(off) : "memory"); }
__device__ __forceinline__ void wg_fence() { asm volatile("wgmma.fence.sync.aligned;" ::: "memory"); }
__device__ __forceinline__ void wg_commit() { asm volatile("wgmma.commit_group.sync.aligned;" ::: "memory"); }
template <int N> __device__ __forceinline__ void wg_wait() { asm volatile("wgmma.wait_group.sync.aligned %0;" ::"n"(N) : "memory"); }
template <int LO = 0, int HI = 56, int N> __device__ __forceinline__ void pin(float (&a)[N]) {
#pragma unroll
    for (int i = LO; i < (HI < N ? HI : N); i++) asm volatile("" : "+f"(a[i])::"memory");
}
__device__ __forceinline__ uint32_t ldg_u16(const void* p) {
    uint32_t v;
    asm volatile("ld.global.nc.u16 %0, [%1];" : "=r"(v) : "l"(p) : "memory");
    return v;
}
__device__ __forceinline__ uint32_t pack2(float lo, float hi) { uint32_t r; asm("cvt.rn.bf16x2.f32 %0, %1, %2;" : "=r"(r) : "f"(hi), "f"(lo)); return r; }
__device__ __forceinline__ float bf_lo(uint32_t v) { return __uint_as_float(v << 16); }
__device__ __forceinline__ float bf_hi(uint32_t v) { return __uint_as_float(v & 0xFFFF0000u); }
__device__ __forceinline__ uint32_t split2(float x) { return pack2(x, x - bf_lo(pack2(x, 0.f))); }
__device__ __forceinline__ void stsm4(uint32_t a, uint32_t r0, uint32_t r1, uint32_t r2, uint32_t r3) {
    asm volatile("stmatrix.sync.aligned.m8n8.x4.shared.b16 [%0], {%1, %2, %3, %4};" ::"r"(a), "r"(r0), "r"(r1), "r"(r2), "r"(r3) : "memory");
}
__device__ __forceinline__ void stsm2(uint32_t a, uint32_t r0, uint32_t r1) {
    asm volatile("stmatrix.sync.aligned.m8n8.x2.shared.b16 [%0], {%1, %2};" ::"r"(a), "r"(r0), "r"(r1) : "memory");
}
__device__ __forceinline__ void ldsm4(uint32_t a, uint32_t (&r)[4]) {
    asm volatile("ldmatrix.sync.aligned.m8n8.x4.shared.b16 {%0, %1, %2, %3}, [%4];" : "=r"(r[0]), "=r"(r[1]), "=r"(r[2]), "=r"(r[3]) : "r"(a) : "memory");
}
__device__ __forceinline__ void ldsm4t(uint32_t a, uint32_t (&r)[4]) {
    asm volatile("ldmatrix.sync.aligned.m8n8.x4.trans.shared.b16 {%0, %1, %2, %3}, [%4];" : "=r"(r[0]), "=r"(r[1]), "=r"(r[2]), "=r"(r[3]) : "r"(a) : "memory");
}
__device__ __forceinline__ void mma16816(float (&c)[4], uint32_t a0, uint32_t a1, uint32_t a2, uint32_t a3, uint32_t b0, uint32_t b1) {
    asm volatile("mma.sync.aligned.m16n8k16.row.col.f32.bf16.bf16.f32 {%0,%1,%2,%3}, {%4,%5,%6,%7}, {%8,%9}, {%0,%1,%2,%3};"
                 : "+f"(c[0]), "+f"(c[1]), "+f"(c[2]), "+f"(c[3]) : "r"(a0), "r"(a1), "r"(a2), "r"(a3), "r"(b0), "r"(b1));
}
__device__ __forceinline__ void mma1688(float (&c)[4], uint32_t a0, uint32_t a1, uint32_t b0) {
    asm volatile("mma.sync.aligned.m16n8k8.row.col.f32.bf16.bf16.f32 {%0,%1,%2,%3}, {%4,%5}, {%6}, {%0,%1,%2,%3};"
                 : "+f"(c[0]), "+f"(c[1]), "+f"(c[2]), "+f"(c[3]) : "r"(a0), "r"(a1), "r"(b0));
}
constexpr uint32_t SB0 = 1024;
__device__ __forceinline__ uint32_t desc_lo(uint32_t off, uint32_t lbo) { return ((SB0 + off) >> 4) + ((lbo >> 4) << 16); }
constexpr uint32_t H_SW = (1024 >> 4) | (1u << 30), H_H = 128 >> 4, H_U = 1024 >> 4;
__device__ __forceinline__ float ex2(float x) { float r; asm("ex2.approx.ftz.f32 %0, %1;" : "=f"(r) : "f"(x)); return r; }
__device__ __forceinline__ float rsq(float x) { float r; asm("rsqrt.approx.ftz.f32 %0, %1;" : "=f"(r) : "f"(x)); return r; }
__device__ __forceinline__ float rcp(float x) { float r; asm("rcp.approx.ftz.f32 %0, %1;" : "=f"(r) : "f"(x)); return r; }
__device__ __forceinline__ float gelu_half(float h) {
    float y = h * fmaf(h * h, 8.f * 0.0356774081363f, 2.f * 0.7978845608029f), t;
    asm("tanh.approx.f32 %0, %1;" : "=f"(t) : "f"(y));
    return fmaf(h, t, h);
}

template <uint32_t HB, int TB>
__device__ __forceinline__ void wgmma_n56_rs(float (&d)[28], const uint32_t (&a)[4], uint32_t lb, int scale_d) {
    asm volatile("{\n.reg .pred p;\n.reg .b64 db;\nsetp.ne.b32 p, %33, 0;\nmov.b64 db, {%32, %34};\n"
        "wgmma.mma_async.sync.aligned.m64n56k16.f32.bf16.bf16 "
        "{%0, %1, %2, %3, %4, %5, %6, %7, %8, %9, %10, %11, %12, %13, %14, %15, %16, %17, %18, %19, %20, %21, %22, %23, %24, %25, %26, %27}, "
        "{%28, %29, %30, %31}, db, p, 1, 1, %35;\n}\n"
        : "+f"(d[0]), "+f"(d[1]), "+f"(d[2]), "+f"(d[3]), "+f"(d[4]), "+f"(d[5]), "+f"(d[6]), "+f"(d[7]), "+f"(d[8]), "+f"(d[9]), "+f"(d[10]), "+f"(d[11]), "+f"(d[12]), "+f"(d[13]), "+f"(d[14]), "+f"(d[15]), "+f"(d[16]), "+f"(d[17]), "+f"(d[18]), "+f"(d[19]), "+f"(d[20]), "+f"(d[21]), "+f"(d[22]), "+f"(d[23]), "+f"(d[24]), "+f"(d[25]), "+f"(d[26]), "+f"(d[27])
        : "r"(a[0]), "r"(a[1]), "r"(a[2]), "r"(a[3]), "r"(lb), "r"(scale_d), "n"(HB), "n"(TB));
}
template <int TA, uint32_t HA, uint32_t HB>
__device__ __forceinline__ void wgmma_n112(float (&d)[56], uint32_t la, uint32_t lb, int scale_d = 1) {
    asm volatile("{\n.reg .b64 da, db;\n.reg .pred p;\nsetp.ne.b32 p, %61, 0;\nmov.b64 da, {%56, %59};\nmov.b64 db, {%57, %60};\n"
        "wgmma.mma_async.sync.aligned.m64n112k16.f32.bf16.bf16 "
        "{%0, %1, %2, %3, %4, %5, %6, %7, %8, %9, %10, %11, %12, %13, %14, %15, %16, %17, %18, %19, %20, %21, %22, %23, %24, %25, %26, %27, %28, %29, %30, %31, %32, %33, %34, %35, %36, %37, %38, %39, %40, %41, %42, %43, %44, %45, %46, %47, %48, %49, %50, %51, %52, %53, %54, %55}, "
        "da, db, p, 1, 1, %58, 1;\n}\n"
        : "+f"(d[0]), "+f"(d[1]), "+f"(d[2]), "+f"(d[3]), "+f"(d[4]), "+f"(d[5]), "+f"(d[6]), "+f"(d[7]), "+f"(d[8]), "+f"(d[9]), "+f"(d[10]), "+f"(d[11]), "+f"(d[12]), "+f"(d[13]), "+f"(d[14]), "+f"(d[15]), "+f"(d[16]), "+f"(d[17]), "+f"(d[18]), "+f"(d[19]), "+f"(d[20]), "+f"(d[21]), "+f"(d[22]), "+f"(d[23]), "+f"(d[24]), "+f"(d[25]), "+f"(d[26]), "+f"(d[27]), "+f"(d[28]), "+f"(d[29]), "+f"(d[30]), "+f"(d[31]), "+f"(d[32]), "+f"(d[33]), "+f"(d[34]), "+f"(d[35]), "+f"(d[36]), "+f"(d[37]), "+f"(d[38]), "+f"(d[39]), "+f"(d[40]), "+f"(d[41]), "+f"(d[42]), "+f"(d[43]), "+f"(d[44]), "+f"(d[45]), "+f"(d[46]), "+f"(d[47]), "+f"(d[48]), "+f"(d[49]), "+f"(d[50]), "+f"(d[51]), "+f"(d[52]), "+f"(d[53]), "+f"(d[54]), "+f"(d[55])
        : "r"(la), "r"(lb), "n"(TA), "n"(HA), "n"(HB), "r"(scale_d));
}
template <int TA, uint32_t HA, uint32_t HB>
__device__ __forceinline__ void wgmma_n8(float (&d)[4], uint32_t la, uint32_t lb, int scale_d = 1) {
    asm volatile("{\n.reg .b64 da, db;\n.reg .pred p;\nsetp.ne.b32 p, %9, 0;\nmov.b64 da, {%4, %7};\nmov.b64 db, {%5, %8};\n"
        "wgmma.mma_async.sync.aligned.m64n8k16.f32.bf16.bf16 "
        "{%0, %1, %2, %3}, "
        "da, db, p, 1, 1, %6, 1;\n}\n"
        : "+f"(d[0]), "+f"(d[1]), "+f"(d[2]), "+f"(d[3])
        : "r"(la), "r"(lb), "n"(TA), "n"(HA), "n"(HB), "r"(scale_d));
}

__device__ __forceinline__ void send8(const float* a, uint32_t rbuf, uint32_t rbar, uint32_t on) {
    asm volatile("{\n.reg .pred p;\nsetp.ne.u32 p, %6, 0;\n@p st.async.weak.shared::cluster.mbarrier::complete_tx::bytes.v4.b32 [%0], {%1,%2,%3,%4}, [%5];\n}"
                 ::"r"(rbuf), "r"(pack2(a[0], a[1])), "r"(pack2(a[2], a[3])), "r"(pack2(a[4], a[5])), "r"(pack2(a[6], a[7])), "r"(rbar), "r"(on) : "memory");
}
__device__ __forceinline__ void send_half(const float (&a)[56], uint32_t rbuf, uint32_t rbar, int t, uint32_t on) {
#pragma unroll
    for (int i = 0; i < 3; i++) send8(a + 28 + 8 * i, rbuf + i * 2048 + t * 16, rbar, on);
    asm volatile("{\n.reg .pred p;\nsetp.ne.u32 p, %4, 0;\n@p st.async.weak.shared::cluster.mbarrier::complete_tx::bytes.v2.b32 [%0], {%1,%2}, [%3];\n}"
                 ::"r"(rbuf + 6144 + t * 8), "r"(pack2(a[52], a[53])), "r"(pack2(a[54], a[55])), "r"(rbar), "r"(on) : "memory");
}
__device__ __forceinline__ void recv_half(uint32_t (&p)[14], uint32_t buf, int t) {
#pragma unroll
    for (int i = 0; i < 3; i++)
        asm volatile("ld.shared.v4.b32 {%0,%1,%2,%3}, [%4];" : "=r"(p[4 * i]), "=r"(p[4 * i + 1]), "=r"(p[4 * i + 2]), "=r"(p[4 * i + 3]) : "r"(buf + i * 2048 + t * 16) : "memory");
    asm volatile("ld.shared.v2.b32 {%0,%1}, [%2];" : "=r"(p[12]), "=r"(p[13]) : "r"(buf + 6144 + t * 8) : "memory");
}

struct Maps { CUtensorMap xl, x, wqkv, hst, w1, w2, xn, old_, ost, out[2], wo; };

__global__ void __cluster_dims__(2, 1, 1) __launch_bounds__(512, 1)
fused_kernel(const __nv_bfloat16* __restrict__ x, const __nv_bfloat16* __restrict__ wqkv,
             const __nv_bfloat16* __restrict__ b1, const __nv_bfloat16* __restrict__ b2, uint8_t* __restrict__ scr,
             uint8_t* __restrict__ out, const __grid_constant__ Maps mp) {
    extern __shared__ __align__(1024) uint8_t smem[];
    const uint32_t sb = smem_u32(smem);
    const uint32_t bar = sb + OFF_BAR;
    const int tid = threadIdx.x, lane = tid & 31;
    const int b = blockIdx.x, z = b & 1, c = b >> 1;
    unsigned* const ctr = reinterpret_cast<unsigned*>(scr + G_CTR);
    if (tid < 112) l2_prefetch(reinterpret_cast<const uint8_t*>(x) + (b * 112 + tid) * 128);
    const int wline = (tid & 127) * 128 + b;
    const bool wfirst = ((wline / 1344) & ~ROT) == 0;
    if (PFW && (tid >> 7) == 1 && wline < 9408 && wfirst) l2_prefetch(reinterpret_cast<const uint8_t*>(wqkv) + wline * 128);
    const uint32_t t_in = clock32();
    TS0(0);
    TG(60);
    const int warp = __shfl_sync(0xffffffffu, tid >> 5, 0);
    int q, j;
    if (c < 4) { q = 15; j = c; } else if (c < 36) { q = (c - 4) & 7; j = (c - 4) >> 3; } else { q = 8 + (c - 36) % 7; j = (c - 36) / 7; }
    const bool g1 = q < 14;
    const int R = q < 8 ? q : q == 15 ? 2 : q < 10 ? q - 8 : q - 7, P = (q >> 3) * 4 + j;
    auto krow = [&](int kb) { const int k = kb + (R & ROT); return (k >= 7 ? k - 7 : k) * 64; };
    auto x_load = [&](int kb) {
        mbar_expect(bar + 8 * (B_FULLQ + kb), 40960);
        tma2d(sb + OFF_A + ((XSLOT >> (4 * kb)) & 7) * 16384, &mp.x, z * D_ + krow(kb), R * 128, bar + 8 * (B_FULLQ + kb));
    };
    if (warp == 12 && elect()) {
#pragma unroll
        for (int i = B_FULLQ; i < B_EMPTYQ; i++) mbar_init(bar + 8 * i, 1);
        mbar_expect(bar + 8 * B_LNIN, BLK);
        tma3d(sb + OFF_A, &mp.xl, 0, 16 * b, 0, bar + 8 * B_LNIN);
        x_load(0);
        TS(15);
    }
    if (warp == 13 && elect()) {
#pragma unroll
        for (int i = B_EMPTYQ; i < B_COUNT; i++)
            mbar_init(bar + 8 * i, i < B_FULL ? (i < B_EMPTYQ + 2 ? 16 : 8) + (((i - B_EMPTYQ) & ~1) == (R & 6 & ~ROT) ? 8 : 0)
                                   : i < B_EMPTY ? 2 : i == B_UDONE ? (g1 ? 3 : 1) : (i < B_AUX || i == B_NONE || i == B_OST || i == B_KV) ? 8
                                   : (i == B_UST || i == B_UST + 1 || i == B_AUX || i == B_HALO) ? 4 : 1);
#pragma unroll
        for (int i = B_RECV1; i < B_UST; i++) mbar_expect(bar + 8 * i, i < B_RECV2 ? 7168 : 8192 - 2048 * z);
    }
    asm volatile("fence.mbarrier_init.release.cluster;" ::: "memory");
    __syncwarp();
    asm volatile("barrier.cluster.arrive.relaxed.aligned;\nbarrier.cluster.wait.aligned;" ::: "memory");
    auto slot = [](uint32_t r) { return r - 6 * ((r * 43) >> 8); };
    auto phase = [](uint32_t r) { return ((r * 43) >> 8) & 1; };
    const uint32_t r_o = g1 ? 16 : 0, r_u = r_o + 4;
    auto epoch = [&]() { mbar_wait(bar + 8 * B_EP, 0); return *reinterpret_cast<volatile unsigned*>(smem + OFF_EP); };

    if (warp < 8) {
        const int wg = warp >> 2, w4 = warp & 3, t = tid & 127, g = lane >> 2, tq = lane & 3;
        asm volatile("setmaxnreg.inc.sync.aligned.u32 208;");
        uint32_t xa[4];
#pragma unroll
        for (int k = 0; k < 4; k++) xa[k] = sb + OFF_A + (warp * 16 + (lane & 15)) * 128 + (((2 * k + (lane >> 4)) ^ (lane & 7)) << 4);
        {
            const int rg = warp & 1, jq = warp >> 1;
            const uint32_t ex = sb + OFF_LNX + (rg * 8 + g) * 32, ew = ex + jq * 8, ls = sb + OFF_LNST + (rg * 8 + g) * 8;
            uint32_t r[4][4], la[4], ha[4], dep = ex | ew | ls;
#pragma unroll
            for (int i = 0; i < 4; i++) {
                const int cg = 14 * jq + 4 * i + ((lane >> 3) & (i < 3 ? 3 : 1));
                la[i] = sb + OFF_A + (cg >> 3) * 2048 + rg * 1024 + (lane & 7) * 128 + (((cg ^ lane) & 7) << 4);
                int pos = 4 * i + (lane >> 3) + (b >= 64 ? 7 : 0);
                if (pos >= 14) pos -= 14;
                ha[i] = sb + OFF_A + jq * 3584 + rg * 1792 + (lane & 7) * 16 + pos * 128;
                dep |= la[i] | ha[i] | xa[i];
            }
            TS0(46);
            mbar_wait(bar + 8 * B_LNIN, dep >> 31);
            TS0(16);
#pragma unroll
            for (int i = 0; i < 4; i++) ldsm4(la[i], r[i]);
            float rs[4] = {0.f, 0.f, 0.f, 0.f}, rt[4] = {0.f, 0.f, 0.f, 0.f}, sq[4], v[28];
            const float sh = bf_lo(__shfl_sync(0xffffffffu, r[0][0], lane & 28));
            mma16816(rs, r[0][0], r[0][1], r[0][2], r[0][3], 0x3F803F80u, 0x3F803F80u);
            mma16816(rt, r[1][0], r[1][1], r[1][2], r[1][3], 0x3F803F80u, 0x3F803F80u);
            mma16816(rs, r[2][0], r[2][1], r[2][2], r[2][3], 0x3F803F80u, 0x3F803F80u);
            mma1688(rt, r[3][0], r[3][1], 0x3F803F80u);
#pragma unroll
            for (int n = 0; n < 14; n++) { v[2 * n] = bf_lo(r[n >> 2][n & 3]) - sh; v[2 * n + 1] = bf_hi(r[n >> 2][n & 3]) - sh; }
#pragma unroll
            for (int n = 0; n < 28; n++) sq[n & 3] = n < 4 ? v[n] * v[n] : fmaf(v[n], v[n], sq[n & 3]);
            const float mq = ((rs[0] + rs[2]) + (rt[0] + rt[2])) * (1.f / 112), dq = mq - sh;
            float m2 = fmaf(-28.f * dq, dq, (sq[0] + sq[1]) + (sq[2] + sq[3]));
            m2 += __shfl_xor_sync(0xffffffffu, m2, 1);
            m2 += __shfl_xor_sync(0xffffffffu, m2, 2);
            asm volatile("st.shared.v2.f32 [%0], {%1, %2};" ::"r"(ew), "f"(mq), "f"(m2) : "memory");
            bar_sync<1, 256>();
            float4 e0, e1;
            asm volatile("ld.shared.v4.f32 {%0,%1,%2,%3}, [%4];" : "=f"(e0.x), "=f"(e0.y), "=f"(e0.z), "=f"(e0.w) : "r"(ex) : "memory");
            asm volatile("ld.shared.v4.f32 {%0,%1,%2,%3}, [%4];" : "=f"(e1.x), "=f"(e1.y), "=f"(e1.z), "=f"(e1.w) : "r"(ex + 16) : "memory");
            const float mean = 0.25f * ((e0.x + e0.z) + (e1.x + e1.z));
            const float d0 = e0.x - mean, d1 = e0.z - mean, d2 = e1.x - mean, d3 = e1.z - mean;
            const float var = fmaxf(((e0.y + e0.w) + (e1.y + e1.w)) * (1.f / D_) + 0.25f * (fmaf(d0, d0, d1 * d1) + fmaf(d2, d2, d3 * d3)), 0.f);
            const float r1 = rsq(var + 1e-5f), sc = rsq(fmaf(1e-5f, var + 1e-5f, var)), of = (sh - mean) * sc;
#pragma unroll
            for (int n = 0; n < 14; n++) r[n >> 2][n & 3] = pack2(fmaf(v[2 * n], sc, of), fmaf(v[2 * n + 1], sc, of));
#pragma unroll
            for (int i = 0; i < 3; i++) stsm4(ha[i], r[i][0], r[i][1], r[i][2], r[i][3]);
            stsm2(ha[3], r[3][0], r[3][1]);
            asm volatile("st.shared.v2.b32 [%0], {%1, %2};" ::"r"(ls), "r"(__float_as_uint(r1)), "r"(split2(-mean)) : "memory");
            TS0(24);
            asm volatile("bar.arrive 10, 288;" ::: "memory");
        }
        const int row = q * 128 + warp * 16 + g;
        const uint32_t bl = ldg_u16(b2 + row), bh = ldg_u16(b2 + row + 8);
        const uint32_t cl = ldg_u16(b1 + (g1 ? row : 0)), ch = ldg_u16(b1 + (g1 ? row : 0) + 8);
        float a1[56];
        float rq[2];
        uint32_t qp[14], kp[14];
        const uint32_t ka = sb + OFF_K + warp * 896 + (lane & 7) * 112 + (lane >> 3) * 16;
        const uint32_t va = sb + OFF_V + (warp * 16 + (lane & 15)) * 112 + (lane >> 4) * 16;
        const uint32_t sta = sb + OFF_RSTD + warp * 64 + tq * 8;
        const uint32_t dA = desc_lo(OFF_A + wg * 8192, 16), dH = desc_lo(OFF_B, 1792), dU = desc_lo(OFF_B, 128);
        auto release = [&](uint32_t a) { mbar_arrive_if0(a, lane); };
        auto sched_fence = [&]() { mbar_wait(bar + 8 * B_LNIN, 0); };
        uint32_t rel = bar + 8 * (B_EMPTYQ + 6);
        auto g1_run = [&](uint32_t r0, uint32_t r1, int gate = 0) {
#pragma unroll 1
            for (uint32_t r = g1 ? r0 : r1; r < r1; r++) {
                const uint32_t s = slot(r), n = min(r + 1, 15u);
                if (gate == 4) gate_wait(r == ATT_STEP);
                TSD(64 + r);
                wg_fence();
#pragma unroll
                for (int k = 0; k < 4; k++) wgmma_n112<1, H_SW, H_H>(a1, dA + s * 1024 + k * 128, dH + s * 896 + k * 224, k ? 1 : r);
                wg_commit();
                wg_wait<1>();
                release(rel);
                rel = bar + 8 * (B_EMPTY + s);
                mbar_wait(bar + 8 * (B_FULL + slot(n)), phase(n));
            }
        };
        uint32_t solo = g1 && !wg;
        asm volatile("" : "+r"(solo));
        solo = __shfl_sync(0xffffffffu, solo, 0);
        auto g1_wait = [&](uint32_t r) { mbar_wait(bar + 8 * (g1 ? B_FULL + r % 6 : B_LNIN), g1 && ((r / 6) & 1)); };
        auto g1_one = [&](uint32_t r) {
#pragma unroll 1
            for (uint32_t n = 0; n < solo; n++) {
                TSD(64 + r);
                wg_fence();
#pragma unroll
                for (int k = 0; k < 4; k++) wgmma_n112<1, H_SW, H_H>(a1, dA + r % 6 * 1024 + k * 128, dH + r % 6 * 896 + k * 224);
                wg_commit();
                wg_wait<1>();
                release(rel);
                rel = bar + 8 * (B_EMPTY + r % 6);
            }
        };
        auto drain = [&]() { wg_wait<0>(); release(rel); rel = bar + 8 * B_NONE; };
        {
            float aq0[28], aq1[28], aq2[28];
            const uint32_t dW = desc_lo(OFF_B + (P & 1) * 16, 16);
            uint32_t xf[2][4][4];
            const uint32_t rb = mapa(bar + 8 * (B_EMPTYQ - 1), z ^ 1);
            auto fetch = [&](int kb, uint32_t (&f)[4][4]) {
                TSD(178 + kb);
                mbar_wait(bar + 8 * (B_FULLQ + kb), 0);
                TSD(170 + kb);
#pragma unroll
                for (int k = 0; k < 4; k++) ldsm4(xa[k] + ((XSLOT >> (4 * kb)) & 7) * 16384, f[k]);
            };
            auto mma = [&](int kb, uint32_t (&f)[4][4], int k0, int k1) {
                const uint32_t d0 = dW + ((WSLOT >> (4 * kb)) & 7) * 1536;
                wg_fence();
#pragma unroll
                for (int k = k0; k < k1; k++) {
                    const uint32_t d = d0 + (k >> 1) * 768 + (k & 1) * 128;
                    const int sc = k > 0 ? 1 : kb;
                    wgmma_n56_rs<H_SW, 1>(aq0, f[k], d, sc);
                    wgmma_n56_rs<H_SW, 1>(aq1, f[k], d + 256, sc);
                    wgmma_n56_rs<H_SW, 1>(aq2, f[k], d + 512, sc);
                }
            };
            auto retire = [&](int kb) {
                wg_commit();
                wg_wait<1>();
                mbar_arrive_if0(bar + 8 * (B_EMPTYQ + kb - 1), lane | (kb < 1));
                asm volatile("{\n.reg .pred p;\nsetp.eq.u32 p, %1, 0;\n@p mbarrier.arrive.shared::cluster.b64 _, [%0];\n}"
                             ::"r"(rb + 8 * kb), "r"(lane | ((uint32_t)(kb - 1) > 1)) : "memory");
            };
            auto stage = [&](int kb, uint32_t (&f)[4][4], uint32_t (&n)[4][4]) {
                mma(kb, f, 0, KS);
                retire(kb);
                fetch(kb + 1, n);
                if (KS < 4) { mma(kb, f, KS, 4); wg_commit(); }
            };
            fetch(0, xf[0]);
#pragma unroll kQUnroll
            for (int kb = 0; kb < 6; kb += 2) {
                stage(kb, xf[0], xf[1]);
                stage(kb + 1, xf[1], xf[0]);
            }
            mma(6, xf[0], 0, KS);
            retire(6);
            TS0(2);
            mbar_wait(bar + 8 * B_AUX, 0);
            {
                uint32_t (&f)[4] = xf[1][0];
                const uint2* mt = reinterpret_cast<const uint2*>(smem + OFF_STATS) + warp * 16 + g;
                const uint2 m0 = mt[0], m1 = mt[8];
                const uint32_t sel = tq == 0 ? 0x1010 : tq == 1 ? 0x3232 : 0x4444;
                f[0] = __byte_perm(m0.y, 0, sel); f[1] = __byte_perm(m1.y, 0, sel); f[2] = f[3] = 0;
                rq[0] = __uint_as_float(m0.x); rq[1] = __uint_as_float(m1.x);
                asm volatile("" : "+r"(f[0]), "+r"(f[1]), "+r"(f[2]), "+r"(f[3])::"memory");
                const uint32_t d = desc_lo(OFF_CSB + (P & 1) * 128, 0);
                mma(6, xf[0], KS, 4);
                wgmma_n56_rs<H_H, 0>(aq1, f, d + 64, 1);
                wgmma_n56_rs<H_H, 0>(aq2, f, d + 128, 1);
                wgmma_n56_rs<H_H, 0>(aq0, f, d, 1);
                wg_commit();
            }
            g1_wait(0);
            g1_run(0, wg ? 0 : NE);
            drain();
            pin(aq0); pin(aq1); pin(aq2);
            TSW(3);
            mbar_wait(bar + 8 * (B_EMPTYQ + 5), 0);
#pragma unroll
            for (int i = 0; i < 14; i++) { kp[i] = pack2(aq1[2 * i], aq1[2 * i + 1]); qp[i] = pack2(aq2[2 * i], aq2[2 * i + 1]); }
            stsm4(ka + 896, kp[1], kp[3], kp[5], kp[7]);
            stsm4(ka + 896 + 48, kp[7], kp[9], kp[11], kp[13]);
#pragma unroll
            for (int n = 0; n < 3; n++) stsm4(va + 896 + n * 32, qp[4 * n], qp[4 * n + 1], qp[4 * n + 2], qp[4 * n + 3]);
            stsm2(va + 896 + 96, qp[12], qp[13]);
            __syncwarp();
            mbar_arrive_if0(bar + 8 * B_QKV, tid - 224);
            release(bar + 8 * B_KV);
#pragma unroll
            for (int i = 0; i < 14; i++) qp[i] = pack2(aq0[2 * i], aq0[2 * i + 1]);
            TSW(4);
        }
        g1_run(wg ? 0 : NE, wg ? PRE1 : PRE0);
        {
            uint32_t kf[2][3][4], vf[2][3][4];
            const bool up0 = 2 * tq > g, up1 = 2 * tq + 1 > g, edge = (R | warp) == 0;
            float rk[2][2], fs[2][2], rs[3][2];
            mbar_wait(bar + 8 * (warp ? B_KV : B_HALO), 0);
#pragma unroll
            for (int i = 0; i < 3; i++)
                asm volatile("ld.shared.v2.f32 {%0,%1}, [%2];" : "=f"(rs[i][0]), "=f"(rs[i][1]) : "r"(sta + i * 32) : "memory");
#pragma unroll
            for (int hd = 0; hd < 2; hd++) {
                ldsm4(ka + hd * 48, kf[hd][0]);
#pragma unroll
                for (int i = 0; i < 4; i++) { kf[hd][1][i] = kp[6 * hd + 2 * i]; kf[hd][2][i] = kp[6 * hd + 2 * i + 1]; }
                ldsm4t(va + hd * 48, vf[hd][0]); ldsm4t(va + hd * 48 + 32, vf[hd][1]);
                ldsm4t(ka + (OFF_V - OFF_K) + warp * 896 + hd * 48 + 1792, vf[hd][2]);
            }
            const uint32_t q0l = tq < 2 ? qp[6] : 0, q0h = tq < 2 ? qp[7] : 0, q1l = tq < 2 ? 0 : qp[6], q1h = tq < 2 ? 0 : qp[7];
            const uint32_t mk = (up0 ? 0xFFFFu : 0u) | (up1 ? 0xFFFF0000u : 0u);
            TSW(7);
            g1_run(wg ? PRE1 : PRE0, ATT_STEP);
#pragma unroll
            for (int i = 0; i < 4; i++) {
                rk[i >> 1][i & 1] = ((i & 1) ? up1 : up0) ? rs[i >> 1][i & 1] : rs[(i >> 1) + 1][i & 1];
                fs[i >> 1][i & 1] = rk[i >> 1][i & 1] * (rq[i >> 1] * (0.18898223650461362f * 1.4426950408889634f));
                asm volatile("" : "+f"(fs[i >> 1][i & 1])::"memory");
            }
            drain();
            sched_fence();
            TS0(19);
            float sc[2][3][4];
#pragma unroll
            for (int u = 0; u < 3; u++) {
#pragma unroll
                for (int i = 0; i < 8; i++) sc[i >> 2][u][i & 3] = 0.f;
                mma16816(sc[0][u], qp[0], qp[1], qp[2], qp[3], kf[0][u][0], kf[0][u][1]);
                mma16816(sc[1][u], q1l, q1h, qp[8], qp[9], kf[1][u][0], kf[1][u][1]);
            }
#pragma unroll
            for (int u = 0; u < 3; u++) {
                mma16816(sc[0][u], qp[4], qp[5], q0l, q0h, kf[0][u][2], kf[0][u][3]);
                mma16816(sc[1][u], qp[10], qp[11], qp[12], qp[13], kf[1][u][2], kf[1][u][3]);
            }
            float e[2][2][2], mx[2][2], sm[2][4];
#pragma unroll
            for (int hd = 0; hd < 2; hd++) {
                e[hd][0][0] = (up0 ? sc[hd][0][0] : sc[hd][1][0]) * fs[0][0];
                e[hd][0][1] = (up1 ? sc[hd][0][1] : sc[hd][1][1]) * fs[0][1];
                e[hd][1][0] = (up0 ? sc[hd][1][2] : sc[hd][2][2]) * fs[1][0];
                e[hd][1][1] = (up1 ? sc[hd][1][3] : sc[hd][2][3]) * fs[1][1];
                if (edge && up0) e[hd][0][0] = -1e30f;
                if (edge && up1) e[hd][0][1] = -1e30f;
                mx[hd][0] = fmaxf(e[hd][0][0], e[hd][0][1]);
                mx[hd][1] = fmaxf(e[hd][1][0], e[hd][1][1]);
            }
#pragma unroll
            for (int o = 1; o <= 2; o <<= 1)
#pragma unroll
                for (int i = 0; i < 4; i++) mx[i >> 1][i & 1] = fmaxf(mx[i >> 1][i & 1], __shfl_xor_sync(0xffffffffu, mx[i >> 1][i & 1], o));
            uint32_t pp[2][2], pu[2][2];
#pragma unroll
            for (int i = 0; i < 4; i++) {
                const float p0 = ex2(e[i >> 1][i & 1][0] - mx[i >> 1][i & 1]), p1 = ex2(e[i >> 1][i & 1][1] - mx[i >> 1][i & 1]);
                pp[i >> 1][i & 1] = pack2(p0 * rk[i & 1][0], p1 * rk[i & 1][1]);
                pu[i >> 1][i & 1] = pack2(p0, p1);
            }
            float ov[2][4][4];
#pragma unroll
            for (int hd = 0; hd < 2; hd++)
#pragma unroll
                for (int n = 0; n < 4; n++) {
                    ov[hd][n][0] = ov[hd][n][1] = ov[hd][n][2] = ov[hd][n][3] = 0.f;
                    mma16816(ov[hd][n], pp[hd][0] & mk, 0u, pp[hd][0] & ~mk, pp[hd][1] & mk, vf[hd][n >> 1][2 * (n & 1)], vf[hd][n >> 1][2 * (n & 1) + 1]);
                }
#pragma unroll
            for (int hd = 0; hd < 2; hd++) {
                sm[hd][0] = sm[hd][1] = sm[hd][2] = sm[hd][3] = 0.f;
                mma1688(sm[hd], pu[hd][0], pu[hd][1], 0x3F803F80u);
            }
#pragma unroll
            for (int hd = 0; hd < 2; hd++)
#pragma unroll
                for (int n = 0; n < 4; n++) mma1688(ov[hd][n], 0u, pp[hd][1] & ~mk, vf[hd][2][n]);
            sched_fence();
            TS0(18);
            bar_sync<1, 256>();
            g1_one(ATT_STEP);
#pragma unroll
            for (int i = 0; i < 4; i++) asm volatile("" : "+f"(sm[i >> 1][2 * (i & 1)])::"memory");
            uint32_t op[16];
            op[14] = op[15] = 0;
#pragma unroll
            for (int i = 0; i < 4; i++) sm[i >> 1][i & 1] = rcp(sm[i >> 1][2 * (i & 1)]);
#pragma unroll
            for (int n = 0; n < 7; n++) {
                const bool hb = n > 3 || (n == 3 && tq >= 2);
#pragma unroll
                for (int h = 0; h < 2; h++) {
                    const float r = hb ? sm[1][h] : sm[0][h];
                    const float x0 = hb ? ov[1][n >= 3 ? n - 3 : 0][2 * h] : ov[0][n <= 3 ? n : 0][2 * h];
                    const float x1 = hb ? ov[1][n >= 3 ? n - 3 : 0][2 * h + 1] : ov[0][n <= 3 ? n : 0][2 * h + 1];
                    op[2 * n + h] = pack2(x0 * r, x1 * r);
                }
            }
#pragma unroll
            for (int i = 0; i < 14; i++) asm volatile("" : "+r"(op[i])::"memory");
            g1_wait(ATT_STEP + 1);
            if (NQ) { g1_one(ATT_STEP + 1); g1_wait(ATT_STEP + 2); }
#pragma unroll
            for (int n = 0; n < 4; n++) stsm4(xa[n] + OFF_OST, op[4 * n], op[4 * n + 1], op[4 * n + 2], op[4 * n + 3]);
            __syncwarp();
            release(bar + 8 * B_OST);
            g1_one(ATT_STEP + 1 + NQ);
            g1_wait(ATT_STEP + 2 + NQ);
            TSW(5);
        }
        const uint32_t peer = z ^ 1;
        if (!GIN) gate_wait(wg && g1);
        g1_run(wg ? ATT_STEP : ATT_STEP + 2 + NQ, 16, GIN ? 4 : 0);
        if (GIN < 2) gate_open(wg | !g1);
        mbar_wait(bar + 8 * B_FREE, 0);
        drain();
        if (GIN == 2) gate_open(wg | !g1);
        pin(a1);
        TSW(6);
        send_half(a1, mapa(sb + OFF_RECV1 + wg * 7168, peer), mapa(bar + 8 * (B_RECV1 + wg), peer), t, g1);
#pragma unroll
        for (int i = 0; i < 28; i++) a1[i] = fmaf(a1[i], 0.5f, 0.5f * bf_lo((i & 2) ? ch : cl));
        pin<0, 28>(a1);
        if (g1) {
            uint32_t p[14];
            mbar_wait(bar + 8 * (B_RECV1 + wg), 0);
            TSW(8);
            recv_half(p, sb + OFF_RECV1 + wg * 7168, t);
#pragma unroll
            for (int i = 0; i < 14; i++)
                p[i] = pack2(gelu_half(fmaf(bf_lo(p[i]), 0.5f, a1[2 * i])), gelu_half(fmaf(bf_hi(p[i]), 0.5f, a1[2 * i + 1])));
            const uint32_t dst = sb + OFF_UST + wg * 7168 + w4 * 256 + (lane & 15) * 16;
#pragma unroll
            for (int n = 0; n < 3; n++) stsm4(dst + (2 * n + (lane >> 4)) * 1024, p[4 * n], p[4 * n + 1], p[4 * n + 2], p[4 * n + 3]);
            stsm2(dst + 6144, p[12], p[13]);
            __syncwarp();
            release(bar + 8 * (B_UST + wg));
            TSW(9);
        }
        float a2[56];
#pragma unroll 1
        for (uint32_t r = r_o; r < r_u; r++) {
            const uint32_t s = slot(r);
            mbar_wait(bar + 8 * (B_FULL + s), phase(r));
            TSD(64 + 17 + r - r_o);
            wg_fence();
#pragma unroll
            for (int k = 0; k < 4; k++) wgmma_n112<0, H_SW, H_U>(a2, dA + s * 1024 + k * 2, dU + s * 896 + k * 16, k ? 1 : r - r_o);
            wg_commit();
            wg_wait<1>();
            release(rel);
            rel = bar + 8 * (B_EMPTY + s);
        }
        drain();
        TSW(10);
#pragma unroll 1
        for (uint32_t r = r_u; r < r_u + 14; r++) {
            const uint32_t s = slot(r);
            gate_wait(wg && r == r_u + 14 - NS2);
            mbar_wait(bar + 8 * (B_FULL + s), phase(r));
            TSD(85 + r - r_u);
            wg_fence();
#pragma unroll
            for (int k = 0; k < 4; k++) wgmma_n112<1, H_SW, H_U>(a2, dA + s * 1024 + k * 128, dU + s * 896 + k * 16);
            wg_commit();
            wg_wait<1>();
            release(rel);
            rel = bar + 8 * (B_EMPTY + s);
        }
        gate_open(wg);
        mbar_wait(bar + 8 * B_UDONE, 0);
        wg_wait<0>();
        pin(a2);
        TSW(11);
        {
            const uint32_t rbuf = mapa(sb + OFF_RECV2 + wg * 8192 + t * 16, peer) - (z ? 0 : 2048), rbar = mapa(bar + 8 * (B_RECV2 + wg), peer);
#pragma unroll
            for (int i = 3; i >= 0; i--) send8(a2 + 24 + 8 * i, rbuf + i * 2048, rbar, i | z);
            mbar_wait(bar + 8 * B_XR, 0);
#pragma unroll
            for (int k = 0; k < 4; k++) {
                uint32_t xr[4];
                ldsm4(xa[k] + slot(r_u + 14) * 16384, xr);
#pragma unroll
                for (int i = 0; i < 8; i++) a2[8 * k + i] += ((i & 1) ? bf_hi(xr[i >> 1]) : bf_lo(xr[i >> 1])) + bf_lo((i & 2) ? bh : bl);
            }
            pin<0, 32>(a2);
            const uint32_t oa = sb + OFF_OUT + (warp * 16 + (lane >> 3)) * 128 + (((lane ^ (lane >> 3)) & 7) << 4);
            const uint32_t oo = (q * 128 + warp * 16 + (lane >> 3)) * 896 + j * 224 + z * 128 + (lane & 7) * 16;
            uint8_t* og = out + oo;
            mbar_wait(bar + 8 * (B_RECV2 + wg), (oa | oo | (uint32_t)((uint64_t)og >> 32)) >> 31);
            TSW(12);
            uint32_t u[16];
#pragma unroll
            for (int i = 0; i < 4; i++)
                asm volatile("ld.shared.v4.b32 {%0,%1,%2,%3}, [%4];" : "=r"(u[4 * i]), "=r"(u[4 * i + 1]), "=r"(u[4 * i + 2]), "=r"(u[4 * i + 3]) : "r"(sb + OFF_RECV2 + wg * 8192 + i * 2048 + t * 16) : "memory");
#pragma unroll
            for (int e = 0; e < 16; e++) u[e] = pack2(a2[2 * e] + bf_lo(u[e]), a2[2 * e + 1] + bf_hi(u[e]));
#pragma unroll
            for (int i = 0; i < 4; i++) stsm4(xa[i] + OFF_OUT, u[4 * i], u[4 * i + 1], u[4 * i + 2], u[4 * i + 3]);
            __syncwarp();
#pragma unroll
            for (int i = 0; i < 4; i++)
                asm volatile("ld.shared.v4.b32 {%0,%1,%2,%3}, [%4];" : "=r"(u[4 * i]), "=r"(u[4 * i + 1]), "=r"(u[4 * i + 2]), "=r"(u[4 * i + 3]) : "r"((oa ^ ((i & 1) << 6)) + i * 512) : "memory");
            if ((lane & 7) < 8 - 2 * z) {
#pragma unroll
                for (int i = 0; i < 4; i++)
                    asm volatile("st.global.v4.b32 [%0], {%1,%2,%3,%4};" ::"l"(og + i * 3584), "r"(u[4 * i]), "r"(u[4 * i + 1]), "r"(u[4 * i + 2]), "r"(u[4 * i + 3]) : "memory");
            }
        }
        TSW(13);
    } else if (warp < 12) {
        asm volatile("setmaxnreg.dec.sync.aligned.u32 64;");
        const int hw = warp - 8, t = tid & 127;
        while (clock32() - t_in < DLY1) SPIN;
        if (wline < 9408 && !wfirst) l2_prefetch(reinterpret_cast<const uint8_t*>(wqkv) + wline * 128);
        uint8_t* cscell = scr + G_CS + ((P * 8 + R) * 2 + z) * 512 + (t >> 2) * 16;
        if ((lane & 3) == 0) cell_put(cscell, 0, 0, 0);
        uint8_t* cells = scr + G_HALO + ((R * 8 + P) * 2 + z) * 3584 + min(t, 111) * 16;
        cell_put(cells, 0, 0, 0);
        cell_put(cells + 1792, 0, 0, 0);
        reinterpret_cast<uint32_t*>(smem + OFF_ONES)[t] = t < 64 ? 0x3F803F80u : 0;
        fence_async_smem();
        bar_sync<12, 128>();
        const unsigned e1 = epoch();
        {
            const uint32_t da = desc_lo(OFF_B + min((R & 1) * 2 + z, 2) * 4096, 16), db = desc_lo(OFF_ONES, 128);
            float c0[4];
            const int st = R & 6 & ~ROT;
            mbar_wait(bar + 8 * (B_FULLQ + st), 0);
            mbar_wait(bar + 8 * (B_FULLQ + st + 1), 0);
            TSH(47);
            wg_fence();
#pragma unroll
            for (int k = 0; k < 8; k++)
                wgmma_n8<1, H_SW, H_H>(c0, da + ((WSLOT >> (4 * st + (k & 4))) & 7) * 1536 + (k & 2) * 384 + (k & 1) * 128, db + (k >= 4 && R >= 6 ? 16 : 0), k);
            wg_commit();
            wg_wait<0>();
            pin(c0);
            if ((lane & 3) == 0) cell_put(cscell, __float_as_uint(c0[0]), __float_as_uint(c0[2]), e1);
            if (lane < 4) asm volatile("mbarrier.arrive.shared::cluster.b64 _, [%0];" ::"r"(mapa(bar + 8 * (B_EMPTYQ + st + (lane >> 1)), lane & 1)) : "memory");
            TSH(43);
        }
        mbar_wait(bar + 8 * (B_FULLQ + GATHER), 0);
        TSH(39);
        {
            const bool cw = hw < 3;
            const uint8_t* src = cw ? scr + G_CS + P * 8192 + t * 16 : scr + G_STATS + (z * 1024 + R * 128 + lane) * 16;
            uint32_t a[5], d[5], bad;
            do {
                bad = 0;
#pragma unroll
                for (int i = 0; i < 4; i++) bad |= cell_get(src + i * (cw ? 2048 : 512), a[i], d[i], e1);
                if (t >= 120) bad |= cell_get(src - (R ? 512 : 0), a[4], d[4], e1);
            } while (bad);
            TSH(45);
            if (cw) {
                uint4* cb = reinterpret_cast<uint4*>(smem + OFF_CSB) + (t >> 3) * 16 + (t & 7);
                const uint32_t lo = split2((__uint_as_float(a[0]) + __uint_as_float(a[1])) + (__uint_as_float(a[2]) + __uint_as_float(a[3])));
                const uint32_t hi = split2((__uint_as_float(d[0]) + __uint_as_float(d[1])) + (__uint_as_float(d[2]) + __uint_as_float(d[3])));
                cb[0] = make_uint4(lo, lo, 0, 0);
                cb[8] = make_uint4(hi, hi, 0, 0);
            } else {
                uint2* st = reinterpret_cast<uint2*>(smem + OFF_STATS) + lane;
                uint32_t* rd = reinterpret_cast<uint32_t*>(smem + OFF_RSTD) + lane;
#pragma unroll
                for (int i = 0; i < 4; i++) { st[32 * i] = make_uint2(a[i], d[i]); rd[8 + 32 * i] = a[i]; }
                if (t >= 120) rd[-24] = a[4];
            }
            fence_async_smem();
            __syncwarp();
            mbar_arrive_if0(bar + 8 * B_AUX, lane);
            TSH(41);
        }
        {
            uint2* kv = reinterpret_cast<uint2*>(smem + OFF_K) + min(t, 111);
            mbar_wait(bar + 8 * B_QKV, 0);
            uint2 k2 = kv[896], v2 = kv[1792 + (OFF_V - OFF_K) / 8];
            cell_put(cells, k2.x, k2.y, e1);
            cell_put(cells + 1792, v2.x, v2.y, e1);
            k2 = v2 = make_uint2(0, 0);
            if (R > 0) while (cell_get(cells - 16 * 3584, k2.x, k2.y, e1) | cell_get(cells - 16 * 3584 + 1792, v2.x, v2.y, e1)) {}
            kv[0] = k2;
            kv[(OFF_V - OFF_K) / 8] = v2;
            mbar_wait(bar + 8 * B_KV, 0);
            __syncwarp();
            mbar_arrive_if0(bar + 8 * B_HALO, lane);
            TSH(40);
        }
        if (hw == 2) {
            mbar_wait(bar + 8 * B_OST, 0);
            if (elect()) {
                asm volatile("mbarrier.arrive.relaxed.cluster.shared::cluster.b64 _, [%0];" ::"r"(mapa(bar + 8 * B_FREE, z ^ 1)) : "memory");
                fence_async_smem();
                tma2d_store(&mp.ost, sb + OFF_OST, z * 64, P * 1024 + R * 128);
                bulk_commit();
                bulk_wait_all();
                red_relaxed(ctr + C_O + (R * 2 + (P >> 2)) * 32);
                asm volatile("mbarrier.arrive.relaxed.cluster.shared::cluster.b64 _, [%0];" ::"r"(mapa(bar + 8 * B_UDONE, z ^ 1)) : "memory");
                TS(21);
            }
        } else if (hw < 2 && g1) {
            const int ub = 2 * q + hw, zz = ub >= 14 ? 1 : 0;
            uint8_t* ud = scr + G_BIMG + ((8 + ub) * 4 + j) * BLK;
            mbar_wait(bar + 8 * (B_UST + hw), 0);
            if (elect()) {
                fence_async_smem();
                bulk_store(ud + ((7 * z + 1 + 6 * zz) % 14) * 1024, sb + OFF_UST + hw * 7168 + 1024, 6144);
                bulk_store(ud + (7 * z + 6 * zz) * 1024, sb + OFF_UST + hw * 7168, 1024);
                bulk_commit();
                bulk_wait_all();
                red_relaxed(ctr + C_U + (zz * 2 + hw) * 32);
                mbar_arrive(bar + 8 * B_UDONE);
                TS(22 + hw);
            }
        }
    } else {
        asm volatile("setmaxnreg.dec.sync.aligned.u32 32;");
        auto wait_free = [&](uint32_t r, uint32_t first) {
            const uint32_t a = r < 6 ? B_EMPTYQ + ((first >> (4 * r)) & 7) : B_EMPTY + slot(r);
            mbar_wait(bar + 8 * a, r < 6 ? 0 : phase(r) ^ 1);
        };
        if (warp == 12) {
            TS(14);
            if (elect()) {
#pragma unroll 1
                for (int kb = 0; kb < 7; kb++) {
                    if (kb < 2) while (clock32() - t_in < (kb ? DLY2 : DLY0)) SPIN;
                    if (kb >= QDEPTH) { mbar_wait(bar + 8 * (B_FULLQ + kb - QDEPTH), 0); TS(25 + kb - QDEPTH); }
                    if (kb >= 5) mbar_wait(bar + 8 * (B_EMPTYQ + kb - 5), 0);
                    if (kb > 0) x_load(kb);
                    tma3d_mc(sb + OFF_B + ((WSLOT >> (4 * kb)) & 7) * 24576 + z * 12288, &mp.wqkv, (P * 56) & ~15, krow(kb) + z * 32, 0, bar + 8 * (B_FULLQ + kb));
                }
                TS(17);
                ld_relaxed(ctr + C_O + ((q & ~1) + z) * 32);
                mbar_wait(bar + 8 * B_LNFREE, 0);
                if (!g1) {
                    const int ic = (q - 14) * 8 + j * 2 + z, rot = ic >> 3;
                    mbar_wait(bar + 8 * (B_EMPTYQ + 2), 0);
                    mbar_expect(bar + 8 * B_GO, 2 * BLK);
#pragma unroll 1
                    for (int i = 0; i < 2; i++) tma3d(sb + OFF_A + i * BLK, &mp.wo, 0, (ic >> 1) * 56, (z * 2 + i) * 14, bar + 8 * B_GO);
                    mbar_wait(bar + 8 * B_GO, 0);
#pragma unroll 1
                    for (int i = 0; i < 2; i++) {
                        uint8_t* dst = scr + G_BIMG + (ic * 2 + i) * BLK;
                        bulk_store(dst + rot * 6144, sb + OFF_A + i * BLK, 8192);
                        bulk_store(dst + (rot ^ 1) * 8192, sb + OFF_A + i * BLK + 8192, 6144);
                    }
                    bulk_commit();
                    bulk_wait_all();
                    red_relaxed(ctr + C_WO);
                    TS(44);
                }
#pragma unroll 1
                for (uint32_t r = 0; r < r_o; r++) {
                    const uint32_t s = slot(r), fb = bar + 8 * (B_FULL + s);
                    wait_free(r, 0x654320u);
                    mbar_expect(fb, 16384);
                    tma3d(sb + OFF_A + s * 16384, &mp.w1, 0, z * 1024 + r * 64, 2 * q, fb);
                    TS(99 + r);
                }
                mbar_wait(bar + 8 * B_OST, 0);
                poll(ctr + C_O + ((q & ~1) + z) * 32, epoch() * 8);
                fence_async_global();
                TS(32);
#pragma unroll 1
                for (uint32_t r = r_o; r < r_u; r++) {
                    const uint32_t s = slot(r), fb = bar + 8 * (B_FULL + s);
                    wait_free(r, 0x654320u);
                    mbar_expect(fb, 16384);
                    tma2d(sb + OFF_A + s * 16384, &mp.old_, 0, (4 * z + r - r_o) * S_ + q * 128, fb);
                    TS(99 + 17 + r - r_o);
                }
#pragma unroll 1
                for (uint32_t i = 0; i < 14; i++) {
                    const uint32_t r = r_u + i, s = slot(r), fb = bar + 8 * (B_FULL + s);
                    wait_free(r, 0x654320u);
                    mbar_expect(fb, 16384);
                    tma3d(sb + OFF_A + s * 16384, &mp.w2, 0, (14 * z + (i < 7 ? 2 * i : 2 * i - 13)) * 64, 2 * q, fb);
                    TS(99 + 21 + i);
                }
                wait_free(r_u + 14, 0);
                mbar_expect(bar + 8 * B_XR, 16384);
                tma2d(sb + OFF_A + slot(r_u + 14) * 16384, &mp.xn, j * 112 + z * 64, q * 128, bar + 8 * B_XR);
            }
        } else if (warp == 13) {
            if (elect()) {
#pragma unroll 1
                for (int ph = g1 ? 0 : 1; ph < 4; ph++) {
                    const uint8_t* src = ph == 0 ? scr + G_HIMG + (64 * z + j) * BLK : scr + G_BIMG + ((ph == 1 ? 4 * z : 6 + 14 * z + ph) * 4 + j) * BLK;
                    const uint32_t r0 = ph == 0 ? 0 : r_o + (ph == 1 ? 0 : 7 * ph - 10), r1 = r_o + (ph == 0 ? 0 : 7 * ph - 3);
#pragma unroll 1
                    for (uint32_t r = r0; r < r1; r++, src += ph < 2 ? 4 * BLK : 8 * BLK) {
                        const uint32_t s = slot(r), fb = bar + 8 * (B_FULL + s);
                        wait_free(r, 0x644332u);
                        mbar_expect(fb, BLK);
                        mbar_wait(bar + 8 * (B_GO + ph), 0);
                        bulk_load(sb + OFF_B + s * BLK, src, BLK, fb);
                        TS(134 + 16 + (ph > 0) + r - r_o);
                    }
                }
            }
        } else if (warp == 14) {
            uint8_t* stcell = scr + G_STATS + ((lane & 1) * 1024 + 8 * b + (lane >> 1)) * 16;
            if (lane < 16) cell_put(stcell, 0, 0, 0);
            const unsigned e1 = (ld_relaxed(ctr + C_LN) >> 7) + 1;
            if (lane == 0) {
                *reinterpret_cast<volatile unsigned*>(smem + OFF_EP) = e1;
                mbar_arrive(bar + 8 * B_EP);
                TS(36);
            }
            bar_sync<10, 288>();
            if (elect()) {
                fence_async_smem();
                TS(42);
                tma4d_store(&mp.hst, sb + OFF_A, 0, 0, b & 3, b & ~3);
                bulk_commit();
            }
            __syncwarp();
            if (lane < 16) {
                const uint2 v = reinterpret_cast<const uint2*>(smem + OFF_LNST)[lane];
                cell_put(stcell, v.x, v.y, e1);
            }
            bulk_wait_all();
            __syncwarp();
            if (lane == 0) {
                red_relaxed(ctr + C_LN);
                mbar_arrive(bar + 8 * B_LNFREE);
                TS(37);
                ld_relaxed(ctr + C_U + z * 64);
                ld_relaxed(ctr + C_U + z * 64 + 32);
#pragma unroll 1
                for (int ph = g1 ? 0 : 1; ph < 4; ph++) {
                    if (ph) mbar_wait(bar + 8 * (ph == 1 ? B_HALO : g1 ? B_UST : B_OST), 0);
                    poll(ctr + ph * 32 + (ph >> 1) * z * 64, e1 * (ph == 0 ? 128 : ph == 1 ? 16 : 56));
                    fence_async_global();
                    mbar_arrive(bar + 8 * (B_GO + ph));
                    TS(ph == 0 ? 33 : ph == 1 ? 63 : 32 + ph);
                }
            }
        } else {
            if ((sb & 0x3FFFF) != SB0) __trap();
            if (elect()) {
#pragma unroll 1
                for (int i = 2; i < 12; i++) asm volatile("prefetch.tensormap [%0];" ::"l"(reinterpret_cast<const CUtensorMap*>(&mp) + i) : "memory");
            }
            __syncwarp();
            if (elect()) {
                mbar_watch(bar + 8 * B_RECV2);
                mbar_watch(bar + 8 * (B_RECV2 + 1));
            }
        }
    }
}

typedef CUresult (*EncodeFn)(CUtensorMap*, CUtensorMapDataType, cuuint32_t, void*, const cuuint64_t*, const cuuint64_t*, const cuuint32_t*,
                             const cuuint32_t*, CUtensorMapInterleave, CUtensorMapSwizzle, CUtensorMapL2promotion, CUtensorMapFloatOOBfill);

void encode(EncodeFn fn, CUtensorMap* m, const void* p, int rank, const cuuint64_t* dims, const cuuint64_t* strides, const cuuint32_t* box, bool swz) {
    const cuuint32_t es[4] = {1, 1, 1, 1};
    fn(m, CU_TENSOR_MAP_DATA_TYPE_BFLOAT16, rank, const_cast<void*>(p), dims, strides, box, es, CU_TENSOR_MAP_INTERLEAVE_NONE,
       swz ? CU_TENSOR_MAP_SWIZZLE_128B : CU_TENSOR_MAP_SWIZZLE_NONE, CU_TENSOR_MAP_L2_PROMOTION_L2_128B, CU_TENSOR_MAP_FLOAT_OOB_FILL_NONE);
}

}

extern "C" void kernel_launch(void* const* d_in, const int* in_sizes, int n_in, void* d_out, int out_size) {
    const __nv_bfloat16* x = (const __nv_bfloat16*)d_in[0];
    const __nv_bfloat16* wqkv = (const __nv_bfloat16*)d_in[1];
    const __nv_bfloat16* wo = (const __nv_bfloat16*)d_in[2];
    const __nv_bfloat16* w1 = (const __nv_bfloat16*)d_in[4];
    const __nv_bfloat16* b1 = (const __nv_bfloat16*)d_in[5];
    const __nv_bfloat16* w2 = (const __nv_bfloat16*)d_in[6];
    const __nv_bfloat16* b2 = (const __nv_bfloat16*)d_in[7];

    void* fp = nullptr;
    cudaDriverEntryPointQueryResult qr;
    cudaGetDriverEntryPoint("cuTensorMapEncodeTiled", &fp, cudaEnableDefault, &qr);
    EncodeFn fn = (EncodeFn)fp;
    void* sp = nullptr;
    cudaGetSymbolAddress(&sp, g_scratch);
    uint8_t* scr = (uint8_t*)sp;
    void *o = scr + G_O, *himg = scr + G_HIMG;

    Maps mp;
    { cuuint64_t d[3] = {64, 2048, 7}, s[2] = {896, 128}; cuuint32_t bx[3] = {64, 16, 7}; encode(fn, &mp.xl, x, 3, d, s, bx, true); }
    { cuuint64_t d[2] = {896, 1024}, s[1] = {1792}; cuuint32_t bx[2] = {64, 128}; encode(fn, &mp.x, x, 2, d, s, bx, true); }
    { cuuint64_t d[3] = {448, 448, 3}, s[2] = {2688, 896}; cuuint32_t bx[3] = {64, 32, 3}; encode(fn, &mp.wqkv, wqkv, 3, d, s, bx, true); }
    { cuuint64_t d[3] = {64, 2048, 28}, s[2] = {3584, 128}; cuuint32_t bx[3] = {64, 64, 2}; encode(fn, &mp.w1, w1, 3, d, s, bx, true); }
    { cuuint64_t d[3] = {64, 1792, 32}, s[2] = {4096, 128}; cuuint32_t bx[3] = {64, 64, 2}; encode(fn, &mp.w2, w2, 3, d, s, bx, true); }
    { cuuint64_t d[4] = {64, 28, 4, 128}, s[3] = {128, 3584, BLK}; cuuint32_t bx[4] = {64, 28, 1, 4}; encode(fn, &mp.hst, himg, 4, d, s, bx, false); }
    { cuuint64_t d[2] = {448, 2048}, s[1] = {896}; cuuint32_t bx[2] = {64, 128}; encode(fn, &mp.xn, x, 2, d, s, bx, true); }
    { cuuint64_t d[2] = {64, 8 * 2048}, s[1] = {128}; cuuint32_t bx[2] = {64, 128}; encode(fn, &mp.old_, o, 2, d, s, bx, true); }
    { cuuint64_t d[2] = {128, 8 * 1024}, s[1] = {256}; cuuint32_t bx[2] = {64, 128}; encode(fn, &mp.ost, o, 2, d, s, bx, true); }
    { cuuint64_t d[2] = {448, 2048}, s[1] = {896}; cuuint32_t bx[2] = {64, 64}; encode(fn, &mp.out[0], d_out, 2, d, s, bx, true); }
    { cuuint64_t d[2] = {448, 2048}, s[1] = {896}; cuuint32_t bx[2] = {48, 64}; encode(fn, &mp.out[1], d_out, 2, d, s, bx, true); }
    { cuuint64_t d[3] = {8, 448, 56}, s[2] = {896, 16}; cuuint32_t bx[3] = {8, 64, 14}; encode(fn, &mp.wo, wo, 3, d, s, bx, false); }

    cudaFuncSetAttribute(fused_kernel, cudaFuncAttributeMaxDynamicSharedMemorySize, SMEM_BYTES);
    fused_kernel<<<128, 512, SMEM_BYTES>>>(x, wqkv, b1, b2, scr, (uint8_t*)d_out, mp);
}
```

```cpp
#include <cuda_runtime.h>
#include <cuda.h>
#include <cuda_bf16.h>
#include <stdint.h>

namespace {

constexpr int S_ = 2048, D_ = 448;
constexpr uint32_t BLK = 14336;

constexpr uint32_t G_HIMG = 0;
constexpr uint32_t G_BIMG = G_HIMG + 32 * 4 * BLK;
constexpr uint32_t G_O = G_BIMG + 36 * 4 * BLK;
constexpr uint32_t G_STATS = G_O + 8 * S_ * 128;
constexpr uint32_t G_CS = G_STATS + S_ * 16;
constexpr uint32_t G_HALO = G_CS + 8 * 4 * 2048;
constexpr uint32_t G_CTR = G_HALO + 128 * 3584;
constexpr uint32_t G_END = G_CTR + (192 + 16 * 32) * 4;
__device__ __align__(1024) uint8_t g_scratch[G_END];

constexpr int C_LN = 0, C_WO = 32, C_U = 64, C_O = 192;

#define TSX(sel, id)
#define TS(id)
#define TS0(id)
#define TSH(id)
#define TSW(id)
#define TG(id)

#define TSG1 0
#define TSD(id)
#define QDEPTH 3
#define SPIN
#define ROT 6
#define KS 3
#define QUNROLL 1
#define DLY0 0
#define DLY1 1600
#define DLY2 2000
#define GATHER 3
#define PFW 0
#define NS1 5
#define NS2 3
#define NE 2
#define PRE0 8
#define PRE1 5
#define STG 1
#define NX2 0
#define DU 0
#define DO 100
#define NO1 0
#define XF 0
#define SW 1
#define NARM 2
#define NQ 0
#define GIN 1
constexpr uint32_t OFF_A = 0;
constexpr uint32_t OFF_B = 98304;
constexpr uint32_t OFF_X = 184320;
constexpr uint32_t OFF_K = 196608;
constexpr uint32_t OFF_V = OFF_K + 9 * 896;
constexpr uint32_t OFF_OST = OFF_X, OFF_RECV2 = OFF_X, OFF_RECV1 = OFF_X + 16384, OFF_OUT = OFF_X + 16384;
constexpr uint32_t OFF_CSB = 221184;
constexpr uint32_t OFF_ONES = OFF_CSB + 3072;
constexpr uint32_t OFF_STATS = OFF_ONES + 512;
constexpr uint32_t OFF_BIAS = OFF_STATS + 1024;
constexpr uint32_t OFF_LNX = OFF_BIAS + 1024;
constexpr uint32_t OFF_RSTD = OFF_LNX + 512;
constexpr uint32_t OFF_LNST = 229376;
constexpr uint32_t OFF_EP = OFF_LNST + 128;
constexpr uint32_t OFF_BAR = OFF_EP + 16;
constexpr uint32_t OFF_TS = OFF_BAR + 8 * 48;
constexpr uint32_t SMEM_BYTES = OFF_TS;

enum : int {
    B_FULLQ = 0, B_LNIN = 7, B_EMPTYQ = 8, B_FULL = 15, B_EMPTY = 21, B_AUX = 27, B_QKV = 28, B_HALO = 29, B_FREE = 30,
    B_RECV1 = 31, B_RECV2 = 33, B_UST = 35, B_EP = 37, B_OST = 38, B_LNFREE = 39, B_UDONE = 40, B_NONE = 41, B_GO = 42, B_XR = 46, B_KV = 47, B_COUNT = 48, B_LAND = B_FULLQ
};
constexpr int kQUnroll = QUNROLL;
constexpr uint32_t XSLOT = 0x5432154u;
constexpr uint32_t WSLOT = 0x3421034u;
#define ATT_STEP 10

__device__ __forceinline__ uint32_t smem_u32(const void* p) { return (uint32_t)__cvta_generic_to_shared(p); }
__device__ __forceinline__ void mbar_init(uint32_t a, int c) { asm volatile("mbarrier.init.shared::cta.b64 [%0], %1;" ::"r"(a), "r"(c) : "memory"); }
__device__ __forceinline__ void mbar_expect(uint32_t a, uint32_t b) { asm volatile("mbarrier.arrive.expect_tx.shared::cta.b64 _, [%0], %1;" ::"r"(a), "r"(b) : "memory"); }
__device__ __forceinline__ void mbar_arrive(uint32_t a) { asm volatile("mbarrier.arrive.shared::cta.b64 _, [%0];" ::"r"(a) : "memory"); }
__device__ __forceinline__ void mbar_arrive_if0(uint32_t a, uint32_t sel) {
    asm volatile("{\n.reg .pred p;\nsetp.eq.u32 p, %1, 0;\n@p mbarrier.arrive.shared::cta.b64 _, [%0];\n}" ::"r"(a), "r"(sel) : "memory");
}
__device__ __forceinline__ void mbar_wait(uint32_t a, uint32_t parity) {
    asm volatile("{\n.reg .pred p;\nW0:\nmbarrier.try_wait.parity.shared::cta.b64 p, [%0], %1;\n@!p bra W0;\n}\n" ::"r"(a), "r"(parity) : "memory");
}
__device__ __forceinline__ void mbar_watch(uint32_t a, uint32_t parity) {
    asm volatile(
        "{\n.reg .pred p;\n.reg .u32 n;\nmov.u32 n, 0;\n"
        "W0:\nmbarrier.try_wait.parity.shared::cta.b64 p, [%0], %1;\n@p bra W1;\n"
        "add.u32 n, n, 1;\nsetp.lt.u32 p, n, 4194304;\n@p bra W0;\ntrap;\nW1:\n}\n" ::"r"(a), "r"(parity) : "memory");
}
__device__ __forceinline__ bool elect() {
    uint32_t r;
    asm volatile("{\n.reg .pred p;\nelect.sync _|p, 0xffffffff;\nselp.u32 %0, 1, 0, p;\n}" : "=r"(r));
    return r;
}
__device__ __forceinline__ uint32_t mapa(uint32_t a, uint32_t cta) { uint32_t r; asm("mapa.shared::cluster.u32 %0, %1, %2;" : "=r"(r) : "r"(a), "r"(cta)); return r; }
__device__ __forceinline__ void tma2d(uint32_t dst, const CUtensorMap* m, int c0, int c1, uint32_t bar) {
    asm volatile("cp.async.bulk.tensor.2d.shared::cluster.global.mbarrier::complete_tx::bytes [%0], [%1, {%3, %4}], [%2];" ::"r"(dst), "l"(m), "r"(bar), "r"(c0), "r"(c1) : "memory");
}
__device__ __forceinline__ void tma3d(uint32_t dst, const CUtensorMap* m, int c0, int c1, int c2, uint32_t bar) {
    asm volatile("cp.async.bulk.tensor.3d.shared::cluster.global.mbarrier::complete_tx::bytes [%0], [%1, {%3, %4, %5}], [%2];" ::"r"(dst), "l"(m), "r"(bar), "r"(c0), "r"(c1), "r"(c2) : "memory");
}
__device__ __forceinline__ void tma3d_mc(uint32_t dst, const CUtensorMap* m, int c0, int c1, int c2, uint32_t bar) {
    asm volatile("cp.async.bulk.tensor.3d.shared::cluster.global.mbarrier::complete_tx::bytes.multicast::cluster [%0], [%1, {%3, %4, %5}], [%2], %6;"
                 ::"r"(dst), "l"(m), "r"(bar), "r"(c0), "r"(c1), "r"(c2), "h"((uint16_t)3) : "memory");
}
__device__ __forceinline__ void tma2d_store(const CUtensorMap* m, uint32_t src, int c0, int c1) {
    asm volatile("cp.async.bulk.tensor.2d.global.shared::cta.bulk_group [%0, {%2, %3}], [%1];" ::"l"(m), "r"(src), "r"(c0), "r"(c1) : "memory");
}
__device__ __forceinline__ void tma4d_store(const CUtensorMap* m, uint32_t src, int c0, int c1, int c2, int c3) {
    asm volatile("cp.async.bulk.tensor.4d.global.shared::cta.bulk_group [%0, {%2, %3, %4, %5}], [%1];" ::"l"(m), "r"(src), "r"(c0), "r"(c1), "r"(c2), "r"(c3) : "memory");
}
__device__ __forceinline__ void tma4d(uint32_t dst, const CUtensorMap* m, int c0, int c1, int c2, int c3, uint32_t bar) {
    asm volatile("cp.async.bulk.tensor.4d.shared::cluster.global.mbarrier::complete_tx::bytes [%0], [%1, {%3, %4, %5, %6}], [%2];" ::"r"(dst), "l"(m), "r"(bar), "r"(c0), "r"(c1), "r"(c2), "r"(c3) : "memory");
}
__device__ __forceinline__ void bulk_load(uint32_t dst, const void* src, uint32_t bytes, uint32_t bar) {
    asm volatile("cp.async.bulk.shared::cluster.global.mbarrier::complete_tx::bytes [%0], [%1], %2, [%3];" ::"r"(dst), "l"(src), "r"(bytes), "r"(bar) : "memory");
}
__device__ __forceinline__ void bulk_store(void* dst, uint32_t src, uint32_t bytes) {
    asm volatile("cp.async.bulk.global.shared::cta.bulk_group [%0], [%1], %2;" ::"l"(dst), "r"(src), "r"(bytes) : "memory");
}
__device__ __forceinline__ void bulk_commit() { asm volatile("cp.async.bulk.commit_group;" ::: "memory"); }
__device__ __forceinline__ void bulk_wait_all() { asm volatile("cp.async.bulk.wait_group 0;" ::: "memory"); }
__device__ __forceinline__ void bulk_wait_read() { asm volatile("cp.async.bulk.wait_group.read 0;" ::: "memory"); }
__device__ __forceinline__ void l2_prefetch(const void* p) { asm volatile("prefetch.global.L2 [%0];" ::"l"(p)); }
__device__ __forceinline__ void fence_async_smem() { asm volatile("fence.proxy.async.shared::cta;" ::: "memory"); }
__device__ __forceinline__ void fence_async_global() { asm volatile("fence.proxy.async.global;" ::: "memory"); }
__device__ __forceinline__ void red_relaxed(unsigned* p, unsigned v) { asm volatile("red.relaxed.gpu.global.add.u32 [%0], %1;" ::"l"(p), "r"(v) : "memory"); }
__device__ __forceinline__ void publish(unsigned* p) {
    asm volatile("fence.proxy.async.global;\nred.release.gpu.global.add.u32 [%0], 1;" ::"l"(p) : "memory");
}
__device__ __forceinline__ void stg32(void* p, uint32_t v) { asm volatile("st.global.b32 [%0], %1;" ::"l"(p), "r"(v) : "memory"); }
__device__ __forceinline__ unsigned ld_relaxed(const unsigned* p) { unsigned v; asm volatile("ld.relaxed.gpu.global.u32 %0, [%1];" : "=r"(v) : "l"(p) : "memory"); return v; }
__device__ __forceinline__ bool ctr_done(unsigned v, unsigned target) { return ((v - target) & 0x1FFFFFFu) == 0; }
__device__ __forceinline__ uint32_t clock32() { uint32_t c; asm volatile("mov.u32 %0, %%clock;" : "=r"(c)::"memory"); return c; }
__device__ __forceinline__ void delay(uint32_t n) { const uint32_t t0 = clock32(); while (clock32() - t0 < n) {} }
__device__ __forceinline__ void poll(const unsigned* p, unsigned target) { while (!ctr_done(ld_relaxed(p), target)) {} }
__device__ __forceinline__ void cell_put(void* p, uint32_t a, uint32_t b, uint32_t tag) {
    asm volatile("st.relaxed.gpu.global.v4.b32 [%0], {%1, %3, %2, %3};" ::"l"(p), "r"(a), "r"(b), "r"(tag) : "memory");
}
__device__ __forceinline__ uint32_t cell_get(const void* p, uint32_t& a, uint32_t& b, uint32_t tag) {
    uint32_t t0, t1;
    asm volatile("ld.relaxed.gpu.global.v4.b32 {%0, %1, %2, %3}, [%4];" : "=r"(a), "=r"(t0), "=r"(b), "=r"(t1) : "l"(p) : "memory");
    return (t0 ^ tag) | (t1 ^ tag);
}
template <int ID, int N> __device__ __forceinline__ void bar_sync() { asm volatile("bar.sync %0, %1;" ::"n"(ID), "n"(N) : "memory"); }
__device__ __forceinline__ void bar_sync_id(int id, int n) { asm volatile("bar.sync %0, %1;" ::"r"(id), "r"(n) : "memory"); }
template <int ID = 4> __device__ __forceinline__ void gate_wait(uint32_t on) { asm volatile("{\n.reg .pred p;\nsetp.ne.u32 p, %0, 0;\n@p bar.sync %1, 256;\n}" ::"r"(on), "n"(ID) : "memory"); }
template <int ID = 4> __device__ __forceinline__ void gate_open(uint32_t off) { asm volatile("{\n.reg .pred p;\nsetp.eq.u32 p, %0, 0;\n@p bar.arrive %1, 256;\n}" ::"r"(off), "n"(ID) : "memory"); }
__device__ __forceinline__ void wg_fence() { asm volatile("wgmma.fence.sync.aligned;" ::: "memory"); }
__device__ __forceinline__ void wg_commit() { asm volatile("wgmma.commit_group.sync.aligned;" ::: "memory"); }
template <int N> __device__ __forceinline__ void wg_wait() { asm volatile("wgmma.wait_group.sync.aligned %0;" ::"n"(N) : "memory"); }
template <int LO = 0, int HI = 56, int N> __device__ __forceinline__ void pin(float (&a)[N]) {
#pragma unroll
    for (int i = LO; i < (HI < N ? HI : N); i++) asm volatile("" : "+f"(a[i])::"memory");
}
__device__ __forceinline__ uint32_t ldg_u16(const void* p) {
    uint32_t v;
    asm volatile("ld.global.nc.u16 %0, [%1];" : "=r"(v) : "l"(p) : "memory");
    return v;
}
__device__ __forceinline__ uint32_t pack2(float lo, float hi) { uint32_t r; asm("cvt.rn.bf16x2.f32 %0, %1, %2;" : "=r"(r) : "f"(hi), "f"(lo)); return r; }
__device__ __forceinline__ float bf_lo(uint32_t v) { return __uint_as_float(v << 16); }
__device__ __forceinline__ float bf_hi(uint32_t v) { return __uint_as_float(v & 0xFFFF0000u); }
__device__ __forceinline__ uint32_t split2(float x) { return pack2(x, x - bf_lo(pack2(x, 0.f))); }
__device__ __forceinline__ void stsm4(uint32_t a, uint32_t r0, uint32_t r1, uint32_t r2, uint32_t r3) {
    asm volatile("stmatrix.sync.aligned.m8n8.x4.shared.b16 [%0], {%1, %2, %3, %4};" ::"r"(a), "r"(r0), "r"(r1), "r"(r2), "r"(r3) : "memory");
}
__device__ __forceinline__ void stsm2(uint32_t a, uint32_t r0, uint32_t r1) {
    asm volatile("stmatrix.sync.aligned.m8n8.x2.shared.b16 [%0], {%1, %2};" ::"r"(a), "r"(r0), "r"(r1) : "memory");
}
__device__ __forceinline__ void ldsm4(uint32_t a, uint32_t (&r)[4]) {
    asm volatile("ldmatrix.sync.aligned.m8n8.x4.shared.b16 {%0, %1, %2, %3}, [%4];" : "=r"(r[0]), "=r"(r[1]), "=r"(r[2]), "=r"(r[3]) : "r"(a) : "memory");
}
__device__ __forceinline__ void ldsm4t(uint32_t a, uint32_t (&r)[4]) {
    asm volatile("ldmatrix.sync.aligned.m8n8.x4.trans.shared.b16 {%0, %1, %2, %3}, [%4];" : "=r"(r[0]), "=r"(r[1]), "=r"(r[2]), "=r"(r[3]) : "r"(a) : "memory");
}
__device__ __forceinline__ void mma16816(float (&c)[4], uint32_t a0, uint32_t a1, uint32_t a2, uint32_t a3, uint32_t b0, uint32_t b1) {
    asm volatile("mma.sync.aligned.m16n8k16.row.col.f32.bf16.bf16.f32 {%0,%1,%2,%3}, {%4,%5,%6,%7}, {%8,%9}, {%0,%1,%2,%3};"
                 : "+f"(c[0]), "+f"(c[1]), "+f"(c[2]), "+f"(c[3]) : "r"(a0), "r"(a1), "r"(a2), "r"(a3), "r"(b0), "r"(b1));
}
__device__ __forceinline__ void mma1688(float (&c)[4], uint32_t a0, uint32_t a1, uint32_t b0) {
    asm volatile("mma.sync.aligned.m16n8k8.row.col.f32.bf16.bf16.f32 {%0,%1,%2,%3}, {%4,%5}, {%6}, {%0,%1,%2,%3};"
                 : "+f"(c[0]), "+f"(c[1]), "+f"(c[2]), "+f"(c[3]) : "r"(a0), "r"(a1), "r"(b0));
}
constexpr uint32_t SB0 = 1024;
__device__ __forceinline__ uint32_t desc_lo(uint32_t off, uint32_t lbo) { return ((SB0 + off) >> 4) + ((lbo >> 4) << 16); }
constexpr uint32_t H_SW = (1024 >> 4) | (1u << 30), H_H = 128 >> 4, H_U = 1024 >> 4;
__device__ __forceinline__ float ex2(float x) { float r; asm("ex2.approx.ftz.f32 %0, %1;" : "=f"(r) : "f"(x)); return r; }
__device__ __forceinline__ float rsq(float x) { float r; asm("rsqrt.approx.ftz.f32 %0, %1;" : "=f"(r) : "f"(x)); return r; }
__device__ __forceinline__ float rcp(float x) { float r; asm("rcp.approx.ftz.f32 %0, %1;" : "=f"(r) : "f"(x)); return r; }
__device__ __forceinline__ float gelu_half(float h) {
    float y = h * fmaf(h * h, 8.f * 0.0356774081363f, 2.f * 0.7978845608029f), t;
    asm("tanh.approx.f32 %0, %1;" : "=f"(t) : "f"(y));
    return fmaf(h, t, h);
}

template <uint32_t HB, int TB>
__device__ __forceinline__ void wgmma_n56_rs(float (&d)[28], const uint32_t (&a)[4], uint32_t lb, int scale_d) {
    asm volatile("{\n.reg .pred p;\n.reg .b64 db;\nsetp.ne.b32 p, %33, 0;\nmov.b64 db, {%32, %34};\n"
        "wgmma.mma_async.sync.aligned.m64n56k16.f32.bf16.bf16 "
        "{%0, %1, %2, %3, %4, %5, %6, %7, %8, %9, %10, %11, %12, %13, %14, %15, %16, %17, %18, %19, %20, %21, %22, %23, %24, %25, %26, %27}, "
        "{%28, %29, %30, %31}, db, p, 1, 1, %35;\n}\n"
        : "+f"(d[0]), "+f"(d[1]), "+f"(d[2]), "+f"(d[3]), "+f"(d[4]), "+f"(d[5]), "+f"(d[6]), "+f"(d[7]), "+f"(d[8]), "+f"(d[9]), "+f"(d[10]), "+f"(d[11]), "+f"(d[12]), "+f"(d[13]), "+f"(d[14]), "+f"(d[15]), "+f"(d[16]), "+f"(d[17]), "+f"(d[18]), "+f"(d[19]), "+f"(d[20]), "+f"(d[21]), "+f"(d[22]), "+f"(d[23]), "+f"(d[24]), "+f"(d[25]), "+f"(d[26]), "+f"(d[27])
        : "r"(a[0]), "r"(a[1]), "r"(a[2]), "r"(a[3]), "r"(lb), "r"(scale_d), "n"(HB), "n"(TB));
}
template <int TA, uint32_t HA, uint32_t HB>
__device__ __forceinline__ void wgmma_n112(float (&d)[56], uint32_t la, uint32_t lb, int scale_d = 1) {
    asm volatile("{\n.reg .b64 da, db;\n.reg .pred p;\nsetp.ne.b32 p, %61, 0;\nmov.b64 da, {%56, %59};\nmov.b64 db, {%57, %60};\n"
        "wgmma.mma_async.sync.aligned.m64n112k16.f32.bf16.bf16 "
        "{%0, %1, %2, %3, %4, %5, %6, %7, %8, %9, %10, %11, %12, %13, %14, %15, %16, %17, %18, %19, %20, %21, %22, %23, %24, %25, %26, %27, %28, %29, %30, %31, %32, %33, %34, %35, %36, %37, %38, %39, %40, %41, %42, %43, %44, %45, %46, %47, %48, %49, %50, %51, %52, %53, %54, %55}, "
        "da, db, p, 1, 1, %58, 1;\n}\n"
        : "+f"(d[0]), "+f"(d[1]), "+f"(d[2]), "+f"(d[3]), "+f"(d[4]), "+f"(d[5]), "+f"(d[6]), "+f"(d[7]), "+f"(d[8]), "+f"(d[9]), "+f"(d[10]), "+f"(d[11]), "+f"(d[12]), "+f"(d[13]), "+f"(d[14]), "+f"(d[15]), "+f"(d[16]), "+f"(d[17]), "+f"(d[18]), "+f"(d[19]), "+f"(d[20]), "+f"(d[21]), "+f"(d[22]), "+f"(d[23]), "+f"(d[24]), "+f"(d[25]), "+f"(d[26]), "+f"(d[27]), "+f"(d[28]), "+f"(d[29]), "+f"(d[30]), "+f"(d[31]), "+f"(d[32]), "+f"(d[33]), "+f"(d[34]), "+f"(d[35]), "+f"(d[36]), "+f"(d[37]), "+f"(d[38]), "+f"(d[39]), "+f"(d[40]), "+f"(d[41]), "+f"(d[42]), "+f"(d[43]), "+f"(d[44]), "+f"(d[45]), "+f"(d[46]), "+f"(d[47]), "+f"(d[48]), "+f"(d[49]), "+f"(d[50]), "+f"(d[51]), "+f"(d[52]), "+f"(d[53]), "+f"(d[54]), "+f"(d[55])
        : "r"(la), "r"(lb), "n"(TA), "n"(HA), "n"(HB), "r"(scale_d));
}
template <int TA, uint32_t HA, uint32_t HB>
__device__ __forceinline__ void wgmma_n64(float (&d)[32], uint32_t la, uint32_t lb, int scale_d = 1) {
    asm volatile("{\n.reg .b64 da, db;\n.reg .pred p;\nsetp.ne.b32 p, %37, 0;\nmov.b64 da, {%32, %35};\nmov.b64 db, {%33, %36};\n"
        "wgmma.mma_async.sync.aligned.m64n64k16.f32.bf16.bf16 "
        "{%0, %1, %2, %3, %4, %5, %6, %7, %8, %9, %10, %11, %12, %13, %14, %15, %16, %17, %18, %19, %20, %21, %22, %23, %24, %25, %26, %27, %28, %29, %30, %31}, "
        "da, db, p, 1, 1, %34, 1;\n}\n"
        : "+f"(d[0]), "+f"(d[1]), "+f"(d[2]), "+f"(d[3]), "+f"(d[4]), "+f"(d[5]), "+f"(d[6]), "+f"(d[7]), "+f"(d[8]), "+f"(d[9]), "+f"(d[10]), "+f"(d[11]), "+f"(d[12]), "+f"(d[13]), "+f"(d[14]), "+f"(d[15]), "+f"(d[16]), "+f"(d[17]), "+f"(d[18]), "+f"(d[19]), "+f"(d[20]), "+f"(d[21]), "+f"(d[22]), "+f"(d[23]), "+f"(d[24]), "+f"(d[25]), "+f"(d[26]), "+f"(d[27]), "+f"(d[28]), "+f"(d[29]), "+f"(d[30]), "+f"(d[31])
        : "r"(la), "r"(lb), "n"(TA), "n"(HA), "n"(HB), "r"(scale_d));
}
template <int TA, uint32_t HA, uint32_t HB>
__device__ __forceinline__ void wgmma_n56(float (&d)[28], uint32_t la, uint32_t lb, int scale_d = 1) {
    asm volatile("{\n.reg .b64 da, db;\n.reg .pred p;\nsetp.ne.b32 p, %33, 0;\nmov.b64 da, {%28, %31};\nmov.b64 db, {%29, %32};\n"
        "wgmma.mma_async.sync.aligned.m64n56k16.f32.bf16.bf16 "
        "{%0, %1, %2, %3, %4, %5, %6, %7, %8, %9, %10, %11, %12, %13, %14, %15, %16, %17, %18, %19, %20, %21, %22, %23, %24, %25, %26, %27}, "
        "da, db, p, 1, 1, %30, 1;\n}\n"
        : "+f"(d[0]), "+f"(d[1]), "+f"(d[2]), "+f"(d[3]), "+f"(d[4]), "+f"(d[5]), "+f"(d[6]), "+f"(d[7]), "+f"(d[8]), "+f"(d[9]), "+f"(d[10]), "+f"(d[11]), "+f"(d[12]), "+f"(d[13]), "+f"(d[14]), "+f"(d[15]), "+f"(d[16]), "+f"(d[17]), "+f"(d[18]), "+f"(d[19]), "+f"(d[20]), "+f"(d[21]), "+f"(d[22]), "+f"(d[23]), "+f"(d[24]), "+f"(d[25]), "+f"(d[26]), "+f"(d[27])
        : "r"(la), "r"(lb), "n"(TA), "n"(HA), "n"(HB), "r"(scale_d));
}
template <int TA, uint32_t HA, uint32_t HB>
__device__ __forceinline__ void wgmma_n48(float (&d)[24], uint32_t la, uint32_t lb, int scale_d = 1) {
    asm volatile("{\n.reg .b64 da, db;\n.reg .pred p;\nsetp.ne.b32 p, %29, 0;\nmov.b64 da, {%24, %27};\nmov.b64 db, {%25, %28};\n"
        "wgmma.mma_async.sync.aligned.m64n48k16.f32.bf16.bf16 "
        "{%0, %1, %2, %3, %4, %5, %6, %7, %8, %9, %10, %11, %12, %13, %14, %15, %16, %17, %18, %19, %20, %21, %22, %23}, "
        "da, db, p, 1, 1, %26, 1;\n}\n"
        : "+f"(d[0]), "+f"(d[1]), "+f"(d[2]), "+f"(d[3]), "+f"(d[4]), "+f"(d[5]), "+f"(d[6]), "+f"(d[7]), "+f"(d[8]), "+f"(d[9]), "+f"(d[10]), "+f"(d[11]), "+f"(d[12]), "+f"(d[13]), "+f"(d[14]), "+f"(d[15]), "+f"(d[16]), "+f"(d[17]), "+f"(d[18]), "+f"(d[19]), "+f"(d[20]), "+f"(d[21]), "+f"(d[22]), "+f"(d[23])
        : "r"(la), "r"(lb), "n"(TA), "n"(HA), "n"(HB), "r"(scale_d));
}
template <int TA, uint32_t HA, uint32_t HB>
__device__ __forceinline__ void wgmma_n8(float (&d)[4], uint32_t la, uint32_t lb, int scale_d = 1) {
    asm volatile("{\n.reg .b64 da, db;\n.reg .pred p;\nsetp.ne.b32 p, %9, 0;\nmov.b64 da, {%4, %7};\nmov.b64 db, {%5, %8};\n"
        "wgmma.mma_async.sync.aligned.m64n8k16.f32.bf16.bf16 "
        "{%0, %1, %2, %3}, "
        "da, db, p, 1, 1, %6, 1;\n}\n"
        : "+f"(d[0]), "+f"(d[1]), "+f"(d[2]), "+f"(d[3])
        : "r"(la), "r"(lb), "n"(TA), "n"(HA), "n"(HB), "r"(scale_d));
}

__device__ __forceinline__ void send8(const float* a, uint32_t rbuf, uint32_t rbar, uint32_t on) {
    asm volatile("{\n.reg .pred p;\nsetp.ne.u32 p, %6, 0;\n@p st.async.weak.shared::cluster.mbarrier::complete_tx::bytes.v4.b32 [%0], {%1,%2,%3,%4}, [%5];\n}"
                 ::"r"(rbuf), "r"(pack2(a[0], a[1])), "r"(pack2(a[2], a[3])), "r"(pack2(a[4], a[5])), "r"(pack2(a[6], a[7])), "r"(rbar), "r"(on) : "memory");
}
__device__ __forceinline__ void send_half(const float (&a)[56], uint32_t rbuf, uint32_t rbar, int t, uint32_t on) {
#pragma unroll
    for (int i = 0; i < 3; i++) send8(a + 28 + 8 * i, rbuf + i * 2048 + t * 16, rbar, on);
    asm volatile("{\n.reg .pred p;\nsetp.ne.u32 p, %4, 0;\n@p st.async.weak.shared::cluster.mbarrier::complete_tx::bytes.v2.b32 [%0], {%1,%2}, [%3];\n}"
                 ::"r"(rbuf + 6144 + t * 8), "r"(pack2(a[52], a[53])), "r"(pack2(a[54], a[55])), "r"(rbar), "r"(on) : "memory");
}
__device__ __forceinline__ void recv_half(uint32_t (&p)[14], uint32_t buf, int t) {
#pragma unroll
    for (int i = 0; i < 3; i++)
        asm volatile("ld.shared.v4.b32 {%0,%1,%2,%3}, [%4];" : "=r"(p[4 * i]), "=r"(p[4 * i + 1]), "=r"(p[4 * i + 2]), "=r"(p[4 * i + 3]) : "r"(buf + i * 2048 + t * 16) : "memory");
    asm volatile("ld.shared.v2.b32 {%0,%1}, [%2];" : "=r"(p[12]), "=r"(p[13]) : "r"(buf + 6144 + t * 8) : "memory");
}

struct Maps { CUtensorMap xl, x, wqkv, hst, w1, w2, xn, old_, ost, wo; };

__global__ void __cluster_dims__(2, 1, 1) __launch_bounds__(512, 1)
fused_kernel(const __nv_bfloat16* __restrict__ x, const __nv_bfloat16* __restrict__ wqkv,
             const __nv_bfloat16* __restrict__ b1, const __nv_bfloat16* __restrict__ b2, uint8_t* __restrict__ scr,
             uint8_t* __restrict__ out, const __grid_constant__ Maps mp) {
    extern __shared__ __align__(1024) uint8_t smem[];
    const uint32_t sb = smem_u32(smem);
    const uint32_t bar = sb + OFF_BAR;
    const int tid = threadIdx.x, lane = tid & 31;
    const int b = blockIdx.x, z = b & 1, c = b >> 1;
    unsigned* const ctr = reinterpret_cast<unsigned*>(scr + G_CTR);
    if (tid < 112) l2_prefetch(reinterpret_cast<const uint8_t*>(x) + (b * 112 + tid) * 128);
    const int wline = (tid & 127) * 128 + b;
    const bool wfirst = ((wline / 1344) & ~ROT) == 0;
    if (PFW && (tid >> 7) == 1 && wline < 9408 && wfirst) l2_prefetch(reinterpret_cast<const uint8_t*>(wqkv) + wline * 128);
    const uint32_t t_in = clock32();
    TS0(0);
    TG(60);
    const int warp = __shfl_sync(0xffffffffu, tid >> 5, 0);
    int q, j;
    if (c < 4) { q = 15; j = c; } else if (c < 36) { q = (c - 4) & 7; j = (c - 4) >> 3; } else { q = 8 + (c - 36) % 7; j = (c - 36) / 7; }
    const bool g1 = q < 14;
    const int R = q < 8 ? q : q == 15 ? 2 : q < 10 ? q - 8 : q - 7, P = (q >> 3) * 4 + j;
    auto krow = [&](int kb) { const int k = kb + (R & ROT); return (k >= 7 ? k - 7 : k) * 64; };
    auto x_load = [&](int kb) {
        mbar_expect(bar + 8 * (B_FULLQ + kb), 40960);
        tma2d(sb + OFF_A + ((XSLOT >> (4 * kb)) & 7) * 16384, &mp.x, z * D_ + krow(kb), R * 128, bar + 8 * (B_FULLQ + kb));
    };
    if (warp == 12 && elect()) {
#pragma unroll
        for (int i = B_FULLQ; i < B_EMPTYQ; i++) mbar_init(bar + 8 * i, 1);
        mbar_expect(bar + 8 * B_LNIN, BLK);
        tma3d(sb + OFF_A, &mp.xl, 0, 16 * b, 0, bar + 8 * B_LNIN);
        x_load(0);
        TS(15);
    }
    if (warp == 13 && elect()) {
#pragma unroll
        for (int i = B_EMPTYQ; i < B_COUNT; i++)
            mbar_init(bar + 8 * i, i < B_FULL ? (i < B_EMPTYQ + 2 ? 16 : 8) + (((i - B_EMPTYQ) & ~1) == (R & 6 & ~ROT) ? 8 : 0)
                                   : i < B_EMPTY || i == B_FREE ? 2 : (i < B_AUX || i == B_NONE || i == B_OST) ? 8 : i == B_KV ? 12
                                   : (i == B_AUX || i == B_HALO) ? 4 : 1);
#pragma unroll
        for (int i = B_RECV1; i < B_UST; i++) mbar_expect(bar + 8 * i, i < B_RECV2 ? 7168 : 8192 - 2048 * z);
    }
    asm volatile("fence.mbarrier_init.release.cluster;" ::: "memory");
    __syncwarp();
    asm volatile("barrier.cluster.arrive.relaxed.aligned;\nbarrier.cluster.wait.aligned;" ::: "memory");
    auto slot = [](uint32_t r) { return r - 6 * ((r * 43) >> 8); };
    auto phase = [](uint32_t r) { return ((r * 43) >> 8) & 1; };
    const uint32_t r_o = g1 ? 16 : 0, r_u = r_o + 4;
    auto fetch_x = [&](uint32_t r, bool arm = true) {
        const uint32_t s = slot(r), lb = bar + 8 * (B_LAND + s), i = r - r_o;
        if (arm) mbar_expect(lb, i < 4 ? 16384 : BLK);
        if (i < 4) tma2d(sb + OFF_A + s * 16384, &mp.old_, 0, (4 * z + i) * S_ + q * 128, lb);
        else bulk_load(sb + OFF_B + s * BLK, scr + G_BIMG + ((14 * z + (i < 11 ? 2 * i : 2 * i - 13)) * 4 + j) * BLK, BLK, lb);
    };
    auto epoch = [&]() { mbar_wait(bar + 8 * B_EP, 0); return *reinterpret_cast<volatile unsigned*>(smem + OFF_EP); };

    if (warp < 8) {
        const int wg = warp >> 2, w4 = warp & 3, t = tid & 127, g = lane >> 2, tq = lane & 3;
        asm volatile("setmaxnreg.inc.sync.aligned.u32 208;");
        uint32_t xa[4];
#pragma unroll
        for (int k = 0; k < 4; k++) xa[k] = sb + OFF_A + (warp * 16 + (lane & 15)) * 128 + (((2 * k + (lane >> 4)) ^ (lane & 7)) << 4);
        {
            const int rg = warp & 1, jq = warp >> 1;
            const uint32_t ex = sb + OFF_LNX + (rg * 8 + g) * 32, ew = ex + jq * 8, ls = sb + OFF_LNST + (rg * 8 + g) * 8;
            uint32_t r[4][4], la[4], ha[4], dep = ex | ew | ls;
#pragma unroll
            for (int i = 0; i < 4; i++) {
                const int cg = 14 * jq + 4 * i + ((lane >> 3) & (i < 3 ? 3 : 1));
                la[i] = sb + OFF_A + (cg >> 3) * 2048 + rg * 1024 + (lane & 7) * 128 + (((cg ^ lane) & 7) << 4);
                int pos = 4 * i + (lane >> 3) + (b >= 64 ? 7 : 0);
                if (pos >= 14) pos -= 14;
                ha[i] = sb + OFF_A + jq * 3584 + rg * 1792 + (lane & 7) * 16 + pos * 128;
                dep |= la[i] | xa[i] | ha[i];
            }
            mbar_wait(bar + 8 * B_LNIN, dep >> 31);
            TS0(16);
#pragma unroll
            for (int i = 0; i < 4; i++) ldsm4(la[i], r[i]);
            float rs[4] = {0.f, 0.f, 0.f, 0.f}, rt[4] = {0.f, 0.f, 0.f, 0.f}, sq[4], v[28];
            const float sh = bf_lo(__shfl_sync(0xffffffffu, r[0][0], lane & 28));
            mma16816(rs, r[0][0], r[0][1], r[0][2], r[0][3], 0x3F803F80u, 0x3F803F80u);
            mma16816(rt, r[1][0], r[1][1], r[1][2], r[1][3], 0x3F803F80u, 0x3F803F80u);
            mma16816(rs, r[2][0], r[2][1], r[2][2], r[2][3], 0x3F803F80u, 0x3F803F80u);
            mma1688(rt, r[3][0], r[3][1], 0x3F803F80u);
#pragma unroll
            for (int n = 0; n < 14; n++) { v[2 * n] = bf_lo(r[n >> 2][n & 3]) - sh; v[2 * n + 1] = bf_hi(r[n >> 2][n & 3]) - sh; }
#pragma unroll
            for (int n = 0; n < 28; n++) sq[n & 3] = n < 4 ? v[n] * v[n] : fmaf(v[n], v[n], sq[n & 3]);
            const float mq = ((rs[0] + rs[2]) + (rt[0] + rt[2])) * (1.f / 112), dq = mq - sh;
            float m2 = fmaf(-28.f * dq, dq, (sq[0] + sq[1]) + (sq[2] + sq[3]));
            m2 += __shfl_xor_sync(0xffffffffu, m2, 1);
            m2 += __shfl_xor_sync(0xffffffffu, m2, 2);
            asm volatile("st.shared.v2.f32 [%0], {%1, %2};" ::"r"(ew), "f"(mq), "f"(m2) : "memory");
            bar_sync<1, 256>();
            float4 e0, e1;
            asm volatile("ld.shared.v4.f32 {%0,%1,%2,%3}, [%4];" : "=f"(e0.x), "=f"(e0.y), "=f"(e0.z), "=f"(e0.w) : "r"(ex) : "memory");
            asm volatile("ld.shared.v4.f32 {%0,%1,%2,%3}, [%4];" : "=f"(e1.x), "=f"(e1.y), "=f"(e1.z), "=f"(e1.w) : "r"(ex + 16) : "memory");
            const float mean = 0.25f * ((e0.x + e0.z) + (e1.x + e1.z));
            const float d0 = e0.x - mean, d1 = e0.z - mean, d2 = e1.x - mean, d3 = e1.z - mean;
            const float var = fmaxf(((e0.y + e0.w) + (e1.y + e1.w)) * (1.f / D_) + 0.25f * (fmaf(d0, d0, d1 * d1) + fmaf(d2, d2, d3 * d3)), 0.f);
            const float r1 = rsq(var + 1e-5f), sc = rsq(fmaf(1e-5f, var + 1e-5f, var)), of = (sh - mean) * sc;
#pragma unroll
            for (int n = 0; n < 14; n++) r[n >> 2][n & 3] = pack2(fmaf(v[2 * n], sc, of), fmaf(v[2 * n + 1], sc, of));
#pragma unroll
            for (int i = 0; i < 3; i++) stsm4(ha[i], r[i][0], r[i][1], r[i][2], r[i][3]);
            stsm2(ha[3], r[3][0], r[3][1]);
            asm volatile("st.shared.v2.b32 [%0], {%1, %2};" ::"r"(ls), "r"(__float_as_uint(r1)), "r"(split2(-mean)) : "memory");
            TS0(24);
            asm volatile("bar.arrive 10, 288;" ::: "memory");
        }
        float a1[56];
        float rq[2], hb1[2], fb2[2];
        uint32_t qp[14], kp[14];
        const uint32_t ka = sb + OFF_K + warp * 896 + (lane & 7) * 112 + (lane >> 3) * 16;
        const uint32_t va = sb + OFF_V + (warp * 16 + (lane & 15)) * 112 + (lane >> 4) * 16;
        const uint32_t sta = sb + OFF_RSTD + warp * 64 + tq * 8;
        const uint32_t dA = desc_lo(OFF_A + wg * 8192, 16), dH = desc_lo(OFF_B, 1792), dU = desc_lo(OFF_B, 128);
        auto release = [&](uint32_t a) { mbar_arrive_if0(a, lane); };
        auto sched_fence = [&]() { mbar_wait(bar + 8 * B_LNIN, 0); };
        uint32_t rel = bar + 8 * (B_EMPTYQ + 6);
        auto g1_run = [&](uint32_t r0, uint32_t r1, int gate = 0) {
#pragma unroll 1
            for (uint32_t r = g1 ? r0 : r1; r < r1; r++) {
                const uint32_t s = slot(r), n = min(r + 1, 15u);
                if (gate == 4) gate_wait(wg && r == r0);
                if (TSG1) TSD(64 + r);
                wg_fence();
#pragma unroll
                for (int k = 0; k < 4; k++) wgmma_n112<1, H_SW, H_H>(a1, dA + s * 1024 + k * 128, dH + s * 896 + k * 224, k ? 1 : r);
                wg_commit();
                wg_wait<1>();
                release(rel);
                rel = bar + 8 * (B_EMPTY + s);
                mbar_wait(bar + 8 * (B_FULL + slot(n)), phase(n));
            }
        };
        uint32_t solo = g1 && wg == SW;
        asm volatile("" : "+r"(solo));
        solo = __shfl_sync(0xffffffffu, solo, 0);
        auto g1_wait = [&](uint32_t r) { mbar_wait(bar + 8 * (g1 ? B_FULL + r % 6 : B_LNIN), g1 && ((r / 6) & 1)); };
        auto g1_one = [&](uint32_t r) {
#pragma unroll 1
            for (uint32_t n = 0; n < solo; n++) {
                if (TSG1) TSD(64 + r);
                wg_fence();
#pragma unroll
                for (int k = 0; k < 4; k++) wgmma_n112<1, H_SW, H_H>(a1, dA + r % 6 * 1024 + k * 128, dH + r % 6 * 896 + k * 224);
                wg_commit();
                wg_wait<1>();
                release(rel);
                rel = bar + 8 * (B_EMPTY + r % 6);
            }
        };
        auto drain = [&]() { wg_wait<0>(); release(rel); rel = bar + 8 * B_NONE; };
        {
            float aq0[28], aq1[28], aq2[28];
            const uint32_t dW = desc_lo(OFF_B + (P & 1) * 16, 16);
            uint32_t xf[2][4][4];
            const uint32_t rb = mapa(bar + 8 * (B_EMPTYQ - 1), z ^ 1);
            auto fetch = [&](int kb, uint32_t (&f)[4][4]) {
                if (TSG1) TSD(178 + kb);
                mbar_wait(bar + 8 * (B_FULLQ + kb), 0);
                if (TSG1) TSD(170 + kb);
#pragma unroll
                for (int k = 0; k < 4; k++) ldsm4(xa[k] + ((XSLOT >> (4 * kb)) & 7) * 16384, f[k]);
            };
            auto mma = [&](int kb, uint32_t (&f)[4][4], int k0, int k1) {
                const uint32_t d0 = dW + ((WSLOT >> (4 * kb)) & 7) * 1536;
                wg_fence();
#pragma unroll
                for (int k = k0; k < k1; k++) {
                    const uint32_t d = d0 + (k >> 1) * 768 + (k & 1) * 128;
                    const int sc = k > 0 ? 1 : kb;
                    wgmma_n56_rs<H_SW, 1>(aq0, f[k], d, sc);
                    wgmma_n56_rs<H_SW, 1>(aq1, f[k], d + 256, sc);
                    wgmma_n56_rs<H_SW, 1>(aq2, f[k], d + 512, sc);
                }
            };
            auto retire = [&](int kb) {
                wg_commit();
                wg_wait<1>();
                mbar_arrive_if0(bar + 8 * (B_EMPTYQ + kb - 1), lane | (kb < 1));
                asm volatile("{\n.reg .pred p;\nsetp.eq.u32 p, %1, 0;\n@p mbarrier.arrive.shared::cluster.b64 _, [%0];\n}"
                             ::"r"(rb + 8 * kb), "r"(lane | ((uint32_t)(kb - 1) > 1)) : "memory");
            };
            auto stage = [&](int kb, uint32_t (&f)[4][4], uint32_t (&n)[4][4]) {
                mma(kb, f, 0, KS);
                retire(kb);
                fetch(kb + 1, n);
                if (KS < 4) { mma(kb, f, KS, 4); wg_commit(); }
            };
            fetch(0, xf[0]);
#pragma unroll kQUnroll
            for (int kb = 0; kb < 6; kb += 2) {
                stage(kb, xf[0], xf[1]);
                stage(kb + 1, xf[1], xf[0]);
            }
            mma(6, xf[0], 0, KS);
            retire(6);
            TS0(2);
            mbar_wait(bar + 8 * B_AUX, 0);
            {
                uint32_t (&f)[4] = xf[1][0];
                const uint2* mt = reinterpret_cast<const uint2*>(smem + OFF_STATS) + warp * 16 + g;
                const uint2 m0 = mt[0], m1 = mt[8];
                const uint32_t sel = tq == 0 ? 0x1010 : tq == 1 ? 0x3232 : 0x4444;
                f[0] = __byte_perm(m0.y, 0, sel); f[1] = __byte_perm(m1.y, 0, sel); f[2] = f[3] = 0;
                rq[0] = __uint_as_float(m0.x); rq[1] = __uint_as_float(m1.x);
                asm volatile("" : "+r"(f[0]), "+r"(f[1]), "+r"(f[2]), "+r"(f[3])::"memory");
                const uint32_t d = desc_lo(OFF_CSB + (P & 1) * 128, 0);
                mma(6, xf[0], KS, 4);
                wgmma_n56_rs<H_H, 0>(aq1, f, d + 64, 1);
                wgmma_n56_rs<H_H, 0>(aq2, f, d + 128, 1);
                wgmma_n56_rs<H_H, 0>(aq0, f, d, 1);
                wg_commit();
            }
            g1_wait(0);
            g1_run(0, wg ? 0 : NE);
            drain();
            pin(aq0); pin(aq1); pin(aq2);
            TSW(3);
            mbar_wait(bar + 8 * (B_EMPTYQ + 5), 0);
#pragma unroll
            for (int i = 0; i < 14; i++) { kp[i] = pack2(aq1[2 * i], aq1[2 * i + 1]); qp[i] = pack2(aq2[2 * i], aq2[2 * i + 1]); }
            stsm4(ka + 896, kp[1], kp[3], kp[5], kp[7]);
            stsm4(ka + 896 + 48, kp[7], kp[9], kp[11], kp[13]);
#pragma unroll
            for (int n = 0; n < 3; n++) stsm4(va + 896 + n * 32, qp[4 * n], qp[4 * n + 1], qp[4 * n + 2], qp[4 * n + 3]);
            stsm2(va + 896 + 96, qp[12], qp[13]);
            __syncwarp();
            mbar_arrive_if0(bar + 8 * B_QKV, tid - 224);
            release(bar + 8 * B_KV);
#pragma unroll
            for (int i = 0; i < 14; i++) qp[i] = pack2(aq0[2 * i], aq0[2 * i + 1]);
            TSW(4);
        }
        g1_run(wg ? 0 : NE, wg ? PRE1 : PRE0);
        {
            uint32_t kf[2][3][4], vf[2][3][4];
            const bool up0 = 2 * tq > g, up1 = 2 * tq + 1 > g, edge = (R | warp) == 0;
            float rk[2][2], fs[2][2], rs[3][2];
            mbar_wait(bar + 8 * (warp ? B_KV : B_HALO), 0);
            const uint32_t tag = *reinterpret_cast<volatile unsigned*>(smem + OFF_EP);
#pragma unroll
            for (int i = 0; i < 2; i++)
                asm volatile("ld.shared.v2.f32 {%0,%1}, [%2];" : "=f"(hb1[i]), "=f"(fb2[i]) : "r"(sb + OFF_BIAS + (warp * 16 + g + 8 * i) * 8) : "memory");
#pragma unroll
            for (int i = 0; i < 3; i++)
                asm volatile("ld.shared.v2.f32 {%0,%1}, [%2];" : "=f"(rs[i][0]), "=f"(rs[i][1]) : "r"(sta + i * 32) : "memory");
#pragma unroll
            for (int hd = 0; hd < 2; hd++) {
                ldsm4(ka + hd * 48, kf[hd][0]);
#pragma unroll
                for (int i = 0; i < 4; i++) { kf[hd][1][i] = kp[6 * hd + 2 * i]; kf[hd][2][i] = kp[6 * hd + 2 * i + 1]; }
                ldsm4t(va + hd * 48, vf[hd][0]); ldsm4t(va + hd * 48 + 32, vf[hd][1]);
                ldsm4t(ka + (OFF_V - OFF_K) + warp * 896 + hd * 48 + 1792, vf[hd][2]);
            }
            const uint32_t q0l = tq < 2 ? qp[6] : 0, q0h = tq < 2 ? qp[7] : 0, q1l = tq < 2 ? 0 : qp[6], q1h = tq < 2 ? 0 : qp[7];
            const uint32_t mk = (up0 ? 0xFFFFu : 0u) | (up1 ? 0xFFFF0000u : 0u);
            TSW(7);
            g1_run(wg ? PRE1 : PRE0, ATT_STEP);
#pragma unroll
            for (int i = 0; i < 4; i++) {
                rk[i >> 1][i & 1] = ((i & 1) ? up1 : up0) ? rs[i >> 1][i & 1] : rs[(i >> 1) + 1][i & 1];
                fs[i >> 1][i & 1] = rk[i >> 1][i & 1] * (rq[i >> 1] * (0.18898223650461362f * 1.4426950408889634f));
                asm volatile("" : "+f"(fs[i >> 1][i & 1])::"memory");
            }
            drain();
            sched_fence();
            TS0(19);
            float sc[2][3][4];
#pragma unroll
            for (int u = 0; u < 3; u++) {
#pragma unroll
                for (int i = 0; i < 8; i++) sc[i >> 2][u][i & 3] = 0.f;
                mma16816(sc[0][u], qp[0], qp[1], qp[2], qp[3], kf[0][u][0], kf[0][u][1]);
                mma16816(sc[1][u], q1l, q1h, qp[8], qp[9], kf[1][u][0], kf[1][u][1]);
            }
#pragma unroll
            for (int u = 0; u < 3; u++) {
                mma16816(sc[0][u], qp[4], qp[5], q0l, q0h, kf[0][u][2], kf[0][u][3]);
                mma16816(sc[1][u], qp[10], qp[11], qp[12], qp[13], kf[1][u][2], kf[1][u][3]);
            }
            float e[2][2][2], mx[2][2], sm[2][4];
#pragma unroll
            for (int hd = 0; hd < 2; hd++) {
                e[hd][0][0] = (up0 ? sc[hd][0][0] : sc[hd][1][0]) * fs[0][0];
                e[hd][0][1] = (up1 ? sc[hd][0][1] : sc[hd][1][1]) * fs[0][1];
                e[hd][1][0] = (up0 ? sc[hd][1][2] : sc[hd][2][2]) * fs[1][0];
                e[hd][1][1] = (up1 ? sc[hd][1][3] : sc[hd][2][3]) * fs[1][1];
                if (edge && up0) e[hd][0][0] = -1e30f;
                if (edge && up1) e[hd][0][1] = -1e30f;
                mx[hd][0] = fmaxf(e[hd][0][0], e[hd][0][1]);
                mx[hd][1] = fmaxf(e[hd][1][0], e[hd][1][1]);
            }
#pragma unroll
            for (int o = 1; o <= 2; o <<= 1)
#pragma unroll
                for (int i = 0; i < 4; i++) mx[i >> 1][i & 1] = fmaxf(mx[i >> 1][i & 1], __shfl_xor_sync(0xffffffffu, mx[i >> 1][i & 1], o));
            uint32_t pp[2][2], pu[2][2];
#pragma unroll
            for (int i = 0; i < 4; i++) {
                const float p0 = ex2(e[i >> 1][i & 1][0] - mx[i >> 1][i & 1]), p1 = ex2(e[i >> 1][i & 1][1] - mx[i >> 1][i & 1]);
                pp[i >> 1][i & 1] = pack2(p0 * rk[i & 1][0], p1 * rk[i & 1][1]);
                pu[i >> 1][i & 1] = pack2(p0, p1);
            }
            float ov[2][4][4];
#pragma unroll
            for (int hd = 0; hd < 2; hd++)
#pragma unroll
                for (int n = 0; n < 4; n++) {
                    ov[hd][n][0] = ov[hd][n][1] = ov[hd][n][2] = ov[hd][n][3] = 0.f;
                    mma16816(ov[hd][n], pp[hd][0] & mk, 0u, pp[hd][0] & ~mk, pp[hd][1] & mk, vf[hd][n >> 1][2 * (n & 1)], vf[hd][n >> 1][2 * (n & 1) + 1]);
                }
#pragma unroll
            for (int hd = 0; hd < 2; hd++) {
                sm[hd][0] = sm[hd][1] = sm[hd][2] = sm[hd][3] = 0.f;
                mma1688(sm[hd], pu[hd][0], pu[hd][1], 0x3F803F80u);
            }
#pragma unroll
            for (int hd = 0; hd < 2; hd++)
#pragma unroll
                for (int n = 0; n < 4; n++) mma1688(ov[hd][n], 0u, pp[hd][1] & ~mk, vf[hd][2][n]);
            sched_fence();
            TS0(18);
            bar_sync<1, 256>();
            g1_one(ATT_STEP);
#pragma unroll
            for (int i = 0; i < 4; i++) asm volatile("" : "+f"(sm[i >> 1][2 * (i & 1)])::"memory");
            uint32_t op[16];
            op[14] = op[15] = tag & 0x3FFF;
#pragma unroll
            for (int i = 0; i < 4; i++) sm[i >> 1][i & 1] = rcp(sm[i >> 1][2 * (i & 1)]);
#pragma unroll
            for (int n = 0; n < 7; n++) {
                const bool hb = n > 3 || (n == 3 && tq >= 2);
#pragma unroll
                for (int h = 0; h < 2; h++) {
                    const float r = hb ? sm[1][h] : sm[0][h];
                    const float x0 = hb ? ov[1][n >= 3 ? n - 3 : 0][2 * h] : ov[0][n <= 3 ? n : 0][2 * h];
                    const float x1 = hb ? ov[1][n >= 3 ? n - 3 : 0][2 * h + 1] : ov[0][n <= 3 ? n : 0][2 * h + 1];
                    op[2 * n + h] = pack2(x0 * r, x1 * r);
                }
            }
#pragma unroll
            for (int i = 0; i < 14; i++) asm volatile("" : "+r"(op[i])::"memory");
            g1_wait(ATT_STEP + 1);
            if (NQ) { g1_one(ATT_STEP + 1); g1_wait(ATT_STEP + 2); }
#pragma unroll
            for (int n = 0; n < 4; n++) stsm4(xa[n] + OFF_OST, op[4 * n], op[4 * n + 1], op[4 * n + 2], op[4 * n + 3]);
            __syncwarp();
            release(bar + 8 * B_OST);
            g1_one(ATT_STEP + 1 + NQ);
            g1_wait(ATT_STEP + 2 + NQ);
            TSW(5);
        }
        const uint32_t peer = z ^ 1;
        if (SW) drain();
        if (!GIN) gate_wait(wg && g1);
        g1_run(wg != SW ? ATT_STEP : ATT_STEP + 2 + NQ, 16, GIN ? 4 : 0);
        if (GIN < 2) gate_open(wg | !g1);
        mbar_wait(bar + 8 * B_FREE, 0);
        drain();
        if (GIN == 2) gate_open(wg | !g1);
        pin(a1);
        TSW(6);
        send_half(a1, mapa(sb + OFF_RECV1 + wg * 7168, peer), mapa(bar + 8 * (B_RECV1 + wg), peer), t, g1);
#pragma unroll
        for (int i = 0; i < 28; i++) a1[i] = fmaf(a1[i], 0.5f, hb1[(i >> 1) & 1]);
        pin<0, 28>(a1);
        float a2[56];
        auto o_run = [&](uint32_t i0, uint32_t i1) {
#pragma unroll 1
            for (uint32_t i = i0; i < i1; i++) {
                const uint32_t s = slot(r_o + i);
                mbar_wait(bar + 8 * (B_FULL + s), phase(r_o + i));
                TSD(64 + 17 + i);
                wg_fence();
#pragma unroll
                for (int k = 0; k < 4; k++) wgmma_n112<0, H_SW, H_U>(a2, dA + s * 1024 + k * 2, dU + s * 896 + k * 16, k ? 1 : i);
                wg_commit();
                wg_wait<1>();
                release(rel);
                rel = bar + 8 * (B_EMPTY + s);
            }
        };
        if (NO1) o_run(0, wg ? NO1 : 0);
        if (g1) {
            uint32_t p[14];
            const int ub = 2 * q + wg, zz = ub >= 14 ? 1 : 0;
            uint8_t* u0 = scr + G_BIMG + ((8 + ub) * 4 + j) * BLK + (7 * z + 6 * zz) * 1024 + w4 * 256 + lane * 4;
            uint8_t* u1 = u0 - (z & zz ? BLK : 0);
            mbar_wait(bar + 8 * (B_RECV1 + wg), (uint32_t)(((uint64_t)u0 | (uint64_t)u1) >> 63));
            TSW(8);
            recv_half(p, sb + OFF_RECV1 + wg * 7168, t);
#pragma unroll
            for (int i = 0; i < 14; i++) {
                stg32((i < 2 ? u0 : u1) + (i >> 1) * 1024 + (i & 1) * 128,
                      pack2(gelu_half(fmaf(bf_lo(p[i]), 0.5f, a1[2 * i])), gelu_half(fmaf(bf_hi(p[i]), 0.5f, a1[2 * i + 1]))));
            }
            TSW(9);
        }
        o_run(wg ? NO1 : 0, 4);
        drain();
        TSW(10);
#pragma unroll 1
        for (uint32_t r = r_u; r < r_u + 14 - NX2; r++) {
            const uint32_t s = slot(r);
            if (!NX2) gate_wait(wg && r == r_u + 14 - NS2);
            mbar_wait(bar + 8 * (B_FULL + s), phase(r));
            TSD(85 + r - r_u);
            wg_fence();
#pragma unroll
            for (int k = 0; k < 4; k++) wgmma_n112<1, H_SW, H_U>(a2, dA + s * 1024 + k * 128, dU + s * 896 + k * 16);
            wg_commit();
            wg_wait<1>();
            release(rel);
            rel = bar + 8 * (B_EMPTY + s);
        }
        uint32_t xr[4][4];
        auto x_fetch = [&]() {
            mbar_wait(bar + 8 * B_XR, 0);
#pragma unroll
            for (int k = 0; k < 4; k++) ldsm4(xa[k] + slot(r_u + 14) * 16384, xr[k]);
        };
        gate_open(wg);
        mbar_wait(bar + 8 * B_UDONE, 0);
        if (XF) x_fetch();
        wg_wait<0>();
        pin(a2);
        TSW(11);
        {
            const uint32_t rbuf = mapa(sb + OFF_RECV2 + wg * 8192 + t * 16, peer) - (z ? 0 : 2048), rbar = mapa(bar + 8 * (B_RECV2 + wg), peer);
#pragma unroll
            for (int i = 3; i >= 0; i--) send8(a2 + 24 + 8 * i, rbuf + i * 2048, rbar, i | z);
            if (!XF && !NX2) x_fetch();
#pragma unroll
            for (int i = 0; i < 32; i++) a2[i] += ((i & 1) ? bf_hi(xr[i >> 3][(i >> 1) & 3]) : bf_lo(xr[i >> 3][(i >> 1) & 3])) + fb2[(i >> 1) & 1];
            pin<0, 32>(a2);
            const uint32_t oa = sb + OFF_OUT + (warp * 16 + (lane >> 3)) * 128 + (((lane ^ (lane >> 3)) & 7) << 4);
            const uint32_t oo = (q * 128 + warp * 16 + (lane >> 3)) * 896 + j * 224 + z * 128 + (lane & 7) * 16;
            uint8_t* og = out + oo;
            mbar_wait(bar + 8 * (B_RECV2 + wg), (oa | oo | (uint32_t)((uint64_t)og >> 32)) >> 31);
            TSW(12);
            uint32_t u[16];
#pragma unroll
            for (int i = 0; i < 4; i++)
                asm volatile("ld.shared.v4.b32 {%0,%1,%2,%3}, [%4];" : "=r"(u[4 * i]), "=r"(u[4 * i + 1]), "=r"(u[4 * i + 2]), "=r"(u[4 * i + 3]) : "r"(sb + OFF_RECV2 + wg * 8192 + i * 2048 + t * 16) : "memory");
#pragma unroll
            for (int e = 0; e < 16; e++) u[e] = pack2(a2[2 * e] + bf_lo(u[e]), a2[2 * e + 1] + bf_hi(u[e]));
#pragma unroll
            for (int i = 0; i < 4; i++) stsm4(xa[i] + OFF_OUT, u[4 * i], u[4 * i + 1], u[4 * i + 2], u[4 * i + 3]);
            __syncwarp();
#pragma unroll
            for (int i = 0; i < 4; i++)
                asm volatile("ld.shared.v4.b32 {%0,%1,%2,%3}, [%4];" : "=r"(u[4 * i]), "=r"(u[4 * i + 1]), "=r"(u[4 * i + 2]), "=r"(u[4 * i + 3]) : "r"((oa ^ ((i & 1) << 6)) + i * 512) : "memory");
            if ((lane & 7) < 8 - 2 * z) {
#pragma unroll
                for (int i = 0; i < 4; i++)
                    asm volatile("st.global.v4.b32 [%0], {%1,%2,%3,%4};" ::"l"(og + i * 3584), "r"(u[4 * i]), "r"(u[4 * i + 1]), "r"(u[4 * i + 2]), "r"(u[4 * i + 3]) : "memory");
            }
        }
        TSW(13);
    } else if (warp < 12) {
        asm volatile("setmaxnreg.dec.sync.aligned.u32 64;");
        const int hw = warp - 8, t = tid & 127;
        reinterpret_cast<uint32_t*>(smem + OFF_ONES)[t] = t < 64 ? 0x3F803F80u : 0;
        fence_async_smem();
        bar_sync<12, 128>();
        while (clock32() - t_in < DLY1) SPIN;
        if (wline < 9408 && !wfirst) l2_prefetch(reinterpret_cast<const uint8_t*>(wqkv) + wline * 128);
        uint8_t* cscell = scr + G_CS + ((P * 8 + R) * 2 + z) * 512 + (t >> 2) * 16;
        if ((lane & 3) == 0) cell_put(cscell, 0, 0, 0);
        uint8_t* cells = scr + G_HALO + ((R * 8 + P) * 2 + z) * 3584 + min(t, 111) * 16;
        cell_put(cells, 0, 0, 0);
        cell_put(cells + 1792, 0, 0, 0);
        const unsigned e1 = epoch();
        const uint32_t bv1 = ldg_u16(b1 + (g1 ? q * 128 : 0) + t), bv2 = ldg_u16(b2 + q * 128 + t);
        {
            const uint32_t da = desc_lo(OFF_B + min((R & 1) * 2 + z, 2) * 4096, 16), db = desc_lo(OFF_ONES, 128);
            float c0[4];
            const int st = R & 6 & ~ROT;
            mbar_wait(bar + 8 * (B_FULLQ + st), 0);
            mbar_wait(bar + 8 * (B_FULLQ + st + 1), 0);
            TSH(47);
            wg_fence();
#pragma unroll
            for (int k = 0; k < 8; k++)
                wgmma_n8<1, H_SW, H_H>(c0, da + ((WSLOT >> (4 * st + (k & 4))) & 7) * 1536 + (k & 2) * 384 + (k & 1) * 128, db + (k >= 4 && R >= 6 ? 16 : 0), k);
            wg_commit();
            wg_wait<0>();
            pin(c0);
            if ((lane & 3) == 0) cell_put(cscell, __float_as_uint(c0[0]), __float_as_uint(c0[2]), e1);
            if (lane < 4) asm volatile("mbarrier.arrive.shared::cluster.b64 _, [%0];" ::"r"(mapa(bar + 8 * (B_EMPTYQ + st + (lane >> 1)), lane & 1)) : "memory");
            TSH(43);
        }
        mbar_wait(bar + 8 * (B_FULLQ + GATHER), 0);
        TSH(39);
        {
            const bool cw = hw < 3;
            const uint8_t* src = cw ? scr + G_CS + P * 8192 + t * 16 : scr + G_STATS + (z * 1024 + R * 128 + lane) * 16;
            uint32_t a[5], d[5], bad;
            do {
                bad = 0;
#pragma unroll
                for (int i = 0; i < 4; i++) bad |= cell_get(src + i * (cw ? 2048 : 512), a[i], d[i], e1);
                if (t >= 120) bad |= cell_get(src - (R ? 512 : 0), a[4], d[4], e1);
            } while (bad);
            TSH(45);
            if (cw) {
                uint4* cb = reinterpret_cast<uint4*>(smem + OFF_CSB) + (t >> 3) * 16 + (t & 7);
                const uint32_t lo = split2((__uint_as_float(a[0]) + __uint_as_float(a[1])) + (__uint_as_float(a[2]) + __uint_as_float(a[3])));
                const uint32_t hi = split2((__uint_as_float(d[0]) + __uint_as_float(d[1])) + (__uint_as_float(d[2]) + __uint_as_float(d[3])));
                cb[0] = make_uint4(lo, lo, 0, 0);
                cb[8] = make_uint4(hi, hi, 0, 0);
            } else {
                uint2* st = reinterpret_cast<uint2*>(smem + OFF_STATS) + lane;
                uint32_t* rd = reinterpret_cast<uint32_t*>(smem + OFF_RSTD) + lane;
#pragma unroll
                for (int i = 0; i < 4; i++) { st[32 * i] = make_uint2(a[i], d[i]); rd[8 + 32 * i] = a[i]; }
                if (t >= 120) rd[-24] = a[4];
            }
            fence_async_smem();
            __syncwarp();
            mbar_arrive_if0(bar + 8 * B_AUX, lane);
            TSH(41);
            reinterpret_cast<float2*>(smem + OFF_BIAS)[t] = make_float2(0.5f * bf_lo(bv1), bf_lo(bv2));
            __syncwarp();
            mbar_arrive_if0(bar + 8 * B_KV, lane);
        }
        {
            uint2* kv = reinterpret_cast<uint2*>(smem + OFF_K) + min(t, 111);
            mbar_wait(bar + 8 * B_QKV, 0);
            uint2 k2 = kv[896], v2 = kv[1792 + (OFF_V - OFF_K) / 8];
            cell_put(cells, k2.x, k2.y, e1);
            cell_put(cells + 1792, v2.x, v2.y, e1);
            k2 = v2 = make_uint2(0, 0);
            if (R > 0) while (cell_get(cells - 16 * 3584, k2.x, k2.y, e1) | cell_get(cells - 16 * 3584 + 1792, v2.x, v2.y, e1)) {}
            kv[0] = k2;
            kv[(OFF_V - OFF_K) / 8] = v2;
            mbar_wait(bar + 8 * B_KV, 0);
            __syncwarp();
            mbar_arrive_if0(bar + 8 * B_HALO, lane);
            TSH(40);
        }
        if (hw == 3) {
            mbar_wait(bar + 8 * B_OST, 0);
            if (elect()) {
                unsigned* oc = ctr + C_O + (R * 2 + (P >> 2)) * 32;
                asm volatile("mbarrier.arrive.relaxed.cluster.shared::cluster.b64 _, [%0];" ::"r"(mapa(bar + 8 * B_FREE, z ^ 1)) : "memory");
                fence_async_smem();
                tma2d_store(&mp.ost, sb + OFF_OST, z * 64, P * 1024 + R * 128);
                bulk_commit();
                delay(DO);
                red_relaxed(oc, 1);
                TS(21);
                bulk_wait_all();
                asm volatile("mbarrier.arrive.relaxed.cluster.shared::cluster.b64 _, [%0];" ::"r"(mapa(bar + 8 * B_UDONE, z ^ 1)) : "memory");
                TS(20);
            }
        } else {
            const uint32_t tag = e1 & 0x3FFF;
            const uint32_t ca = sb + OFF_A + lane * 128 + ((~lane & 7) << 4) + (lane >> 3) * 4, cb = sb + OFF_B + lane * 132;
            uint32_t par = 0x3F;
#pragma unroll 1
            for (uint32_t r = r_o + hw; r < r_u + 14;) {
                const uint32_t s = slot(r);
                const bool isa = r - r_o < 4;
                const uint32_t a0 = isa ? ca + s * 16384 : cb + s * BLK, a3 = a0 - (isa ? 0 : (lane & 16) * 132);
                mbar_wait(bar + 8 * (B_LAND + s), (par >> s) & 1);
                par ^= 1 << s;
                bool ok = true;
#pragma unroll
                for (int k = 0; k < 4; k++) {
                    uint32_t v;
                    asm volatile("ld.shared.b32 %0, [%1];" : "=r"(v) : "r"((k < 3 ? a0 : a3) + k * 4096) : "memory");
                    ok &= (v == (isa ? tag : ~0u)) == isa;
                }
                if (__all_sync(0xffffffffu, ok)) {
                    mbar_arrive_if0(bar + 8 * (B_FULL + s), lane);
                    if (r == r_o || r == r_u) TS(r == r_o ? 29 : 30);
                    r += 3;
                } else if (elect()) {
                    TS(31);
                    fetch_x(r);
                }
            }
        }
    } else {
        asm volatile("setmaxnreg.dec.sync.aligned.u32 32;");
        auto wait_free = [&](uint32_t r, uint32_t first) {
            const uint32_t a = r < 6 ? B_EMPTYQ + ((first >> (4 * r)) & 7) : B_EMPTY + slot(r);
            mbar_wait(bar + 8 * a, r < 6 ? 0 : phase(r) ^ 1);
        };
        if (warp == 12) {
            TS(14);
            if (elect()) {
#pragma unroll 1
                for (int kb = 0; kb < 7; kb++) {
                    if (kb < 2) while (clock32() - t_in < (kb ? DLY2 : DLY0)) SPIN;
                    if (kb >= QDEPTH) { mbar_wait(bar + 8 * (B_FULLQ + kb - QDEPTH), 0); TS(25 + kb - QDEPTH); }
                    if (kb >= 5) mbar_wait(bar + 8 * (B_EMPTYQ + kb - 5), 0);
                    if (kb > 0) x_load(kb);
                    tma3d_mc(sb + OFF_B + ((WSLOT >> (4 * kb)) & 7) * 24576 + z * 12288, &mp.wqkv, (P * 56) & ~15, krow(kb) + z * 32, 0, bar + 8 * (B_FULLQ + kb));
                }
                TS(17);
                ld_relaxed(ctr + C_O + ((q & ~1) + z) * 32);
                mbar_wait(bar + 8 * B_LNFREE, 0);
                if (!g1) {
                    const int ic = (q - 14) * 8 + j * 2 + z, rot = ic >> 3;
                    mbar_wait(bar + 8 * (B_EMPTYQ + 2), 0);
                    mbar_expect(bar + 8 * B_GO, 2 * BLK);
#pragma unroll 1
                    for (int i = 0; i < 2; i++) tma4d(sb + OFF_A + i * BLK, &mp.wo, 0, 0, (z * 2 + i) * 14, ic >> 1, bar + 8 * B_GO);
                    mbar_wait(bar + 8 * B_GO, 0);
#pragma unroll 1
                    for (int i = 0; i < 2; i++) {
                        uint8_t* dst = scr + G_BIMG + (ic * 2 + i) * BLK;
                        bulk_store(dst + rot * 6144, sb + OFF_A + i * BLK, 8192);
                        bulk_store(dst + (rot ^ 1) * 8192, sb + OFF_A + i * BLK + 8192, 6144);
                    }
                    bulk_commit();
                    bulk_wait_all();
                    publish(ctr + C_WO);
                    TS(44);
                }
#pragma unroll 1
                for (uint32_t r = 0; r < r_o; r++) {
                    const uint32_t s = slot(r), fb = bar + 8 * (B_FULL + s);
                    wait_free(r, 0x654320u);
                    mbar_expect(fb, 16384);
                    tma3d(sb + OFF_A + s * 16384, &mp.w1, 0, z * 1024 + r * 64, 2 * q, fb);
                    TS(99 + r);
                }
                mbar_wait(bar + 8 * B_OST, 0);
#pragma unroll 1
                for (uint32_t r = r_o; r < r_o + NARM; r++) {
                    wait_free(r, 0x654320u);
                    mbar_expect(bar + 8 * (B_LAND + slot(r)), 16384);
                }
                poll(ctr + C_O + ((q & ~1) + z) * 32, epoch() * 8);
                TS(32);
#pragma unroll
                for (uint32_t i = 0; i < NARM; i++) fetch_x(r_o + i, false);
                TS(99 + 17);
#pragma unroll 1
                for (uint32_t r = r_o + NARM; r < r_u; r++) {
                    wait_free(r, 0x654320u);
                    fetch_x(r);
                    TS(99 + 17 + r - r_o);
                }
#pragma unroll 1
                for (uint32_t i = 0; i < 14; i++) {
                    const uint32_t r = r_u + i, s = slot(r), fb = bar + 8 * (B_FULL + s);
                    wait_free(r, 0x654320u);
                    mbar_expect(fb, 16384);
                    tma3d(sb + OFF_A + s * 16384, &mp.w2, 0, (14 * z + (i < 7 ? 2 * i : 2 * i - 13)) * 64, 2 * q, fb);
                    TS(99 + 21 + i);
                }
                wait_free(r_u + 14, 0);
                mbar_expect(bar + 8 * B_XR, 16384);
                tma2d(sb + OFF_A + slot(r_u + 14) * 16384, &mp.xn, j * 112 + z * 64, q * 128, bar + 8 * B_XR);
            }
        } else if (warp == 13) {
            if (elect()) {
#pragma unroll 1
                for (int ph = g1 ? 0 : 1; ph < 4; ph++) {
                    const uint8_t* src = ph == 0 ? scr + G_HIMG + (64 * z + j) * BLK : scr + G_BIMG + ((ph == 1 ? 4 * z : 6 + 14 * z + ph) * 4 + j) * BLK;
                    const uint32_t r0 = ph == 0 ? 0 : r_o + (ph == 1 ? 0 : 7 * ph - 10), r1 = r_o + (ph == 0 ? 0 : 7 * ph - 3);
#pragma unroll 1
                    for (uint32_t r = r0; r < r1; r++, src += ph < 2 ? 4 * BLK : 8 * BLK) {
                        const uint32_t s = slot(r), fb = bar + 8 * ((ph < 2 ? B_FULL : B_LAND) + s);
                        wait_free(r, 0x644332u);
                        mbar_expect(fb, BLK);
                        mbar_wait(bar + 8 * (B_GO + ph), 0);
                        bulk_load(sb + OFF_B + s * BLK, src, BLK, fb);
                        TS(134 + 16 + (ph > 0) + r - r_o);
                    }
                }
            }
        } else if (warp == 14) {
            uint8_t* stcell = scr + G_STATS + ((lane & 1) * 1024 + 8 * b + (lane >> 1)) * 16;
            if (lane < 16) cell_put(stcell, 0, 0, 0);
            const unsigned ev = ld_relaxed(ctr + C_LN);
            uint8_t* hb = scr + G_HIMG + (b & ~3) * BLK;
            const unsigned e1 = (ev >> 7) + 1;
            if (lane == 0) {
                *reinterpret_cast<volatile unsigned*>(smem + OFF_EP) = e1;
                mbar_arrive(bar + 8 * B_EP);
                TS(36);
            }
            bar_sync<10, 288>();
            if (elect()) {
                fence_async_smem();
                TS(42);
                tma4d_store(&mp.hst, sb + OFF_A, 0, 0, b & 3, b & ~3);
                bulk_commit();
            }
            __syncwarp();
            if (lane < 16) {
                const uint2 v = reinterpret_cast<const uint2*>(smem + OFF_LNST)[lane];
                cell_put(stcell, v.x, v.y, e1);
            }
            bulk_wait_all();
            __syncwarp();
            TS(63);
            unsigned rb = 0;
#pragma unroll
            for (int i = 0; i < 4; i++) rb |= ld_relaxed(reinterpret_cast<const unsigned*>(hb + i * BLK + ((b & 3) * 28 + min(lane, 27)) * 128));
            if (lane == 0) {
                mbar_arrive(bar + 8 * B_LNFREE);
                red_relaxed(ctr + C_LN, 1 + (rb & (sb >> 31)));
                TS(37);
                ld_relaxed(ctr + C_U + z * 64);
                ld_relaxed(ctr + C_U + z * 64 + 32);
#pragma unroll 1
                for (int ph = g1 ? 0 : 1; ph < 4; ph++) {
                    if (ph) mbar_wait(bar + 8 * (ph == 1 ? B_HALO : g1 ? B_RECV1 : B_OST), 0);
                    poll(ctr + ph * 32 + (ph >> 1) * z * 64, e1 * (ph == 0 ? 128 : ph == 1 ? 16 : 56));
                    fence_async_global();
                    mbar_arrive(bar + 8 * (B_GO + ph));
                    if (ph != 1) TS(ph == 0 ? 33 : 32 + ph);
                }
            }
        } else {
            if ((sb & 0x3FFFF) != SB0) __trap();
            if (elect()) {
#pragma unroll 1
                for (int i = 2; i < 10; i++) asm volatile("prefetch.tensormap [%0];" ::"l"(reinterpret_cast<const CUtensorMap*>(&mp) + i) : "memory");
            }
            __syncwarp();
            mbar_watch(bar + 8 * B_KV, 0);
#pragma unroll 1
            for (int i = g1 ? 0 : 8; i < 8; i++) {
                uint32_t l = (7 * z + (q >= 7 ? 6 : 0)) * 8 + (i & 3) * 14 + min(lane >> 1, 13);
                if (l >= 112) l -= 112;
                cell_put(scr + G_BIMG + ((8 + 2 * q + (i >> 2)) * 4 + j) * BLK + l * 128 + (l & 24) * 4 + (lane & 1) * 16, ~0u, ~0u, ~0u);
            }
            __threadfence();
            __syncwarp();
            mbar_arrive_if0(bar + 8 * B_FREE, lane);
            TS(59);
#pragma unroll 1
            for (int i = g1 ? 0 : 2; i < 2; i++) {
                mbar_watch(bar + 8 * (B_RECV1 + i), 0);
                delay(DU);
                if (lane == 0) red_relaxed(ctr + C_U + ((q >= 7 ? 2 : 0) + i) * 32, 1);
                TS(22 + i);
            }
            mbar_watch(bar + 8 * B_RECV2, 0);
            mbar_watch(bar + 8 * (B_RECV2 + 1), 0);
        }
    }
}

typedef CUresult (*EncodeFn)(CUtensorMap*, CUtensorMapDataType, cuuint32_t, void*, const cuuint64_t*, const cuuint64_t*, const cuuint32_t*,
                             const cuuint32_t*, CUtensorMapInterleave, CUtensorMapSwizzle, CUtensorMapL2promotion, CUtensorMapFloatOOBfill);

void encode(EncodeFn fn, CUtensorMap* m, const void* p, int rank, const cuuint64_t* dims, const cuuint64_t* strides, const cuuint32_t* box, bool swz) {
    const cuuint32_t es[4] = {1, 1, 1, 1};
    fn(m, CU_TENSOR_MAP_DATA_TYPE_BFLOAT16, rank, const_cast<void*>(p), dims, strides, box, es, CU_TENSOR_MAP_INTERLEAVE_NONE,
       swz ? CU_TENSOR_MAP_SWIZZLE_128B : CU_TENSOR_MAP_SWIZZLE_NONE, CU_TENSOR_MAP_L2_PROMOTION_L2_128B, CU_TENSOR_MAP_FLOAT_OOB_FILL_NONE);
}

}

extern "C" void kernel_launch(void* const* d_in, const int* in_sizes, int n_in, void* d_out, int out_size) {
    const __nv_bfloat16* x = (const __nv_bfloat16*)d_in[0];
    const __nv_bfloat16* wqkv = (const __nv_bfloat16*)d_in[1];
    const __nv_bfloat16* wo = (const __nv_bfloat16*)d_in[2];
    const __nv_bfloat16* w1 = (const __nv_bfloat16*)d_in[4];
    const __nv_bfloat16* b1 = (const __nv_bfloat16*)d_in[5];
    const __nv_bfloat16* w2 = (const __nv_bfloat16*)d_in[6];
    const __nv_bfloat16* b2 = (const __nv_bfloat16*)d_in[7];

    void* fp = nullptr;
    cudaDriverEntryPointQueryResult qr;
    cudaGetDriverEntryPoint("cuTensorMapEncodeTiled", &fp, cudaEnableDefault, &qr);
    EncodeFn fn = (EncodeFn)fp;
    void* sp = nullptr;
    cudaGetSymbolAddress(&sp, g_scratch);
    uint8_t* scr = (uint8_t*)sp;
    void *o = scr + G_O, *himg = scr + G_HIMG;

    Maps mp;
    { cuuint64_t d[3] = {64, 2048, 7}, s[2] = {896, 128}; cuuint32_t bx[3] = {64, 16, 7}; encode(fn, &mp.xl, x, 3, d, s, bx, true); }
    { cuuint64_t d[2] = {896, 1024}, s[1] = {1792}; cuuint32_t bx[2] = {64, 128}; encode(fn, &mp.x, x, 2, d, s, bx, true); }
    { cuuint64_t d[3] = {448, 448, 3}, s[2] = {2688, 896}; cuuint32_t bx[3] = {64, 32, 3}; encode(fn, &mp.wqkv, wqkv, 3, d, s, bx, true); }
    { cuuint64_t d[3] = {64, 2048, 28}, s[2] = {3584, 128}; cuuint32_t bx[3] = {64, 64, 2}; encode(fn, &mp.w1, w1, 3, d, s, bx, true); }
    { cuuint64_t d[3] = {64, 1792, 32}, s[2] = {4096, 128}; cuuint32_t bx[3] = {64, 64, 2}; encode(fn, &mp.w2, w2, 3, d, s, bx, true); }
    { cuuint64_t d[4] = {64, 28, 4, 128}, s[3] = {128, 3584, BLK}; cuuint32_t bx[4] = {64, 28, 1, 4}; encode(fn, &mp.hst, himg, 4, d, s, bx, false); }
    { cuuint64_t d[2] = {448, 2048}, s[1] = {896}; cuuint32_t bx[2] = {64, 128}; encode(fn, &mp.xn, x, 2, d, s, bx, true); }
    { cuuint64_t d[2] = {64, 8 * 2048}, s[1] = {128}; cuuint32_t bx[2] = {64, 128}; encode(fn, &mp.old_, o, 2, d, s, bx, true); }
    { cuuint64_t d[2] = {128, 8 * 1024}, s[1] = {256}; cuuint32_t bx[2] = {64, 128}; encode(fn, &mp.ost, o, 2, d, s, bx, true); }
    { cuuint64_t d[4] = {8, 56, 56, 8}, s[3] = {896, 16, 56 * 896}; cuuint32_t bx[4] = {8, 64, 14, 1}; encode(fn, &mp.wo, wo, 4, d, s, bx, false); }

    cudaFuncSetAttribute(fused_kernel, cudaFuncAttributeMaxDynamicSharedMemorySize, SMEM_BYTES);
    fused_kernel<<<128, 512, SMEM_BYTES>>>(x, wqkv, b1, b2, scr, (uint8_t*)d_out, mp);
}
```

```cpp
#include <cuda_runtime.h>
#include <cuda.h>
#include <cuda_bf16.h>
#include <stdint.h>

namespace {

constexpr int S_ = 2048, D_ = 448;
constexpr uint32_t BLK = 14336;

constexpr uint32_t G_HIMG = 0;
constexpr uint32_t G_BIMG = G_HIMG + 32 * 4 * BLK;
constexpr uint32_t G_O = G_BIMG + 36 * 4 * BLK;
constexpr uint32_t G_STATS = G_O + 8 * S_ * 128;
constexpr uint32_t G_CS = G_STATS + S_ * 16;
constexpr uint32_t G_HALO = G_CS + 8 * 4 * 2048;
constexpr uint32_t G_CTR = G_HALO + 128 * 3584;
constexpr uint32_t G_END = G_CTR + (192 + 16 * 32) * 4;
__device__ __align__(1024) uint8_t g_scratch[G_END];

constexpr int C_LN = 0, C_WO = 32, C_U = 64, C_O = 192;

#define TSX(sel, id)
#define TS(id)
#define TS0(id)
#define TSH(id)
#define TSW(id)
#define TG(id)

#define TSG1 0
#define TSD(id)
#define QDEPTH 3
#define ROT 6
#define KS 3
#define QUNROLL 1
#define W0 1
#define DLY1 1600
#define DLY2 2000
#define GATHER 3
#define PFW 0
#define NS1 5
#define NS2 3
#define NE 2
#define PRE0 8
#define PRE1 5
#define STG 1
#define NX2 0
#define DU 0
#define DO 100
#define NO1 0
#define XF 0
#define SW 1
#define NARM 2
#define DH 400
#define NH 2
#define GH 4
#define NQ 0
#define GIN 1
constexpr uint32_t OFF_A = 0;
constexpr uint32_t OFF_B = 98304;
constexpr uint32_t OFF_X = 184320;
constexpr uint32_t OFF_K = 196608;
constexpr uint32_t OFF_V = OFF_K + 9 * 896;
constexpr uint32_t OFF_OST = OFF_X, OFF_RECV2 = OFF_X, OFF_RECV1 = OFF_X + 16384, OFF_OUT = OFF_X + 16384;
constexpr uint32_t OFF_CSB = 221184;
constexpr uint32_t OFF_ONES = OFF_CSB + 3072;
constexpr uint32_t OFF_STATS = OFF_ONES + 512;
constexpr uint32_t OFF_BIAS = OFF_STATS + 1024;
constexpr uint32_t OFF_LNX = OFF_BIAS + 1024;
constexpr uint32_t OFF_RSTD = OFF_LNX + 512;
constexpr uint32_t OFF_LNST = 229376;
constexpr uint32_t OFF_EP = OFF_LNST + 128;
constexpr uint32_t OFF_BAR = OFF_EP + 16;
constexpr uint32_t OFF_TS = OFF_BAR + 8 * 48;
constexpr uint32_t SMEM_BYTES = OFF_TS;

enum : int {
    B_FULLQ = 0, B_LNIN = 7, B_EMPTYQ = 8, B_FULL = 15, B_EMPTY = 21, B_AUX = 27, B_QKV = 28, B_HALO = 29, B_FREE = 30,
    B_RECV1 = 31, B_RECV2 = 33, B_GOH = 35, B_EP = 37, B_OST = 38, B_LNFREE = 39, B_UDONE = 40, B_NONE = 41, B_GO = 42, B_XR = 46, B_KV = 47, B_COUNT = 48, B_LAND = B_FULLQ
};
constexpr int kQUnroll = QUNROLL;
constexpr uint32_t XSLOT = 0x5432154u;
constexpr uint32_t WSLOT = 0x3421034u;
#define ATT_STEP 10

__device__ __forceinline__ uint32_t smem_u32(const void* p) { return (uint32_t)__cvta_generic_to_shared(p); }
__device__ __forceinline__ void mbar_init(uint32_t a, int c) { asm volatile("mbarrier.init.shared::cta.b64 [%0], %1;" ::"r"(a), "r"(c) : "memory"); }
__device__ __forceinline__ void mbar_expect(uint32_t a, uint32_t b) { asm volatile("mbarrier.arrive.expect_tx.shared::cta.b64 _, [%0], %1;" ::"r"(a), "r"(b) : "memory"); }
__device__ __forceinline__ void mbar_arrive(uint32_t a) { asm volatile("mbarrier.arrive.shared::cta.b64 _, [%0];" ::"r"(a) : "memory"); }
__device__ __forceinline__ void mbar_arrive_if0(uint32_t a, uint32_t sel) {
    asm volatile("{\n.reg .pred p;\nsetp.eq.u32 p, %1, 0;\n@p mbarrier.arrive.shared::cta.b64 _, [%0];\n}" ::"r"(a), "r"(sel) : "memory");
}
__device__ __forceinline__ void mbar_wait(uint32_t a, uint32_t parity) {
    asm volatile("{\n.reg .pred p;\nW0:\nmbarrier.try_wait.parity.shared::cta.b64 p, [%0], %1;\n@!p bra W0;\n}\n" ::"r"(a), "r"(parity) : "memory");
}
__device__ __forceinline__ void mbar_watch(uint32_t a, uint32_t parity) {
    asm volatile(
        "{\n.reg .pred p;\n.reg .u32 n;\nmov.u32 n, 0;\n"
        "W0:\nmbarrier.try_wait.parity.shared::cta.b64 p, [%0], %1;\n@p bra W1;\n"
        "add.u32 n, n, 1;\nsetp.lt.u32 p, n, 4194304;\n@p bra W0;\ntrap;\nW1:\n}\n" ::"r"(a), "r"(parity) : "memory");
}
__device__ __forceinline__ bool elect() {
    uint32_t r;
    asm volatile("{\n.reg .pred p;\nelect.sync _|p, 0xffffffff;\nselp.u32 %0, 1, 0, p;\n}" : "=r"(r));
    return r;
}
__device__ __forceinline__ uint32_t mapa(uint32_t a, uint32_t cta) { uint32_t r; asm("mapa.shared::cluster.u32 %0, %1, %2;" : "=r"(r) : "r"(a), "r"(cta)); return r; }
__device__ __forceinline__ void tma2d(uint32_t dst, const CUtensorMap* m, int c0, int c1, uint32_t bar) {
    asm volatile("cp.async.bulk.tensor.2d.shared::cluster.global.mbarrier::complete_tx::bytes [%0], [%1, {%3, %4}], [%2];" ::"r"(dst), "l"(m), "r"(bar), "r"(c0), "r"(c1) : "memory");
}
__device__ __forceinline__ void tma3d(uint32_t dst, const CUtensorMap* m, int c0, int c1, int c2, uint32_t bar) {
    asm volatile("cp.async.bulk.tensor.3d.shared::cluster.global.mbarrier::complete_tx::bytes [%0], [%1, {%3, %4, %5}], [%2];" ::"r"(dst), "l"(m), "r"(bar), "r"(c0), "r"(c1), "r"(c2) : "memory");
}
__device__ __forceinline__ void tma3d_mc(uint32_t dst, const CUtensorMap* m, int c0, int c1, int c2, uint32_t bar) {
    asm volatile("cp.async.bulk.tensor.3d.shared::cluster.global.mbarrier::complete_tx::bytes.multicast::cluster [%0], [%1, {%3, %4, %5}], [%2], %6;"
                 ::"r"(dst), "l"(m), "r"(bar), "r"(c0), "r"(c1), "r"(c2), "h"((uint16_t)3) : "memory");
}
__device__ __forceinline__ void tma2d_store(const CUtensorMap* m, uint32_t src, int c0, int c1) {
    asm volatile("cp.async.bulk.tensor.2d.global.shared::cta.bulk_group [%0, {%2, %3}], [%1];" ::"l"(m), "r"(src), "r"(c0), "r"(c1) : "memory");
}
__device__ __forceinline__ void tma4d_store(const CUtensorMap* m, uint32_t src, int c0, int c1, int c2, int c3) {
    asm volatile("cp.async.bulk.tensor.4d.global.shared::cta.bulk_group [%0, {%2, %3, %4, %5}], [%1];" ::"l"(m), "r"(src), "r"(c0), "r"(c1), "r"(c2), "r"(c3) : "memory");
}
__device__ __forceinline__ void tma4d(uint32_t dst, const CUtensorMap* m, int c0, int c1, int c2, int c3, uint32_t bar) {
    asm volatile("cp.async.bulk.tensor.4d.shared::cluster.global.mbarrier::complete_tx::bytes [%0], [%1, {%3, %4, %5, %6}], [%2];" ::"r"(dst), "l"(m), "r"(bar), "r"(c0), "r"(c1), "r"(c2), "r"(c3) : "memory");
}
__device__ __forceinline__ void bulk_load(uint32_t dst, const void* src, uint32_t bytes, uint32_t bar) {
    asm volatile("cp.async.bulk.shared::cluster.global.mbarrier::complete_tx::bytes [%0], [%1], %2, [%3];" ::"r"(dst), "l"(src), "r"(bytes), "r"(bar) : "memory");
}
__device__ __forceinline__ void bulk_store(void* dst, uint32_t src, uint32_t bytes) {
    asm volatile("cp.async.bulk.global.shared::cta.bulk_group [%0], [%1], %2;" ::"l"(dst), "r"(src), "r"(bytes) : "memory");
}
__device__ __forceinline__ void bulk_commit() { asm volatile("cp.async.bulk.commit_group;" ::: "memory"); }
__device__ __forceinline__ void bulk_wait_all() { asm volatile("cp.async.bulk.wait_group 0;" ::: "memory"); }
__device__ __forceinline__ void bulk_wait_read() { asm volatile("cp.async.bulk.wait_group.read 0;" ::: "memory"); }
__device__ __forceinline__ void l2_prefetch(const void* p) { asm volatile("prefetch.global.L2 [%0];" ::"l"(p)); }
__device__ __forceinline__ void fence_async_smem() { asm volatile("fence.proxy.async.shared::cta;" ::: "memory"); }
__device__ __forceinline__ void fence_async_global() { asm volatile("fence.proxy.async.global;" ::: "memory"); }
__device__ __forceinline__ void red_relaxed(unsigned* p, unsigned v) { asm volatile("red.relaxed.gpu.global.add.u32 [%0], %1;" ::"l"(p), "r"(v) : "memory"); }
__device__ __forceinline__ void publish(unsigned* p) {
    asm volatile("fence.proxy.async.global;\nred.release.gpu.global.add.u32 [%0], 1;" ::"l"(p) : "memory");
}
__device__ __forceinline__ void stg32(void* p, uint32_t v) { asm volatile("st.global.b32 [%0], %1;" ::"l"(p), "r"(v) : "memory"); }
__device__ __forceinline__ unsigned ld_relaxed(const unsigned* p) { unsigned v; asm volatile("ld.relaxed.gpu.global.u32 %0, [%1];" : "=r"(v) : "l"(p) : "memory"); return v; }
__device__ __forceinline__ bool ctr_done(unsigned v, unsigned target) { return ((v - target) & 0x1FFFFFFu) == 0; }
__device__ __forceinline__ uint32_t clock32() { uint32_t c; asm volatile("mov.u32 %0, %%clock;" : "=r"(c)::"memory"); return c; }
__device__ __forceinline__ void delay(uint32_t n) { const uint32_t t0 = clock32(); while (clock32() - t0 < n) {} }
__device__ __forceinline__ void poll(const unsigned* p, unsigned target) { while (!ctr_done(ld_relaxed(p), target)) {} }
__device__ __forceinline__ void cell_put(void* p, uint32_t a, uint32_t b, uint32_t tag) {
    asm volatile("st.relaxed.gpu.global.v4.b32 [%0], {%1, %3, %2, %3};" ::"l"(p), "r"(a), "r"(b), "r"(tag) : "memory");
}
__device__ __forceinline__ uint32_t cell_get(const void* p, uint32_t& a, uint32_t& b, uint32_t tag) {
    uint32_t t0, t1;
    asm volatile("ld.relaxed.gpu.global.v4.b32 {%0, %1, %2, %3}, [%4];" : "=r"(a), "=r"(t0), "=r"(b), "=r"(t1) : "l"(p) : "memory");
    return (t0 ^ tag) | (t1 ^ tag);
}
template <int ID, int N> __device__ __forceinline__ void bar_sync() { asm volatile("bar.sync %0, %1;" ::"n"(ID), "n"(N) : "memory"); }
__device__ __forceinline__ void bar_sync_id(int id, int n) { asm volatile("bar.sync %0, %1;" ::"r"(id), "r"(n) : "memory"); }
template <int ID = 4> __device__ __forceinline__ void gate_wait(uint32_t on) { asm volatile("{\n.reg .pred p;\nsetp.ne.u32 p, %0, 0;\n@p bar.sync %1, 256;\n}" ::"r"(on), "n"(ID) : "memory"); }
template <int ID = 4> __device__ __forceinline__ void gate_open(uint32_t off) { asm volatile("{\n.reg .pred p;\nsetp.eq.u32 p, %0, 0;\n@p bar.arrive %1, 256;\n}" ::"r"(off), "n"(ID) : "memory"); }
__device__ __forceinline__ void wg_fence() { asm volatile("wgmma.fence.sync.aligned;" ::: "memory"); }
__device__ __forceinline__ void wg_commit() { asm volatile("wgmma.commit_group.sync.aligned;" ::: "memory"); }
template <int N> __device__ __forceinline__ void wg_wait() { asm volatile("wgmma.wait_group.sync.aligned %0;" ::"n"(N) : "memory"); }
template <int LO = 0, int HI = 56, int N> __device__ __forceinline__ void pin(float (&a)[N]) {
#pragma unroll
    for (int i = LO; i < (HI < N ? HI : N); i++) asm volatile("" : "+f"(a[i])::"memory");
}
__device__ __forceinline__ uint32_t ldg_u16(const void* p) {
    uint32_t v;
    asm volatile("ld.global.nc.u16 %0, [%1];" : "=r"(v) : "l"(p) : "memory");
    return v;
}
__device__ __forceinline__ uint32_t pack2(float lo, float hi) { uint32_t r; asm("cvt.rn.bf16x2.f32 %0, %1, %2;" : "=r"(r) : "f"(hi), "f"(lo)); return r; }
__device__ __forceinline__ float bf_lo(uint32_t v) { return __uint_as_float(v << 16); }
__device__ __forceinline__ float bf_hi(uint32_t v) { return __uint_as_float(v & 0xFFFF0000u); }
__device__ __forceinline__ uint32_t split2(float x) { return pack2(x, x - bf_lo(pack2(x, 0.f))); }
__device__ __forceinline__ void stsm4(uint32_t a, uint32_t r0, uint32_t r1, uint32_t r2, uint32_t r3) {
    asm volatile("stmatrix.sync.aligned.m8n8.x4.shared.b16 [%0], {%1, %2, %3, %4};" ::"r"(a), "r"(r0), "r"(r1), "r"(r2), "r"(r3) : "memory");
}
__device__ __forceinline__ void stsm2(uint32_t a, uint32_t r0, uint32_t r1) {
    asm volatile("stmatrix.sync.aligned.m8n8.x2.shared.b16 [%0], {%1, %2};" ::"r"(a), "r"(r0), "r"(r1) : "memory");
}
__device__ __forceinline__ void ldsm4(uint32_t a, uint32_t (&r)[4]) {
    asm volatile("ldmatrix.sync.aligned.m8n8.x4.shared.b16 {%0, %1, %2, %3}, [%4];" : "=r"(r[0]), "=r"(r[1]), "=r"(r[2]), "=r"(r[3]) : "r"(a) : "memory");
}
__device__ __forceinline__ void ldsm4t(uint32_t a, uint32_t (&r)[4]) {
    asm volatile("ldmatrix.sync.aligned.m8n8.x4.trans.shared.b16 {%0, %1, %2, %3}, [%4];" : "=r"(r[0]), "=r"(r[1]), "=r"(r[2]), "=r"(r[3]) : "r"(a) : "memory");
}
__device__ __forceinline__ void mma16816(float (&c)[4], uint32_t a0, uint32_t a1, uint32_t a2, uint32_t a3, uint32_t b0, uint32_t b1) {
    asm volatile("mma.sync.aligned.m16n8k16.row.col.f32.bf16.bf16.f32 {%0,%1,%2,%3}, {%4,%5,%6,%7}, {%8,%9}, {%0,%1,%2,%3};"
                 : "+f"(c[0]), "+f"(c[1]), "+f"(c[2]), "+f"(c[3]) : "r"(a0), "r"(a1), "r"(a2), "r"(a3), "r"(b0), "r"(b1));
}
__device__ __forceinline__ void mma1688(float (&c)[4], uint32_t a0, uint32_t a1, uint32_t b0) {
    asm volatile("mma.sync.aligned.m16n8k8.row.col.f32.bf16.bf16.f32 {%0,%1,%2,%3}, {%4,%5}, {%6}, {%0,%1,%2,%3};"
                 : "+f"(c[0]), "+f"(c[1]), "+f"(c[2]), "+f"(c[3]) : "r"(a0), "r"(a1), "r"(b0));
}
constexpr uint32_t SB0 = 1024;
__device__ __forceinline__ uint32_t desc_lo(uint32_t off, uint32_t lbo) { return ((SB0 + off) >> 4) + ((lbo >> 4) << 16); }
constexpr uint32_t H_SW = (1024 >> 4) | (1u << 30), H_H = 128 >> 4, H_U = 1024 >> 4;
__device__ __forceinline__ float ex2(float x) { float r; asm("ex2.approx.ftz.f32 %0, %1;" : "=f"(r) : "f"(x)); return r; }
__device__ __forceinline__ float rsq(float x) { float r; asm("rsqrt.approx.ftz.f32 %0, %1;" : "=f"(r) : "f"(x)); return r; }
__device__ __forceinline__ float rcp(float x) { float r; asm("rcp.approx.ftz.f32 %0, %1;" : "=f"(r) : "f"(x)); return r; }
__device__ __forceinline__ float gelu_half(float h) {
    float y = h * fmaf(h * h, 8.f * 0.0356774081363f, 2.f * 0.7978845608029f), t;
    asm("tanh.approx.f32 %0, %1;" : "=f"(t) : "f"(y));
    return fmaf(h, t, h);
}

template <uint32_t HB, int TB>
__device__ __forceinline__ void wgmma_n56_rs(float (&d)[28], const uint32_t (&a)[4], uint32_t lb, int scale_d) {
    asm volatile("{\n.reg .pred p;\n.reg .b64 db;\nsetp.ne.b32 p, %33, 0;\nmov.b64 db, {%32, %34};\n"
        "wgmma.mma_async.sync.aligned.m64n56k16.f32.bf16.bf16 "
        "{%0, %1, %2, %3, %4, %5, %6, %7, %8, %9, %10, %11, %12, %13, %14, %15, %16, %17, %18, %19, %20, %21, %22, %23, %24, %25, %26, %27}, "
        "{%28, %29, %30, %31}, db, p, 1, 1, %35;\n}\n"
        : "+f"(d[0]), "+f"(d[1]), "+f"(d[2]), "+f"(d[3]), "+f"(d[4]), "+f"(d[5]), "+f"(d[6]), "+f"(d[7]), "+f"(d[8]), "+f"(d[9]), "+f"(d[10]), "+f"(d[11]), "+f"(d[12]), "+f"(d[13]), "+f"(d[14]), "+f"(d[15]), "+f"(d[16]), "+f"(d[17]), "+f"(d[18]), "+f"(d[19]), "+f"(d[20]), "+f"(d[21]), "+f"(d[22]), "+f"(d[23]), "+f"(d[24]), "+f"(d[25]), "+f"(d[26]), "+f"(d[27])
        : "r"(a[0]), "r"(a[1]), "r"(a[2]), "r"(a[3]), "r"(lb), "r"(scale_d), "n"(HB), "n"(TB));
}
template <int TA, uint32_t HA, uint32_t HB>
__device__ __forceinline__ void wgmma_n112(float (&d)[56], uint32_t la, uint32_t lb, int scale_d = 1) {
    asm volatile("{\n.reg .b64 da, db;\n.reg .pred p;\nsetp.ne.b32 p, %61, 0;\nmov.b64 da, {%56, %59};\nmov.b64 db, {%57, %60};\n"
        "wgmma.mma_async.sync.aligned.m64n112k16.f32.bf16.bf16 "
        "{%0, %1, %2, %3, %4, %5, %6, %7, %8, %9, %10, %11, %12, %13, %14, %15, %16, %17, %18, %19, %20, %21, %22, %23, %24, %25, %26, %27, %28, %29, %30, %31, %32, %33, %34, %35, %36, %37, %38, %39, %40, %41, %42, %43, %44, %45, %46, %47, %48, %49, %50, %51, %52, %53, %54, %55}, "
        "da, db, p, 1, 1, %58, 1;\n}\n"
        : "+f"(d[0]), "+f"(d[1]), "+f"(d[2]), "+f"(d[3]), "+f"(d[4]), "+f"(d[5]), "+f"(d[6]), "+f"(d[7]), "+f"(d[8]), "+f"(d[9]), "+f"(d[10]), "+f"(d[11]), "+f"(d[12]), "+f"(d[13]), "+f"(d[14]), "+f"(d[15]), "+f"(d[16]), "+f"(d[17]), "+f"(d[18]), "+f"(d[19]), "+f"(d[20]), "+f"(d[21]), "+f"(d[22]), "+f"(d[23]), "+f"(d[24]), "+f"(d[25]), "+f"(d[26]), "+f"(d[27]), "+f"(d[28]), "+f"(d[29]), "+f"(d[30]), "+f"(d[31]), "+f"(d[32]), "+f"(d[33]), "+f"(d[34]), "+f"(d[35]), "+f"(d[36]), "+f"(d[37]), "+f"(d[38]), "+f"(d[39]), "+f"(d[40]), "+f"(d[41]), "+f"(d[42]), "+f"(d[43]), "+f"(d[44]), "+f"(d[45]), "+f"(d[46]), "+f"(d[47]), "+f"(d[48]), "+f"(d[49]), "+f"(d[50]), "+f"(d[51]), "+f"(d[52]), "+f"(d[53]), "+f"(d[54]), "+f"(d[55])
        : "r"(la), "r"(lb), "n"(TA), "n"(HA), "n"(HB), "r"(scale_d));
}
template <int TA, uint32_t HA, uint32_t HB>
__device__ __forceinline__ void wgmma_n64(float (&d)[32], uint32_t la, uint32_t lb, int scale_d = 1) {
    asm volatile("{\n.reg .b64 da, db;\n.reg .pred p;\nsetp.ne.b32 p, %37, 0;\nmov.b64 da, {%32, %35};\nmov.b64 db, {%33, %36};\n"
        "wgmma.mma_async.sync.aligned.m64n64k16.f32.bf16.bf16 "
        "{%0, %1, %2, %3, %4, %5, %6, %7, %8, %9, %10, %11, %12, %13, %14, %15, %16, %17, %18, %19, %20, %21, %22, %23, %24, %25, %26, %27, %28, %29, %30, %31}, "
        "da, db, p, 1, 1, %34, 1;\n}\n"
        : "+f"(d[0]), "+f"(d[1]), "+f"(d[2]), "+f"(d[3]), "+f"(d[4]), "+f"(d[5]), "+f"(d[6]), "+f"(d[7]), "+f"(d[8]), "+f"(d[9]), "+f"(d[10]), "+f"(d[11]), "+f"(d[12]), "+f"(d[13]), "+f"(d[14]), "+f"(d[15]), "+f"(d[16]), "+f"(d[17]), "+f"(d[18]), "+f"(d[19]), "+f"(d[20]), "+f"(d[21]), "+f"(d[22]), "+f"(d[23]), "+f"(d[24]), "+f"(d[25]), "+f"(d[26]), "+f"(d[27]), "+f"(d[28]), "+f"(d[29]), "+f"(d[30]), "+f"(d[31])
        : "r"(la), "r"(lb), "n"(TA), "n"(HA), "n"(HB), "r"(scale_d));
}
template <int TA, uint32_t HA, uint32_t HB>
__device__ __forceinline__ void wgmma_n56(float (&d)[28], uint32_t la, uint32_t lb, int scale_d = 1) {
    asm volatile("{\n.reg .b64 da, db;\n.reg .pred p;\nsetp.ne.b32 p, %33, 0;\nmov.b64 da, {%28, %31};\nmov.b64 db, {%29, %32};\n"
        "wgmma.mma_async.sync.aligned.m64n56k16.f32.bf16.bf16 "
        "{%0, %1, %2, %3, %4, %5, %6, %7, %8, %9, %10, %11, %12, %13, %14, %15, %16, %17, %18, %19, %20, %21, %22, %23, %24, %25, %26, %27}, "
        "da, db, p, 1, 1, %30, 1;\n}\n"
        : "+f"(d[0]), "+f"(d[1]), "+f"(d[2]), "+f"(d[3]), "+f"(d[4]), "+f"(d[5]), "+f"(d[6]), "+f"(d[7]), "+f"(d[8]), "+f"(d[9]), "+f"(d[10]), "+f"(d[11]), "+f"(d[12]), "+f"(d[13]), "+f"(d[14]), "+f"(d[15]), "+f"(d[16]), "+f"(d[17]), "+f"(d[18]), "+f"(d[19]), "+f"(d[20]), "+f"(d[21]), "+f"(d[22]), "+f"(d[23]), "+f"(d[24]), "+f"(d[25]), "+f"(d[26]), "+f"(d[27])
        : "r"(la), "r"(lb), "n"(TA), "n"(HA), "n"(HB), "r"(scale_d));
}
template <int TA, uint32_t HA, uint32_t HB>
__device__ __forceinline__ void wgmma_n48(float (&d)[24], uint32_t la, uint32_t lb, int scale_d = 1) {
    asm volatile("{\n.reg .b64 da, db;\n.reg .pred p;\nsetp.ne.b32 p, %29, 0;\nmov.b64 da, {%24, %27};\nmov.b64 db, {%25, %28};\n"
        "wgmma.mma_async.sync.aligned.m64n48k16.f32.bf16.bf16 "
        "{%0, %1, %2, %3, %4, %5, %6, %7, %8, %9, %10, %11, %12, %13, %14, %15, %16, %17, %18, %19, %20, %21, %22, %23}, "
        "da, db, p, 1, 1, %26, 1;\n}\n"
        : "+f"(d[0]), "+f"(d[1]), "+f"(d[2]), "+f"(d[3]), "+f"(d[4]), "+f"(d[5]), "+f"(d[6]), "+f"(d[7]), "+f"(d[8]), "+f"(d[9]), "+f"(d[10]), "+f"(d[11]), "+f"(d[12]), "+f"(d[13]), "+f"(d[14]), "+f"(d[15]), "+f"(d[16]), "+f"(d[17]), "+f"(d[18]), "+f"(d[19]), "+f"(d[20]), "+f"(d[21]), "+f"(d[22]), "+f"(d[23])
        : "r"(la), "r"(lb), "n"(TA), "n"(HA), "n"(HB), "r"(scale_d));
}
template <int TA, uint32_t HA, uint32_t HB>
__device__ __forceinline__ void wgmma_n8(float (&d)[4], uint32_t la, uint32_t lb, int scale_d = 1) {
    asm volatile("{\n.reg .b64 da, db;\n.reg .pred p;\nsetp.ne.b32 p, %9, 0;\nmov.b64 da, {%4, %7};\nmov.b64 db, {%5, %8};\n"
        "wgmma.mma_async.sync.aligned.m64n8k16.f32.bf16.bf16 "
        "{%0, %1, %2, %3}, "
        "da, db, p, 1, 1, %6, 1;\n}\n"
        : "+f"(d[0]), "+f"(d[1]), "+f"(d[2]), "+f"(d[3])
        : "r"(la), "r"(lb), "n"(TA), "n"(HA), "n"(HB), "r"(scale_d));
}

__device__ __forceinline__ void send8(const float* a, uint32_t rbuf, uint32_t rbar, uint32_t on) {
    asm volatile("{\n.reg .pred p;\nsetp.ne.u32 p, %6, 0;\n@p st.async.weak.shared::cluster.mbarrier::complete_tx::bytes.v4.b32 [%0], {%1,%2,%3,%4}, [%5];\n}"
                 ::"r"(rbuf), "r"(pack2(a[0], a[1])), "r"(pack2(a[2], a[3])), "r"(pack2(a[4], a[5])), "r"(pack2(a[6], a[7])), "r"(rbar), "r"(on) : "memory");
}
__device__ __forceinline__ void send_half(const float (&a)[56], uint32_t rbuf, uint32_t rbar, int t, uint32_t on) {
#pragma unroll
    for (int i = 0; i < 3; i++) send8(a + 28 + 8 * i, rbuf + i * 2048 + t * 16, rbar, on);
    asm volatile("{\n.reg .pred p;\nsetp.ne.u32 p, %4, 0;\n@p st.async.weak.shared::cluster.mbarrier::complete_tx::bytes.v2.b32 [%0], {%1,%2}, [%3];\n}"
                 ::"r"(rbuf + 6144 + t * 8), "r"(pack2(a[52], a[53])), "r"(pack2(a[54], a[55])), "r"(rbar), "r"(on) : "memory");
}
__device__ __forceinline__ void recv_half(uint32_t (&p)[14], uint32_t buf, int t) {
#pragma unroll
    for (int i = 0; i < 3; i++)
        asm volatile("ld.shared.v4.b32 {%0,%1,%2,%3}, [%4];" : "=r"(p[4 * i]), "=r"(p[4 * i + 1]), "=r"(p[4 * i + 2]), "=r"(p[4 * i + 3]) : "r"(buf + i * 2048 + t * 16) : "memory");
    asm volatile("ld.shared.v2.b32 {%0,%1}, [%2];" : "=r"(p[12]), "=r"(p[13]) : "r"(buf + 6144 + t * 8) : "memory");
}

struct Maps { CUtensorMap xl, x, wqkv, hst, w1, w2, xn, old_, ost, wo; };

__global__ void __cluster_dims__(2, 1, 1) __launch_bounds__(512, 1)
fused_kernel(const __nv_bfloat16* __restrict__ x, const __nv_bfloat16* __restrict__ wqkv,
             const __nv_bfloat16* __restrict__ b1, const __nv_bfloat16* __restrict__ b2, uint8_t* __restrict__ scr,
             uint8_t* __restrict__ out, const __grid_constant__ Maps mp) {
    extern __shared__ __align__(1024) uint8_t smem[];
    const uint32_t sb = smem_u32(smem);
    const uint32_t bar = sb + OFF_BAR;
    const int tid = threadIdx.x, lane = tid & 31;
    const int b = blockIdx.x, z = b & 1, c = b >> 1;
    unsigned* const ctr = reinterpret_cast<unsigned*>(scr + G_CTR);
    if (tid < 112) l2_prefetch(reinterpret_cast<const uint8_t*>(x) + (b * 112 + tid) * 128);
    const int wline = (tid & 127) * 128 + b;
    const bool wfirst = ((wline / 1344) & ~ROT) == 0;
    if (PFW && (tid >> 7) == 1 && wline < 9408 && wfirst) l2_prefetch(reinterpret_cast<const uint8_t*>(wqkv) + wline * 128);
    const uint32_t t_in = clock32();
    TS0(0);
    TG(60);
    const int warp = __shfl_sync(0xffffffffu, tid >> 5, 0);
    int q, j;
    if (c < 4) { q = 15; j = c; } else if (c < 36) { q = (c - 4) & 7; j = (c - 4) >> 3; } else { q = 8 + (c - 36) % 7; j = (c - 36) / 7; }
    const bool g1 = q < 14;
    const int R = q < 8 ? q : q == 15 ? 2 : q < 10 ? q - 8 : q - 7, P = (q >> 3) * 4 + j;
    auto krow = [&](int kb) { const int k = kb + (R & ROT); return (k >= 7 ? k - 7 : k) * 64; };
    auto x_load = [&](int kb) {
        mbar_expect(bar + 8 * (B_FULLQ + kb), 40960);
        tma2d(sb + OFF_A + ((XSLOT >> (4 * kb)) & 7) * 16384, &mp.x, z * D_ + krow(kb), R * 128, bar + 8 * (B_FULLQ + kb));
    };
    auto w_load = [&](int kb) {
        tma3d_mc(sb + OFF_B + ((WSLOT >> (4 * kb)) & 7) * 24576 + z * 12288, &mp.wqkv, (P * 56) & ~15, krow(kb) + z * 32, 0, bar + 8 * (B_FULLQ + kb));
    };
    if (warp == 12 && elect()) {
#pragma unroll
        for (int i = B_FULLQ; i < B_EMPTYQ; i++) mbar_init(bar + 8 * i, 1);
        mbar_expect(bar + 8 * B_LNIN, BLK);
        tma3d(sb + OFF_A, &mp.xl, 0, 16 * b, 0, bar + 8 * B_LNIN);
        x_load(0);
        TS(15);
    }
    if (warp == 13 && elect()) {
#pragma unroll
        for (int i = B_EMPTYQ; i < B_COUNT; i++)
            mbar_init(bar + 8 * i, i < B_FULL ? (i < B_EMPTYQ + 2 ? 16 : 8) + (((i - B_EMPTYQ) & ~1) == (R & 6 & ~ROT) ? 8 : 0)
                                   : i < B_EMPTY || i == B_FREE ? 2 : (i < B_AUX || i == B_NONE || i == B_OST) ? 8 : i == B_KV ? 12
                                   : (i == B_AUX || i == B_HALO) ? 4 : 1);
#pragma unroll
        for (int i = B_RECV1; i < B_GOH; i++) mbar_expect(bar + 8 * i, i < B_RECV2 ? 7168 : 8192 - 2048 * z);
    }
    asm volatile("fence.mbarrier_init.release.cluster;" ::: "memory");
    __syncwarp();
    asm volatile("barrier.cluster.arrive.relaxed.aligned;\nbarrier.cluster.wait.aligned;" ::: "memory");
    if (W0 && warp == 12 && elect()) { w_load(0); TS(16); }
    auto slot = [](uint32_t r) { return r - 6 * ((r * 43) >> 8); };
    auto phase = [](uint32_t r) { return ((r * 43) >> 8) & 1; };
    const uint32_t r_o = g1 ? 16 : 0, r_u = r_o + 4;
    auto fetch_x = [&](uint32_t r, bool arm = true) {
        const uint32_t s = slot(r), lb = bar + 8 * (B_LAND + s), i = r - r_o;
        if (arm) mbar_expect(lb, i < 4 ? 16384 : BLK);
        if (i < 4) tma2d(sb + OFF_A + s * 16384, &mp.old_, 0, (4 * z + i) * S_ + q * 128, lb);
        else bulk_load(sb + OFF_B + s * BLK, scr + G_BIMG + ((14 * z + (i < 11 ? 2 * i : 2 * i - 13)) * 4 + j) * BLK, BLK, lb);
    };
    auto epoch = [&]() { mbar_wait(bar + 8 * B_EP, 0); return *reinterpret_cast<volatile unsigned*>(smem + OFF_EP); };

    if (warp < 8) {
        const int wg = warp >> 2, w4 = warp & 3, t = tid & 127, g = lane >> 2, tq = lane & 3;
        asm volatile("setmaxnreg.inc.sync.aligned.u32 208;");
        uint32_t xa[4];
#pragma unroll
        for (int k = 0; k < 4; k++) xa[k] = sb + OFF_A + (warp * 16 + (lane & 15)) * 128 + (((2 * k + (lane >> 4)) ^ (lane & 7)) << 4);
        {
            const int rg = warp & 1, jq = warp >> 1;
            const uint32_t ex = sb + OFF_LNX + (rg * 8 + g) * 32, ew = ex + jq * 8, ls = sb + OFF_LNST + (rg * 8 + g) * 8;
            uint32_t r[4][4], la[4], ha[4], dep = ex | ew | ls;
#pragma unroll
            for (int i = 0; i < 4; i++) {
                const int cg = 14 * jq + 4 * i + ((lane >> 3) & (i < 3 ? 3 : 1));
                la[i] = sb + OFF_A + (cg >> 3) * 2048 + rg * 1024 + (lane & 7) * 128 + (((cg ^ lane) & 7) << 4);
                int pos = 4 * i + (lane >> 3) + (b >= 64 ? 7 : 0);
                if (pos >= 14) pos -= 14;
                ha[i] = sb + OFF_A + jq * 3584 + rg * 1792 + (lane & 7) * 16 + pos * 128;
                dep |= la[i] | xa[i] | ha[i];
            }
            mbar_wait(bar + 8 * B_LNIN, dep >> 31);
#pragma unroll
            for (int i = 0; i < 4; i++) ldsm4(la[i], r[i]);
            float rs[4] = {0.f, 0.f, 0.f, 0.f}, rt[4] = {0.f, 0.f, 0.f, 0.f}, sq[4], v[28];
            const float sh = bf_lo(__shfl_sync(0xffffffffu, r[0][0], lane & 28));
            mma16816(rs, r[0][0], r[0][1], r[0][2], r[0][3], 0x3F803F80u, 0x3F803F80u);
            mma16816(rt, r[1][0], r[1][1], r[1][2], r[1][3], 0x3F803F80u, 0x3F803F80u);
            mma16816(rs, r[2][0], r[2][1], r[2][2], r[2][3], 0x3F803F80u, 0x3F803F80u);
            mma1688(rt, r[3][0], r[3][1], 0x3F803F80u);
#pragma unroll
            for (int n = 0; n < 14; n++) { v[2 * n] = bf_lo(r[n >> 2][n & 3]) - sh; v[2 * n + 1] = bf_hi(r[n >> 2][n & 3]) - sh; }
#pragma unroll
            for (int n = 0; n < 28; n++) sq[n & 3] = n < 4 ? v[n] * v[n] : fmaf(v[n], v[n], sq[n & 3]);
            const float mq = ((rs[0] + rs[2]) + (rt[0] + rt[2])) * (1.f / 112), dq = mq - sh;
            float m2 = fmaf(-28.f * dq, dq, (sq[0] + sq[1]) + (sq[2] + sq[3]));
            m2 += __shfl_xor_sync(0xffffffffu, m2, 1);
            m2 += __shfl_xor_sync(0xffffffffu, m2, 2);
            asm volatile("st.shared.v2.f32 [%0], {%1, %2};" ::"r"(ew), "f"(mq), "f"(m2) : "memory");
            bar_sync<1, 256>();
            float4 e0, e1;
            asm volatile("ld.shared.v4.f32 {%0,%1,%2,%3}, [%4];" : "=f"(e0.x), "=f"(e0.y), "=f"(e0.z), "=f"(e0.w) : "r"(ex) : "memory");
            asm volatile("ld.shared.v4.f32 {%0,%1,%2,%3}, [%4];" : "=f"(e1.x), "=f"(e1.y), "=f"(e1.z), "=f"(e1.w) : "r"(ex + 16) : "memory");
            const float mean = 0.25f * ((e0.x + e0.z) + (e1.x + e1.z));
            const float d0 = e0.x - mean, d1 = e0.z - mean, d2 = e1.x - mean, d3 = e1.z - mean;
            const float var = fmaxf(((e0.y + e0.w) + (e1.y + e1.w)) * (1.f / D_) + 0.25f * (fmaf(d0, d0, d1 * d1) + fmaf(d2, d2, d3 * d3)), 0.f);
            const float r1 = rsq(var + 1e-5f), sc = rsq(fmaf(1e-5f, var + 1e-5f, var)), of = (sh - mean) * sc;
#pragma unroll
            for (int n = 0; n < 14; n++) r[n >> 2][n & 3] = pack2(fmaf(v[2 * n], sc, of), fmaf(v[2 * n + 1], sc, of));
#pragma unroll
            for (int i = 0; i < 3; i++) stsm4(ha[i], r[i][0], r[i][1], r[i][2], r[i][3]);
            stsm2(ha[3], r[3][0], r[3][1]);
            asm volatile("st.shared.v2.b32 [%0], {%1, %2};" ::"r"(ls), "r"(__float_as_uint(r1)), "r"(split2(-mean)) : "memory");
            TS0(24);
            asm volatile("bar.arrive 10, 288;" ::: "memory");
        }
        float a1[56];
        float rq[2], hb1[2], fb2[2];
        uint32_t qp[14], kp[14];
        const uint32_t ka = sb + OFF_K + warp * 896 + (lane & 7) * 112 + (lane >> 3) * 16;
        const uint32_t va = sb + OFF_V + (warp * 16 + (lane & 15)) * 112 + (lane >> 4) * 16;
        const uint32_t sta = sb + OFF_RSTD + warp * 64 + tq * 8;
        const uint32_t dA = desc_lo(OFF_A + wg * 8192, 16), dH = desc_lo(OFF_B, 1792), dU = desc_lo(OFF_B, 128);
        auto release = [&](uint32_t a) { mbar_arrive_if0(a, lane); };
        auto sched_fence = [&]() { mbar_wait(bar + 8 * B_LNIN, 0); };
        uint32_t rel = bar + 8 * (B_EMPTYQ + 6);
        auto g1_run = [&](uint32_t r0, uint32_t r1, int gate = 0) {
#pragma unroll 1
            for (uint32_t r = g1 ? r0 : r1; r < r1; r++) {
                const uint32_t s = slot(r), n = min(r + 1, 15u);
                if (gate == 4) gate_wait(wg && r == r0);
                if (TSG1) TSD(64 + r);
                wg_fence();
#pragma unroll
                for (int k = 0; k < 4; k++) wgmma_n112<1, H_SW, H_H>(a1, dA + s * 1024 + k * 128, dH + s * 896 + k * 224, k ? 1 : r);
                wg_commit();
                wg_wait<1>();
                release(rel);
                rel = bar + 8 * (B_EMPTY + s);
                mbar_wait(bar + 8 * (B_FULL + slot(n)), phase(n));
            }
        };
        uint32_t solo = g1 && wg == SW;
        asm volatile("" : "+r"(solo));
        solo = __shfl_sync(0xffffffffu, solo, 0);
        auto g1_wait = [&](uint32_t r) { mbar_wait(bar + 8 * (g1 ? B_FULL + r % 6 : B_LNIN), g1 && ((r / 6) & 1)); };
        auto g1_one = [&](uint32_t r) {
#pragma unroll 1
            for (uint32_t n = 0; n < solo; n++) {
                if (TSG1) TSD(64 + r);
                wg_fence();
#pragma unroll
                for (int k = 0; k < 4; k++) wgmma_n112<1, H_SW, H_H>(a1, dA + r % 6 * 1024 + k * 128, dH + r % 6 * 896 + k * 224);
                wg_commit();
                wg_wait<1>();
                release(rel);
                rel = bar + 8 * (B_EMPTY + r % 6);
            }
        };
        auto drain = [&]() { wg_wait<0>(); release(rel); rel = bar + 8 * B_NONE; };
        {
            float aq0[28], aq1[28], aq2[28];
            const uint32_t dW = desc_lo(OFF_B + (P & 1) * 16, 16);
            uint32_t xf[2][4][4];
            const uint32_t rb = mapa(bar + 8 * (B_EMPTYQ - 1), z ^ 1);
            auto fetch = [&](int kb, uint32_t (&f)[4][4]) {
                if (TSG1) TSD(178 + kb);
                mbar_wait(bar + 8 * (B_FULLQ + kb), 0);
                if (TSG1) TSD(170 + kb);
#pragma unroll
                for (int k = 0; k < 4; k++) ldsm4(xa[k] + ((XSLOT >> (4 * kb)) & 7) * 16384, f[k]);
            };
            auto mma = [&](int kb, uint32_t (&f)[4][4], int k0, int k1) {
                const uint32_t d0 = dW + ((WSLOT >> (4 * kb)) & 7) * 1536;
                wg_fence();
#pragma unroll
                for (int k = k0; k < k1; k++) {
                    const uint32_t d = d0 + (k >> 1) * 768 + (k & 1) * 128;
                    const int sc = k > 0 ? 1 : kb;
                    wgmma_n56_rs<H_SW, 1>(aq0, f[k], d, sc);
                    wgmma_n56_rs<H_SW, 1>(aq1, f[k], d + 256, sc);
                    wgmma_n56_rs<H_SW, 1>(aq2, f[k], d + 512, sc);
                }
            };
            auto retire = [&](int kb) {
                wg_commit();
                wg_wait<1>();
                mbar_arrive_if0(bar + 8 * (B_EMPTYQ + kb - 1), lane | (kb < 1));
                asm volatile("{\n.reg .pred p;\nsetp.eq.u32 p, %1, 0;\n@p mbarrier.arrive.shared::cluster.b64 _, [%0];\n}"
                             ::"r"(rb + 8 * kb), "r"(lane | ((uint32_t)(kb - 1) > 1)) : "memory");
            };
            auto stage = [&](int kb, uint32_t (&f)[4][4], uint32_t (&n)[4][4]) {
                mma(kb, f, 0, KS);
                retire(kb);
                fetch(kb + 1, n);
                if (KS < 4) { mma(kb, f, KS, 4); wg_commit(); }
            };
            fetch(0, xf[0]);
#pragma unroll kQUnroll
            for (int kb = 0; kb < 6; kb += 2) {
                stage(kb, xf[0], xf[1]);
                stage(kb + 1, xf[1], xf[0]);
            }
            mma(6, xf[0], 0, KS);
            retire(6);
            TS0(2);
            mbar_wait(bar + 8 * B_AUX, 0);
            {
                uint32_t (&f)[4] = xf[1][0];
                const uint2* mt = reinterpret_cast<const uint2*>(smem + OFF_STATS) + warp * 16 + g;
                const uint2 m0 = mt[0], m1 = mt[8];
                const uint32_t sel = tq == 0 ? 0x1010 : tq == 1 ? 0x3232 : 0x4444;
                f[0] = __byte_perm(m0.y, 0, sel); f[1] = __byte_perm(m1.y, 0, sel); f[2] = f[3] = 0;
                rq[0] = __uint_as_float(m0.x); rq[1] = __uint_as_float(m1.x);
                asm volatile("" : "+r"(f[0]), "+r"(f[1]), "+r"(f[2]), "+r"(f[3])::"memory");
                const uint32_t d = desc_lo(OFF_CSB + (P & 1) * 128, 0);
                mma(6, xf[0], KS, 4);
                wgmma_n56_rs<H_H, 0>(aq1, f, d + 64, 1);
                wgmma_n56_rs<H_H, 0>(aq2, f, d + 128, 1);
                wgmma_n56_rs<H_H, 0>(aq0, f, d, 1);
                wg_commit();
            }
            g1_wait(0);
            g1_run(0, wg ? 0 : NE);
            drain();
            pin(aq0); pin(aq1); pin(aq2);
            TSW(3);
            mbar_wait(bar + 8 * (B_EMPTYQ + 5), 0);
#pragma unroll
            for (int i = 0; i < 14; i++) { kp[i] = pack2(aq1[2 * i], aq1[2 * i + 1]); qp[i] = pack2(aq2[2 * i], aq2[2 * i + 1]); }
            stsm4(ka + 896, kp[1], kp[3], kp[5], kp[7]);
            stsm4(ka + 896 + 48, kp[7], kp[9], kp[11], kp[13]);
#pragma unroll
            for (int n = 0; n < 3; n++) stsm4(va + 896 + n * 32, qp[4 * n], qp[4 * n + 1], qp[4 * n + 2], qp[4 * n + 3]);
            stsm2(va + 896 + 96, qp[12], qp[13]);
            __syncwarp();
            mbar_arrive_if0(bar + 8 * B_QKV, tid - 224);
            release(bar + 8 * B_KV);
#pragma unroll
            for (int i = 0; i < 14; i++) qp[i] = pack2(aq0[2 * i], aq0[2 * i + 1]);
            TSW(4);
        }
        g1_run(wg ? 0 : NE, wg ? PRE1 : PRE0);
        {
            uint32_t kf[2][3][4], vf[2][3][4];
            const bool up0 = 2 * tq > g, up1 = 2 * tq + 1 > g, edge = (R | warp) == 0;
            float rk[2][2], fs[2][2], rs[3][2];
            mbar_wait(bar + 8 * (warp ? B_KV : B_HALO), 0);
            const uint32_t tag = *reinterpret_cast<volatile unsigned*>(smem + OFF_EP);
#pragma unroll
            for (int i = 0; i < 2; i++)
                asm volatile("ld.shared.v2.f32 {%0,%1}, [%2];" : "=f"(hb1[i]), "=f"(fb2[i]) : "r"(sb + OFF_BIAS + (warp * 16 + g + 8 * i) * 8) : "memory");
#pragma unroll
            for (int i = 0; i < 3; i++)
                asm volatile("ld.shared.v2.f32 {%0,%1}, [%2];" : "=f"(rs[i][0]), "=f"(rs[i][1]) : "r"(sta + i * 32) : "memory");
#pragma unroll
            for (int hd = 0; hd < 2; hd++) {
                ldsm4(ka + hd * 48, kf[hd][0]);
#pragma unroll
                for (int i = 0; i < 4; i++) { kf[hd][1][i] = kp[6 * hd + 2 * i]; kf[hd][2][i] = kp[6 * hd + 2 * i + 1]; }
                ldsm4t(va + hd * 48, vf[hd][0]); ldsm4t(va + hd * 48 + 32, vf[hd][1]);
                ldsm4t(ka + (OFF_V - OFF_K) + warp * 896 + hd * 48 + 1792, vf[hd][2]);
            }
            const uint32_t q0l = tq < 2 ? qp[6] : 0, q0h = tq < 2 ? qp[7] : 0, q1l = tq < 2 ? 0 : qp[6], q1h = tq < 2 ? 0 : qp[7];
            const uint32_t mk = (up0 ? 0xFFFFu : 0u) | (up1 ? 0xFFFF0000u : 0u);
            TSW(7);
            g1_run(wg ? PRE1 : PRE0, ATT_STEP);
#pragma unroll
            for (int i = 0; i < 4; i++) {
                rk[i >> 1][i & 1] = ((i & 1) ? up1 : up0) ? rs[i >> 1][i & 1] : rs[(i >> 1) + 1][i & 1];
                fs[i >> 1][i & 1] = rk[i >> 1][i & 1] * (rq[i >> 1] * (0.18898223650461362f * 1.4426950408889634f));
                asm volatile("" : "+f"(fs[i >> 1][i & 1])::"memory");
            }
            drain();
            sched_fence();
            TS0(19);
            float sc[2][3][4];
#pragma unroll
            for (int u = 0; u < 3; u++) {
#pragma unroll
                for (int i = 0; i < 8; i++) sc[i >> 2][u][i & 3] = 0.f;
                mma16816(sc[0][u], qp[0], qp[1], qp[2], qp[3], kf[0][u][0], kf[0][u][1]);
                mma16816(sc[1][u], q1l, q1h, qp[8], qp[9], kf[1][u][0], kf[1][u][1]);
            }
#pragma unroll
            for (int u = 0; u < 3; u++) {
                mma16816(sc[0][u], qp[4], qp[5], q0l, q0h, kf[0][u][2], kf[0][u][3]);
                mma16816(sc[1][u], qp[10], qp[11], qp[12], qp[13], kf[1][u][2], kf[1][u][3]);
            }
            float e[2][2][2], mx[2][2], sm[2][4];
#pragma unroll
            for (int hd = 0; hd < 2; hd++) {
                e[hd][0][0] = (up0 ? sc[hd][0][0] : sc[hd][1][0]) * fs[0][0];
                e[hd][0][1] = (up1 ? sc[hd][0][1] : sc[hd][1][1]) * fs[0][1];
                e[hd][1][0] = (up0 ? sc[hd][1][2] : sc[hd][2][2]) * fs[1][0];
                e[hd][1][1] = (up1 ? sc[hd][1][3] : sc[hd][2][3]) * fs[1][1];
                if (edge && up0) e[hd][0][0] = -1e30f;
                if (edge && up1) e[hd][0][1] = -1e30f;
                mx[hd][0] = fmaxf(e[hd][0][0], e[hd][0][1]);
                mx[hd][1] = fmaxf(e[hd][1][0], e[hd][1][1]);
            }
#pragma unroll
            for (int o = 1; o <= 2; o <<= 1)
#pragma unroll
                for (int i = 0; i < 4; i++) mx[i >> 1][i & 1] = fmaxf(mx[i >> 1][i & 1], __shfl_xor_sync(0xffffffffu, mx[i >> 1][i & 1], o));
            uint32_t pp[2][2], pu[2][2];
#pragma unroll
            for (int i = 0; i < 4; i++) {
                const float p0 = ex2(e[i >> 1][i & 1][0] - mx[i >> 1][i & 1]), p1 = ex2(e[i >> 1][i & 1][1] - mx[i >> 1][i & 1]);
                pp[i >> 1][i & 1] = pack2(p0 * rk[i & 1][0], p1 * rk[i & 1][1]);
                pu[i >> 1][i & 1] = pack2(p0, p1);
            }
            float ov[2][4][4];
#pragma unroll
            for (int hd = 0; hd < 2; hd++)
#pragma unroll
                for (int n = 0; n < 4; n++) {
                    ov[hd][n][0] = ov[hd][n][1] = ov[hd][n][2] = ov[hd][n][3] = 0.f;
                    mma16816(ov[hd][n], pp[hd][0] & mk, 0u, pp[hd][0] & ~mk, pp[hd][1] & mk, vf[hd][n >> 1][2 * (n & 1)], vf[hd][n >> 1][2 * (n & 1) + 1]);
                }
#pragma unroll
            for (int hd = 0; hd < 2; hd++) {
                sm[hd][0] = sm[hd][1] = sm[hd][2] = sm[hd][3] = 0.f;
                mma1688(sm[hd], pu[hd][0], pu[hd][1], 0x3F803F80u);
            }
#pragma unroll
            for (int hd = 0; hd < 2; hd++)
#pragma unroll
                for (int n = 0; n < 4; n++) mma1688(ov[hd][n], 0u, pp[hd][1] & ~mk, vf[hd][2][n]);
            sched_fence();
            TS0(18);
            bar_sync<1, 256>();
            g1_one(ATT_STEP);
#pragma unroll
            for (int i = 0; i < 4; i++) asm volatile("" : "+f"(sm[i >> 1][2 * (i & 1)])::"memory");
            uint32_t op[16];
            op[14] = op[15] = tag & 0x3FFF;
#pragma unroll
            for (int i = 0; i < 4; i++) sm[i >> 1][i & 1] = rcp(sm[i >> 1][2 * (i & 1)]);
#pragma unroll
            for (int n = 0; n < 7; n++) {
                const bool hb = n > 3 || (n == 3 && tq >= 2);
#pragma unroll
                for (int h = 0; h < 2; h++) {
                    const float r = hb ? sm[1][h] : sm[0][h];
                    const float x0 = hb ? ov[1][n >= 3 ? n - 3 : 0][2 * h] : ov[0][n <= 3 ? n : 0][2 * h];
                    const float x1 = hb ? ov[1][n >= 3 ? n - 3 : 0][2 * h + 1] : ov[0][n <= 3 ? n : 0][2 * h + 1];
                    op[2 * n + h] = pack2(x0 * r, x1 * r);
                }
            }
#pragma unroll
            for (int i = 0; i < 14; i++) asm volatile("" : "+r"(op[i])::"memory");
            g1_wait(ATT_STEP + 1);
            if (NQ) { g1_one(ATT_STEP + 1); g1_wait(ATT_STEP + 2); }
#pragma unroll
            for (int n = 0; n < 4; n++) stsm4(xa[n] + OFF_OST, op[4 * n], op[4 * n + 1], op[4 * n + 2], op[4 * n + 3]);
            __syncwarp();
            release(bar + 8 * B_OST);
            g1_one(ATT_STEP + 1 + NQ);
            g1_wait(ATT_STEP + 2 + NQ);
            TSW(5);
        }
        const uint32_t peer = z ^ 1;
        if (SW) drain();
        if (!GIN) gate_wait(wg && g1);
        g1_run(wg != SW ? ATT_STEP : ATT_STEP + 2 + NQ, 16, GIN ? 4 : 0);
        if (GIN < 2) gate_open(wg | !g1);
        mbar_wait(bar + 8 * B_FREE, 0);
        drain();
        if (GIN == 2) gate_open(wg | !g1);
        pin(a1);
        TSW(6);
        send_half(a1, mapa(sb + OFF_RECV1 + wg * 7168, peer), mapa(bar + 8 * (B_RECV1 + wg), peer), t, g1);
#pragma unroll
        for (int i = 0; i < 28; i++) a1[i] = fmaf(a1[i], 0.5f, hb1[(i >> 1) & 1]);
        pin<0, 28>(a1);
        float a2[56];
        auto o_run = [&](uint32_t i0, uint32_t i1) {
#pragma unroll 1
            for (uint32_t i = i0; i < i1; i++) {
                const uint32_t s = slot(r_o + i);
                mbar_wait(bar + 8 * (B_FULL + s), phase(r_o + i));
                TSD(64 + 17 + i);
                wg_fence();
#pragma unroll
                for (int k = 0; k < 4; k++) wgmma_n112<0, H_SW, H_U>(a2, dA + s * 1024 + k * 2, dU + s * 896 + k * 16, k ? 1 : i);
                wg_commit();
                wg_wait<1>();
                release(rel);
                rel = bar + 8 * (B_EMPTY + s);
            }
        };
        if (NO1) o_run(0, wg ? NO1 : 0);
        if (g1) {
            uint32_t p[14];
            const int ub = 2 * q + wg, zz = ub >= 14 ? 1 : 0;
            uint8_t* u0 = scr + G_BIMG + ((8 + ub) * 4 + j) * BLK + (7 * z + 6 * zz) * 1024 + w4 * 256 + lane * 4;
            uint8_t* u1 = u0 - (z & zz ? BLK : 0);
            mbar_wait(bar + 8 * (B_RECV1 + wg), (uint32_t)(((uint64_t)u0 | (uint64_t)u1) >> 63));
            TSW(8);
            recv_half(p, sb + OFF_RECV1 + wg * 7168, t);
#pragma unroll
            for (int i = 0; i < 14; i++) {
                stg32((i < 2 ? u0 : u1) + (i >> 1) * 1024 + (i & 1) * 128,
                      pack2(gelu_half(fmaf(bf_lo(p[i]), 0.5f, a1[2 * i])), gelu_half(fmaf(bf_hi(p[i]), 0.5f, a1[2 * i + 1]))));
            }
            TSW(9);
        }
        o_run(wg ? NO1 : 0, 4);
        drain();
        TSW(10);
#pragma unroll 1
        for (uint32_t r = r_u; r < r_u + 14 - NX2; r++) {
            const uint32_t s = slot(r);
            if (!NX2) gate_wait(wg && r == r_u + 14 - NS2);
            mbar_wait(bar + 8 * (B_FULL + s), phase(r));
            TSD(85 + r - r_u);
            wg_fence();
#pragma unroll
            for (int k = 0; k < 4; k++) wgmma_n112<1, H_SW, H_U>(a2, dA + s * 1024 + k * 128, dU + s * 896 + k * 16);
            wg_commit();
            wg_wait<1>();
            release(rel);
            rel = bar + 8 * (B_EMPTY + s);
        }
        uint32_t xr[4][4];
        auto x_fetch = [&]() {
            mbar_wait(bar + 8 * B_XR, 0);
#pragma unroll
            for (int k = 0; k < 4; k++) ldsm4(xa[k] + slot(r_u + 14) * 16384, xr[k]);
        };
        gate_open(wg);
        mbar_wait(bar + 8 * B_UDONE, 0);
        if (XF) x_fetch();
        wg_wait<0>();
        pin(a2);
        TSW(11);
        {
            const uint32_t rbuf = mapa(sb + OFF_RECV2 + wg * 8192 + t * 16, peer) - (z ? 0 : 2048), rbar = mapa(bar + 8 * (B_RECV2 + wg), peer);
#pragma unroll
            for (int i = 3; i >= 0; i--) send8(a2 + 24 + 8 * i, rbuf + i * 2048, rbar, i | z);
            if (!XF && !NX2) x_fetch();
#pragma unroll
            for (int i = 0; i < 32; i++) a2[i] += ((i & 1) ? bf_hi(xr[i >> 3][(i >> 1) & 3]) : bf_lo(xr[i >> 3][(i >> 1) & 3])) + fb2[(i >> 1) & 1];
            pin<0, 32>(a2);
            const uint32_t oa = sb + OFF_OUT + (warp * 16 + (lane >> 3)) * 128 + (((lane ^ (lane >> 3)) & 7) << 4);
            const uint32_t oo = (q * 128 + warp * 16 + (lane >> 3)) * 896 + j * 224 + z * 128 + (lane & 7) * 16;
            uint8_t* og = out + oo;
            mbar_wait(bar + 8 * (B_RECV2 + wg), (oa | oo | (uint32_t)((uint64_t)og >> 32)) >> 31);
            TSW(12);
            uint32_t u[16];
#pragma unroll
            for (int i = 0; i < 4; i++)
                asm volatile("ld.shared.v4.b32 {%0,%1,%2,%3}, [%4];" : "=r"(u[4 * i]), "=r"(u[4 * i + 1]), "=r"(u[4 * i + 2]), "=r"(u[4 * i + 3]) : "r"(sb + OFF_RECV2 + wg * 8192 + i * 2048 + t * 16) : "memory");
#pragma unroll
            for (int e = 0; e < 16; e++) u[e] = pack2(a2[2 * e] + bf_lo(u[e]), a2[2 * e + 1] + bf_hi(u[e]));
#pragma unroll
            for (int i = 0; i < 4; i++) stsm4(xa[i] + OFF_OUT, u[4 * i], u[4 * i + 1], u[4 * i + 2], u[4 * i + 3]);
            __syncwarp();
#pragma unroll
            for (int i = 0; i < 4; i++)
                asm volatile("ld.shared.v4.b32 {%0,%1,%2,%3}, [%4];" : "=r"(u[4 * i]), "=r"(u[4 * i + 1]), "=r"(u[4 * i + 2]), "=r"(u[4 * i + 3]) : "r"((oa ^ ((i & 1) << 6)) + i * 512) : "memory");
            if ((lane & 7) < 8 - 2 * z) {
#pragma unroll
                for (int i = 0; i < 4; i++)
                    asm volatile("st.global.v4.b32 [%0], {%1,%2,%3,%4};" ::"l"(og + i * 3584), "r"(u[4 * i]), "r"(u[4 * i + 1]), "r"(u[4 * i + 2]), "r"(u[4 * i + 3]) : "memory");
            }
        }
        TSW(13);
    } else if (warp < 12) {
        asm volatile("setmaxnreg.dec.sync.aligned.u32 64;");
        const int hw = warp - 8, t = tid & 127;
        reinterpret_cast<uint32_t*>(smem + OFF_ONES)[t] = t < 64 ? 0x3F803F80u : 0;
        fence_async_smem();
        bar_sync<12, 128>();
        while (clock32() - t_in < DLY1) {}
        if (wline < 9408 && !wfirst) l2_prefetch(reinterpret_cast<const uint8_t*>(wqkv) + wline * 128);
        uint8_t* cscell = scr + G_CS + ((P * 8 + R) * 2 + z) * 512 + (t >> 2) * 16;
        if ((lane & 3) == 0) cell_put(cscell, 0, 0, 0);
        uint8_t* cells = scr + G_HALO + ((R * 8 + P) * 2 + z) * 3584 + min(t, 111) * 16;
        cell_put(cells, 0, 0, 0);
        cell_put(cells + 1792, 0, 0, 0);
        const unsigned e1 = epoch();
        const uint32_t bv1 = ldg_u16(b1 + (g1 ? q * 128 : 0) + t), bv2 = ldg_u16(b2 + q * 128 + t);
        {
            const uint32_t da = desc_lo(OFF_B + min((R & 1) * 2 + z, 2) * 4096, 16), db = desc_lo(OFF_ONES, 128);
            float c0[4];
            const int st = R & 6 & ~ROT;
            mbar_wait(bar + 8 * (B_FULLQ + st), 0);
            mbar_wait(bar + 8 * (B_FULLQ + st + 1), 0);
            TSH(47);
            wg_fence();
#pragma unroll
            for (int k = 0; k < 8; k++)
                wgmma_n8<1, H_SW, H_H>(c0, da + ((WSLOT >> (4 * st + (k & 4))) & 7) * 1536 + (k & 2) * 384 + (k & 1) * 128, db + (k >= 4 && R >= 6 ? 16 : 0), k);
            wg_commit();
            wg_wait<0>();
            pin(c0);
            if ((lane & 3) == 0) cell_put(cscell, __float_as_uint(c0[0]), __float_as_uint(c0[2]), e1);
            if (lane < 4) asm volatile("mbarrier.arrive.shared::cluster.b64 _, [%0];" ::"r"(mapa(bar + 8 * (B_EMPTYQ + st + (lane >> 1)), lane & 1)) : "memory");
            TSH(43);
        }
        mbar_wait(bar + 8 * (B_FULLQ + GATHER), 0);
        TSH(39);
        {
            const bool cw = hw < 3;
            const uint8_t* src = cw ? scr + G_CS + P * 8192 + t * 16 : scr + G_STATS + (z * 1024 + R * 128 + lane) * 16;
            uint32_t a[5], d[5], bad;
            do {
                bad = 0;
#pragma unroll
                for (int i = 0; i < 4; i++) bad |= cell_get(src + i * (cw ? 2048 : 512), a[i], d[i], e1);
                if (t >= 120) bad |= cell_get(src - (R ? 512 : 0), a[4], d[4], e1);
            } while (bad);
            TSH(45);
            if (cw) {
                uint4* cb = reinterpret_cast<uint4*>(smem + OFF_CSB) + (t >> 3) * 16 + (t & 7);
                const uint32_t lo = split2((__uint_as_float(a[0]) + __uint_as_float(a[1])) + (__uint_as_float(a[2]) + __uint_as_float(a[3])));
                const uint32_t hi = split2((__uint_as_float(d[0]) + __uint_as_float(d[1])) + (__uint_as_float(d[2]) + __uint_as_float(d[3])));
                cb[0] = make_uint4(lo, lo, 0, 0);
                cb[8] = make_uint4(hi, hi, 0, 0);
            } else {
                uint2* st = reinterpret_cast<uint2*>(smem + OFF_STATS) + lane;
                uint32_t* rd = reinterpret_cast<uint32_t*>(smem + OFF_RSTD) + lane;
#pragma unroll
                for (int i = 0; i < 4; i++) { st[32 * i] = make_uint2(a[i], d[i]); rd[8 + 32 * i] = a[i]; }
                if (t >= 120) rd[-24] = a[4];
            }
            fence_async_smem();
            __syncwarp();
            mbar_arrive_if0(bar + 8 * B_AUX, lane);
            TSH(41);
            reinterpret_cast<float2*>(smem + OFF_BIAS)[t] = make_float2(0.5f * bf_lo(bv1), bf_lo(bv2));
            __syncwarp();
            mbar_arrive_if0(bar + 8 * B_KV, lane);
        }
        {
            uint2* kv = reinterpret_cast<uint2*>(smem + OFF_K) + min(t, 111);
            mbar_wait(bar + 8 * B_QKV, 0);
            uint2 k2 = kv[896], v2 = kv[1792 + (OFF_V - OFF_K) / 8];
            cell_put(cells, k2.x, k2.y, e1);
            cell_put(cells + 1792, v2.x, v2.y, e1);
            k2 = v2 = make_uint2(0, 0);
            if (DH) delay(DH);
            if (R > 0) while (cell_get(cells - 16 * 3584, k2.x, k2.y, e1) | cell_get(cells - 16 * 3584 + 1792, v2.x, v2.y, e1)) {}
            kv[0] = k2;
            kv[(OFF_V - OFF_K) / 8] = v2;
            mbar_wait(bar + 8 * B_KV, 0);
            __syncwarp();
            mbar_arrive_if0(bar + 8 * B_HALO, lane);
            TSH(40);
        }
        if (hw == 3) {
            mbar_wait(bar + 8 * B_OST, 0);
            if (elect()) {
                unsigned* oc = ctr + C_O + (R * 2 + (P >> 2)) * 32;
                asm volatile("mbarrier.arrive.relaxed.cluster.shared::cluster.b64 _, [%0];" ::"r"(mapa(bar + 8 * B_FREE, z ^ 1)) : "memory");
                fence_async_smem();
                tma2d_store(&mp.ost, sb + OFF_OST, z * 64, P * 1024 + R * 128);
                bulk_commit();
                delay(DO);
                red_relaxed(oc, 1);
                TS(21);
                bulk_wait_all();
                asm volatile("mbarrier.arrive.relaxed.cluster.shared::cluster.b64 _, [%0];" ::"r"(mapa(bar + 8 * B_UDONE, z ^ 1)) : "memory");
                TS(20);
            }
        } else {
            const uint32_t tag = e1 & 0x3FFF;
            const uint32_t ca = sb + OFF_A + lane * 128 + ((~lane & 7) << 4) + (lane >> 3) * 4, cb = sb + OFF_B + lane * 132;
            uint32_t par = 0x3F;
#pragma unroll 1
            for (uint32_t r = r_o + hw; r < r_u + 14;) {
                const uint32_t s = slot(r);
                const bool isa = r - r_o < 4;
                const uint32_t a0 = isa ? ca + s * 16384 : cb + s * BLK, a3 = a0 - (isa ? 0 : (lane & 16) * 132);
                mbar_wait(bar + 8 * (B_LAND + s), (par >> s) & 1);
                par ^= 1 << s;
                bool ok = true;
#pragma unroll
                for (int k = 0; k < 4; k++) {
                    uint32_t v;
                    asm volatile("ld.shared.b32 %0, [%1];" : "=r"(v) : "r"((k < 3 ? a0 : a3) + k * 4096) : "memory");
                    ok &= (v == (isa ? tag : ~0u)) == isa;
                }
                if (__all_sync(0xffffffffu, ok)) {
                    mbar_arrive_if0(bar + 8 * (B_FULL + s), lane);
                    if (r == r_o || r == r_u) TS(r == r_o ? 29 : 30);
                    r += 3;
                } else if (elect()) {
                    TS(31);
                    fetch_x(r);
                }
            }
        }
    } else {
        asm volatile("setmaxnreg.dec.sync.aligned.u32 32;");
        auto wait_free = [&](uint32_t r, uint32_t first) {
            const uint32_t a = r < 6 ? B_EMPTYQ + ((first >> (4 * r)) & 7) : B_EMPTY + slot(r);
            mbar_wait(bar + 8 * a, r < 6 ? 0 : phase(r) ^ 1);
        };
        if (warp == 12) {
            TS(14);
            if (elect()) {
#pragma unroll 1
                for (int kb = W0; kb < 7; kb++) {
                    if (kb == 1) while (clock32() - t_in < DLY2) {}
                    if (kb >= QDEPTH) { mbar_wait(bar + 8 * (B_FULLQ + kb - QDEPTH), 0); TS(25 + kb - QDEPTH); }
                    if (kb >= 5) mbar_wait(bar + 8 * (B_EMPTYQ + kb - 5), 0);
                    if (kb > 0) x_load(kb);
                    w_load(kb);
                    if (kb == 0) TS(16);
                }
                TS(17);
                ld_relaxed(ctr + C_O + ((q & ~1) + z) * 32);
                mbar_wait(bar + 8 * B_LNFREE, 0);
                if (!g1) {
                    const int ic = (q - 14) * 8 + j * 2 + z, rot = ic >> 3;
                    mbar_wait(bar + 8 * (B_EMPTYQ + 2), 0);
                    mbar_expect(bar + 8 * B_GO, 2 * BLK);
#pragma unroll 1
                    for (int i = 0; i < 2; i++) tma4d(sb + OFF_A + i * BLK, &mp.wo, 0, 0, (z * 2 + i) * 14, ic >> 1, bar + 8 * B_GO);
                    mbar_wait(bar + 8 * B_GO, 0);
#pragma unroll 1
                    for (int i = 0; i < 2; i++) {
                        uint8_t* dst = scr + G_BIMG + (ic * 2 + i) * BLK;
                        bulk_store(dst + rot * 6144, sb + OFF_A + i * BLK, 8192);
                        bulk_store(dst + (rot ^ 1) * 8192, sb + OFF_A + i * BLK + 8192, 6144);
                    }
                    bulk_commit();
                    bulk_wait_all();
                    publish(ctr + C_WO);
                    TS(44);
                }
#pragma unroll 1
                for (uint32_t r = 0; r < r_o; r++) {
                    const uint32_t s = slot(r), fb = bar + 8 * (B_FULL + s);
                    wait_free(r, 0x654320u);
                    mbar_expect(fb, 16384);
                    tma3d(sb + OFF_A + s * 16384, &mp.w1, 0, z * 1024 + r * 64, 2 * q, fb);
                    TS(99 + r);
                }
                mbar_wait(bar + 8 * B_OST, 0);
#pragma unroll 1
                for (uint32_t r = r_o; r < r_o + NARM; r++) {
                    wait_free(r, 0x654320u);
                    mbar_expect(bar + 8 * (B_LAND + slot(r)), 16384);
                }
                poll(ctr + C_O + ((q & ~1) + z) * 32, epoch() * 8);
                TS(32);
#pragma unroll
                for (uint32_t i = 0; i < NARM; i++) fetch_x(r_o + i, false);
                TS(99 + 17);
#pragma unroll 1
                for (uint32_t r = r_o + NARM; r < r_u; r++) {
                    wait_free(r, 0x654320u);
                    fetch_x(r);
                    TS(99 + 17 + r - r_o);
                }
#pragma unroll 1
                for (uint32_t i = 0; i < 14; i++) {
                    const uint32_t r = r_u + i, s = slot(r), fb = bar + 8 * (B_FULL + s);
                    wait_free(r, 0x654320u);
                    mbar_expect(fb, 16384);
                    tma3d(sb + OFF_A + s * 16384, &mp.w2, 0, (14 * z + (i < 7 ? 2 * i : 2 * i - 13)) * 64, 2 * q, fb);
                    TS(99 + 21 + i);
                }
                wait_free(r_u + 14, 0);
                mbar_expect(bar + 8 * B_XR, 16384);
                tma2d(sb + OFF_A + slot(r_u + 14) * 16384, &mp.xn, j * 112 + z * 64, q * 128, bar + 8 * B_XR);
            }
        } else if (warp == 13) {
            if (elect()) {
#pragma unroll 1
                for (int ph = g1 ? 0 : 1; ph < 4; ph++) {
                    const uint8_t* src = ph == 0 ? scr + G_HIMG + (64 * z + j) * BLK : scr + G_BIMG + ((ph == 1 ? 4 * z : 6 + 14 * z + ph) * 4 + j) * BLK;
                    const uint32_t r0 = ph == 0 ? 0 : r_o + (ph == 1 ? 0 : 7 * ph - 10), r1 = r_o + (ph == 0 ? 0 : 7 * ph - 3);
#pragma unroll 1
                    for (uint32_t r = r0; r < r1; r++, src += ph < 2 ? 4 * BLK : 8 * BLK) {
                        const uint32_t s = slot(r), fb = bar + 8 * ((ph < 2 ? B_FULL : B_LAND) + s);
                        wait_free(r, 0x644332u);
                        mbar_expect(fb, BLK);
                        mbar_wait(bar + 8 * (ph == 0 && r < NH ? B_GOH : B_GO + ph), 0);
                        bulk_load(sb + OFF_B + s * BLK, src, BLK, fb);
                        TS(134 + 16 + (ph > 0) + r - r_o);
                    }
                }
            }
        } else if (warp == 14) {
            uint8_t* stcell = scr + G_STATS + ((lane & 1) * 1024 + 8 * b + (lane >> 1)) * 16;
            if (lane < 16) cell_put(stcell, 0, 0, 0);
            const unsigned ev = ld_relaxed(ctr + C_LN);
            uint8_t* hb = scr + G_HIMG + (b & ~3) * BLK;
            const unsigned e1 = (ev >> 7) + 1;
            if (lane == 0) {
                *reinterpret_cast<volatile unsigned*>(smem + OFF_EP) = e1;
                mbar_arrive(bar + 8 * B_EP);
                TS(36);
            }
            bar_sync<10, 288>();
            if (elect()) {
                fence_async_smem();
                TS(42);
                tma4d_store(&mp.hst, sb + OFF_A, 0, 0, b & 3, b & ~3);
                bulk_commit();
            }
            __syncwarp();
            if (lane < 16) {
                const uint2 v = reinterpret_cast<const uint2*>(smem + OFF_LNST)[lane];
                cell_put(stcell, v.x, v.y, e1);
            }
            bulk_wait_all();
            __syncwarp();
            TS(63);
            unsigned rb = 0;
#pragma unroll
            for (int i = 0; i < 4; i++) rb |= ld_relaxed(reinterpret_cast<const unsigned*>(hb + i * BLK + ((b & 3) * 28 + min(lane, 27)) * 128));
            if (lane < ((b & 63) < 4 * NH ? 2 : 1)) red_relaxed(ctr + C_LN + lane * (1 + (b >> 6)), 1 + (rb & (sb >> 31)));
            if (lane == 0) {
                mbar_arrive(bar + 8 * B_LNFREE);
                TS(37);
                ld_relaxed(ctr + C_U + z * 64);
                ld_relaxed(ctr + C_U + z * 64 + 32);
#pragma unroll 1
                for (int ph = g1 ? 0 : 1; ph < 4; ph++) {
                    if (ph || NH) mbar_wait(bar + 8 * (ph == 0 ? B_GOH : ph == 1 ? B_HALO : g1 ? B_RECV1 : B_OST), 0);
                    poll(ctr + ph * 32 + (ph >> 1) * z * 64, e1 * (ph == 0 ? 128 : ph == 1 ? 16 : 56));
                    fence_async_global();
                    mbar_arrive(bar + 8 * (B_GO + ph));
                    if (ph != 1) TS(ph == 0 ? 33 : 32 + ph);
                }
            }
        } else {
            if ((sb & 0x3FFFF) != SB0) __trap();
            if (elect()) {
#pragma unroll 1
                for (int i = 2; i < 10; i++) asm volatile("prefetch.tensormap [%0];" ::"l"(reinterpret_cast<const CUtensorMap*>(&mp) + i) : "memory");
            }
            __syncwarp();
            if (NH && g1 && elect()) {
                mbar_watch(bar + 8 * (B_FULLQ + GH), 0);
                const unsigned target = epoch() * (4 * NH);
                for (uint32_t n = 0; !ctr_done(ld_relaxed(ctr + C_LN + 1 + z), target);) if (++n >> 22) __trap();
                fence_async_global();
                mbar_arrive(bar + 8 * B_GOH);
                TS(38);
            }
            __syncwarp();
            mbar_watch(bar + 8 * B_KV, 0);
#pragma unroll 1
            for (int i = g1 ? 0 : 8; i < 8; i++) {
                uint32_t l = (7 * z + (q >= 7 ? 6 : 0)) * 8 + (i & 3) * 14 + min(lane >> 1, 13);
                if (l >= 112) l -= 112;
                cell_put(scr + G_BIMG + ((8 + 2 * q + (i >> 2)) * 4 + j) * BLK + l * 128 + (l & 24) * 4 + (lane & 1) * 16, ~0u, ~0u, ~0u);
            }
            __threadfence();
            __syncwarp();
            mbar_arrive_if0(bar + 8 * B_FREE, lane);
            TS(59);
#pragma unroll 1
            for (int i = g1 ? 0 : 2; i < 2; i++) {
                mbar_watch(bar + 8 * (B_RECV1 + i), 0);
                delay(DU);
                if (lane == 0) red_relaxed(ctr + C_U + ((q >= 7 ? 2 : 0) + i) * 32, 1);
                TS(22 + i);
            }
            mbar_watch(bar + 8 * B_RECV2, 0);
            mbar_watch(bar + 8 * (B_RECV2 + 1), 0);
        }
    }
}

typedef CUresult (*EncodeFn)(CUtensorMap*, CUtensorMapDataType, cuuint32_t, void*, const cuuint64_t*, const cuuint64_t*, const cuuint32_t*,
                             const cuuint32_t*, CUtensorMapInterleave, CUtensorMapSwizzle, CUtensorMapL2promotion, CUtensorMapFloatOOBfill);

void encode(EncodeFn fn, CUtensorMap* m, const void* p, int rank, const cuuint64_t* dims, const cuuint64_t* strides, const cuuint32_t* box, bool swz) {
    const cuuint32_t es[4] = {1, 1, 1, 1};
    fn(m, CU_TENSOR_MAP_DATA_TYPE_BFLOAT16, rank, const_cast<void*>(p), dims, strides, box, es, CU_TENSOR_MAP_INTERLEAVE_NONE,
       swz ? CU_TENSOR_MAP_SWIZZLE_128B : CU_TENSOR_MAP_SWIZZLE_NONE, CU_TENSOR_MAP_L2_PROMOTION_L2_128B, CU_TENSOR_MAP_FLOAT_OOB_FILL_NONE);
}

}

extern "C" void kernel_launch(void* const* d_in, const int* in_sizes, int n_in, void* d_out, int out_size) {
    const __nv_bfloat16* x = (const __nv_bfloat16*)d_in[0];
    const __nv_bfloat16* wqkv = (const __nv_bfloat16*)d_in[1];
    const __nv_bfloat16* wo = (const __nv_bfloat16*)d_in[2];
    const __nv_bfloat16* w1 = (const __nv_bfloat16*)d_in[4];
    const __nv_bfloat16* b1 = (const __nv_bfloat16*)d_in[5];
    const __nv_bfloat16* w2 = (const __nv_bfloat16*)d_in[6];
    const __nv_bfloat16* b2 = (const __nv_bfloat16*)d_in[7];

    void* fp = nullptr;
    cudaDriverEntryPointQueryResult qr;
    cudaGetDriverEntryPoint("cuTensorMapEncodeTiled", &fp, cudaEnableDefault, &qr);
    EncodeFn fn = (EncodeFn)fp;
    void* sp = nullptr;
    cudaGetSymbolAddress(&sp, g_scratch);
    uint8_t* scr = (uint8_t*)sp;
    void *o = scr + G_O, *himg = scr + G_HIMG;

    Maps mp;
    { cuuint64_t d[3] = {64, 2048, 7}, s[2] = {896, 128}; cuuint32_t bx[3] = {64, 16, 7}; encode(fn, &mp.xl, x, 3, d, s, bx, true); }
    { cuuint64_t d[2] = {896, 1024}, s[1] = {1792}; cuuint32_t bx[2] = {64, 128}; encode(fn, &mp.x, x, 2, d, s, bx, true); }
    { cuuint64_t d[3] = {448, 448, 3}, s[2] = {2688, 896}; cuuint32_t bx[3] = {64, 32, 3}; encode(fn, &mp.wqkv, wqkv, 3, d, s, bx, true); }
    { cuuint64_t d[3] = {64, 2048, 28}, s[2] = {3584, 128}; cuuint32_t bx[3] = {64, 64, 2}; encode(fn, &mp.w1, w1, 3, d, s, bx, true); }
    { cuuint64_t d[3] = {64, 1792, 32}, s[2] = {4096, 128}; cuuint32_t bx[3] = {64, 64, 2}; encode(fn, &mp.w2, w2, 3, d, s, bx, true); }
    { cuuint64_t d[4] = {64, 28, 4, 128}, s[3] = {128, 3584, BLK}; cuuint32_t bx[4] = {64, 28, 1, 4}; encode(fn, &mp.hst, himg, 4, d, s, bx, false); }
    { cuuint64_t d[2] = {448, 2048}, s[1] = {896}; cuuint32_t bx[2] = {64, 128}; encode(fn, &mp.xn, x, 2, d, s, bx, true); }
    { cuuint64_t d[2] = {64, 8 * 2048}, s[1] = {128}; cuuint32_t bx[2] = {64, 128}; encode(fn, &mp.old_, o, 2, d, s, bx, true); }
    { cuuint64_t d[2] = {128, 8 * 1024}, s[1] = {256}; cuuint32_t bx[2] = {64, 128}; encode(fn, &mp.ost, o, 2, d, s, bx, true); }
    { cuuint64_t d[4] = {8, 56, 56, 8}, s[3] = {896, 16, 56 * 896}; cuuint32_t bx[4] = {8, 64, 14, 1}; encode(fn, &mp.wo, wo, 4, d, s, bx, false); }

    cudaFuncSetAttribute(fused_kernel, cudaFuncAttributeMaxDynamicSharedMemorySize, SMEM_BYTES);
    fused_kernel<<<128, 512, SMEM_BYTES>>>(x, wqkv, b1, b2, scr, (uint8_t*)d_out, mp);
}
```

```cpp
#include <cuda_runtime.h>
#include <cuda.h>
#include <cuda_bf16.h>
#include <stdint.h>

namespace {

constexpr int S_ = 2048, D_ = 448;
constexpr uint32_t BLK = 14336;

constexpr uint32_t G_HIMG = 0;
constexpr uint32_t G_BIMG = G_HIMG + 32 * 4 * BLK;
constexpr uint32_t G_O = G_BIMG + 36 * 4 * BLK;
constexpr uint32_t G_STATS = G_O + 8 * S_ * 128;
constexpr uint32_t G_CS = G_STATS + S_ * 16;
constexpr uint32_t G_HALO = G_CS + 8 * 4 * 2048;
constexpr uint32_t G_CTR = G_HALO + 128 * 3584;
constexpr uint32_t G_END = G_CTR + (192 + 16 * 32) * 4;
__device__ __align__(1024) uint8_t g_scratch[G_END];

constexpr int C_LN = 0, C_WO = 32, C_U = 64, C_O = 192;

#define TSX(sel, id)
#define TS(id)
#define TS0(id)
#define TSH(id)
#define TSW(id)
#define TG(id)

#define TSG1 0
#define TSD(id)
#define QDEPTH 3
#define ROT 6
#define KS 3
#define DLY1 1600
#define DLY2 2000
#define GATHER 3
#define NS2 3
#define NE 2
#define PRE0 8
#define PRE1 5
#define DU 0
#define DO 100
#define DH 400
#define NQ 0
constexpr uint32_t OFF_A = 0;
constexpr uint32_t OFF_B = 98304;
constexpr uint32_t OFF_X = 184320;
constexpr uint32_t OFF_K = 196608;
constexpr uint32_t OFF_V = OFF_K + 9 * 896;
constexpr uint32_t OFF_OST = OFF_X, OFF_RECV2 = OFF_X, OFF_RECV1 = OFF_X + 16384, OFF_OUT = OFF_X + 16384;
constexpr uint32_t OFF_CSB = 221184;
constexpr uint32_t OFF_ONES = OFF_CSB + 3072;
constexpr uint32_t OFF_STATS = OFF_ONES + 512;
constexpr uint32_t OFF_BIAS = OFF_STATS + 1024;
constexpr uint32_t OFF_LNX = OFF_BIAS + 1024;
constexpr uint32_t OFF_RSTD = OFF_LNX + 512;
constexpr uint32_t OFF_LNST = 229376;
constexpr uint32_t OFF_EP = OFF_LNST + 128;
constexpr uint32_t OFF_BAR = OFF_EP + 16;
constexpr uint32_t OFF_TS = OFF_BAR + 8 * 48;
constexpr uint32_t SMEM_BYTES = OFF_TS;

enum : int {
    B_FULLQ = 0, B_LNIN = 7, B_EMPTYQ = 8, B_FULL = 15, B_EMPTY = 21, B_AUX = 27, B_QKV, B_HALO, B_FREE, B_RECV1, B_RECV2 = B_RECV1 + 2,
    B_EP = B_RECV2 + 2, B_OST, B_LNFREE, B_UDONE, B_NONE, B_GO, B_XR = B_GO + 4, B_KV, B_COUNT, B_LAND = B_FULLQ
};
constexpr uint32_t XSLOT = 0x5432154u;
constexpr uint32_t WSLOT = 0x3421034u;
#define ATT_STEP 10

__device__ __forceinline__ uint32_t smem_u32(const void* p) { return (uint32_t)__cvta_generic_to_shared(p); }
__device__ __forceinline__ void mbar_init(uint32_t a, int c) { asm volatile("mbarrier.init.shared::cta.b64 [%0], %1;" ::"r"(a), "r"(c) : "memory"); }
__device__ __forceinline__ void mbar_expect(uint32_t a, uint32_t b) { asm volatile("mbarrier.arrive.expect_tx.shared::cta.b64 _, [%0], %1;" ::"r"(a), "r"(b) : "memory"); }
__device__ __forceinline__ void mbar_arrive(uint32_t a) { asm volatile("mbarrier.arrive.shared::cta.b64 _, [%0];" ::"r"(a) : "memory"); }
__device__ __forceinline__ void mbar_arrive_if0(uint32_t a, uint32_t sel) {
    asm volatile("{\n.reg .pred p;\nsetp.eq.u32 p, %1, 0;\n@p mbarrier.arrive.shared::cta.b64 _, [%0];\n}" ::"r"(a), "r"(sel) : "memory");
}
__device__ __forceinline__ void mbar_wait(uint32_t a, uint32_t parity) {
    asm volatile("{\n.reg .pred p;\nW0:\nmbarrier.try_wait.parity.shared::cta.b64 p, [%0], %1;\n@!p bra W0;\n}\n" ::"r"(a), "r"(parity) : "memory");
}
__device__ __forceinline__ void mbar_watch(uint32_t a, uint32_t parity) {
    asm volatile(
        "{\n.reg .pred p;\n.reg .u32 n;\nmov.u32 n, 0;\n"
        "W0:\nmbarrier.try_wait.parity.shared::cta.b64 p, [%0], %1;\n@p bra W1;\n"
        "add.u32 n, n, 1;\nsetp.lt.u32 p, n, 4194304;\n@p bra W0;\ntrap;\nW1:\n}\n" ::"r"(a), "r"(parity) : "memory");
}
__device__ __forceinline__ bool elect() {
    uint32_t r;
    asm volatile("{\n.reg .pred p;\nelect.sync _|p, 0xffffffff;\nselp.u32 %0, 1, 0, p;\n}" : "=r"(r));
    return r;
}
__device__ __forceinline__ uint32_t mapa(uint32_t a, uint32_t cta) { uint32_t r; asm("mapa.shared::cluster.u32 %0, %1, %2;" : "=r"(r) : "r"(a), "r"(cta)); return r; }
__device__ __forceinline__ void tma2d(uint32_t dst, const CUtensorMap* m, int c0, int c1, uint32_t bar) {
    asm volatile("cp.async.bulk.tensor.2d.shared::cluster.global.mbarrier::complete_tx::bytes [%0], [%1, {%3, %4}], [%2];" ::"r"(dst), "l"(m), "r"(bar), "r"(c0), "r"(c1) : "memory");
}
__device__ __forceinline__ void tma3d(uint32_t dst, const CUtensorMap* m, int c0, int c1, int c2, uint32_t bar) {
    asm volatile("cp.async.bulk.tensor.3d.shared::cluster.global.mbarrier::complete_tx::bytes [%0], [%1, {%3, %4, %5}], [%2];" ::"r"(dst), "l"(m), "r"(bar), "r"(c0), "r"(c1), "r"(c2) : "memory");
}
__device__ __forceinline__ void tma3d_mc(uint32_t dst, const CUtensorMap* m, int c0, int c1, int c2, uint32_t bar) {
    asm volatile("cp.async.bulk.tensor.3d.shared::cluster.global.mbarrier::complete_tx::bytes.multicast::cluster [%0], [%1, {%3, %4, %5}], [%2], %6;"
                 ::"r"(dst), "l"(m), "r"(bar), "r"(c0), "r"(c1), "r"(c2), "h"((uint16_t)3) : "memory");
}
__device__ __forceinline__ void tma2d_store(const CUtensorMap* m, uint32_t src, int c0, int c1) {
    asm volatile("cp.async.bulk.tensor.2d.global.shared::cta.bulk_group [%0, {%2, %3}], [%1];" ::"l"(m), "r"(src), "r"(c0), "r"(c1) : "memory");
}
__device__ __forceinline__ void tma4d_store(const CUtensorMap* m, uint32_t src, int c0, int c1, int c2, int c3) {
    asm volatile("cp.async.bulk.tensor.4d.global.shared::cta.bulk_group [%0, {%2, %3, %4, %5}], [%1];" ::"l"(m), "r"(src), "r"(c0), "r"(c1), "r"(c2), "r"(c3) : "memory");
}
__device__ __forceinline__ void tma4d(uint32_t dst, const CUtensorMap* m, int c0, int c1, int c2, int c3, uint32_t bar) {
    asm volatile("cp.async.bulk.tensor.4d.shared::cluster.global.mbarrier::complete_tx::bytes [%0], [%1, {%3, %4, %5, %6}], [%2];" ::"r"(dst), "l"(m), "r"(bar), "r"(c0), "r"(c1), "r"(c2), "r"(c3) : "memory");
}
__device__ __forceinline__ void bulk_load(uint32_t dst, const void* src, uint32_t bytes, uint32_t bar) {
    asm volatile("cp.async.bulk.shared::cluster.global.mbarrier::complete_tx::bytes [%0], [%1], %2, [%3];" ::"r"(dst), "l"(src), "r"(bytes), "r"(bar) : "memory");
}
__device__ __forceinline__ void bulk_store(void* dst, uint32_t src, uint32_t bytes) {
    asm volatile("cp.async.bulk.global.shared::cta.bulk_group [%0], [%1], %2;" ::"l"(dst), "r"(src), "r"(bytes) : "memory");
}
__device__ __forceinline__ void bulk_commit() { asm volatile("cp.async.bulk.commit_group;" ::: "memory"); }
__device__ __forceinline__ void bulk_wait_all() { asm volatile("cp.async.bulk.wait_group 0;" ::: "memory"); }
__device__ __forceinline__ void bulk_wait_read() { asm volatile("cp.async.bulk.wait_group.read 0;" ::: "memory"); }
__device__ __forceinline__ void l2_prefetch(const void* p) { asm volatile("prefetch.global.L2 [%0];" ::"l"(p)); }
__device__ __forceinline__ void fence_async_smem() { asm volatile("fence.proxy.async.shared::cta;" ::: "memory"); }
__device__ __forceinline__ void fence_async_global() { asm volatile("fence.proxy.async.global;" ::: "memory"); }
__device__ __forceinline__ void red_relaxed(unsigned* p, unsigned v) { asm volatile("red.relaxed.gpu.global.add.u32 [%0], %1;" ::"l"(p), "r"(v) : "memory"); }
__device__ __forceinline__ void publish(unsigned* p) {
    asm volatile("fence.proxy.async.global;\nred.release.gpu.global.add.u32 [%0], 1;" ::"l"(p) : "memory");
}
__device__ __forceinline__ void stg32(void* p, uint32_t v) { asm volatile("st.global.b32 [%0], %1;" ::"l"(p), "r"(v) : "memory"); }
__device__ __forceinline__ unsigned ld_relaxed(const unsigned* p) { unsigned v; asm volatile("ld.relaxed.gpu.global.u32 %0, [%1];" : "=r"(v) : "l"(p) : "memory"); return v; }
__device__ __forceinline__ bool ctr_done(unsigned v, unsigned target) { return ((v - target) & 0x1FFFFFFu) == 0; }
__device__ __forceinline__ uint32_t clock32() { uint32_t c; asm volatile("mov.u32 %0, %%clock;" : "=r"(c)::"memory"); return c; }
__device__ __forceinline__ void delay(uint32_t n) { const uint32_t t0 = clock32(); while (clock32() - t0 < n) {} }
__device__ __forceinline__ void poll(const unsigned* p, unsigned target) { while (!ctr_done(ld_relaxed(p), target)) {} }
__device__ __forceinline__ void cell_put(void* p, uint32_t a, uint32_t b, uint32_t tag) {
    asm volatile("st.relaxed.gpu.global.v4.b32 [%0], {%1, %3, %2, %3};" ::"l"(p), "r"(a), "r"(b), "r"(tag) : "memory");
}
__device__ __forceinline__ uint32_t cell_get(const void* p, uint32_t& a, uint32_t& b, uint32_t tag) {
    uint32_t t0, t1;
    asm volatile("ld.relaxed.gpu.global.v4.b32 {%0, %1, %2, %3}, [%4];" : "=r"(a), "=r"(t0), "=r"(b), "=r"(t1) : "l"(p) : "memory");
    return (t0 ^ tag) | (t1 ^ tag);
}
template <int ID, int N> __device__ __forceinline__ void bar_sync() { asm volatile("bar.sync %0, %1;" ::"n"(ID), "n"(N) : "memory"); }
template <int ID = 4> __device__ __forceinline__ void gate_wait(uint32_t on) { asm volatile("{\n.reg .pred p;\nsetp.ne.u32 p, %0, 0;\n@p bar.sync %1, 256;\n}" ::"r"(on), "n"(ID) : "memory"); }
template <int ID = 4> __device__ __forceinline__ void gate_open(uint32_t off) { asm volatile("{\n.reg .pred p;\nsetp.eq.u32 p, %0, 0;\n@p bar.arrive %1, 256;\n}" ::"r"(off), "n"(ID) : "memory"); }
__device__ __forceinline__ void wg_fence() { asm volatile("wgmma.fence.sync.aligned;" ::: "memory"); }
__device__ __forceinline__ void wg_commit() { asm volatile("wgmma.commit_group.sync.aligned;" ::: "memory"); }
template <int N> __device__ __forceinline__ void wg_wait() { asm volatile("wgmma.wait_group.sync.aligned %0;" ::"n"(N) : "memory"); }
template <int LO = 0, int HI = 56, int N> __device__ __forceinline__ void pin(float (&a)[N]) {
#pragma unroll
    for (int i = LO; i < (HI < N ? HI : N); i++) asm volatile("" : "+f"(a[i])::"memory");
}
__device__ __forceinline__ uint32_t ldg_u16(const void* p) {
    uint32_t v;
    asm volatile("ld.global.nc.u16 %0, [%1];" : "=r"(v) : "l"(p) : "memory");
    return v;
}
__device__ __forceinline__ uint32_t pack2(float lo, float hi) { uint32_t r; asm("cvt.rn.bf16x2.f32 %0, %1, %2;" : "=r"(r) : "f"(hi), "f"(lo)); return r; }
__device__ __forceinline__ float bf_lo(uint32_t v) { return __uint_as_float(v << 16); }
__device__ __forceinline__ float bf_hi(uint32_t v) { return __uint_as_float(v & 0xFFFF0000u); }
__device__ __forceinline__ uint32_t split2(float x) { return pack2(x, x - bf_lo(pack2(x, 0.f))); }
__device__ __forceinline__ void stsm4(uint32_t a, uint32_t r0, uint32_t r1, uint32_t r2, uint32_t r3) {
    asm volatile("stmatrix.sync.aligned.m8n8.x4.shared.b16 [%0], {%1, %2, %3, %4};" ::"r"(a), "r"(r0), "r"(r1), "r"(r2), "r"(r3) : "memory");
}
__device__ __forceinline__ void stsm2(uint32_t a, uint32_t r0, uint32_t r1) {
    asm volatile("stmatrix.sync.aligned.m8n8.x2.shared.b16 [%0], {%1, %2};" ::"r"(a), "r"(r0), "r"(r1) : "memory");
}
__device__ __forceinline__ void ldsm4(uint32_t a, uint32_t (&r)[4]) {
    asm volatile("ldmatrix.sync.aligned.m8n8.x4.shared.b16 {%0, %1, %2, %3}, [%4];" : "=r"(r[0]), "=r"(r[1]), "=r"(r[2]), "=r"(r[3]) : "r"(a) : "memory");
}
__device__ __forceinline__ void ldsm4t(uint32_t a, uint32_t (&r)[4]) {
    asm volatile("ldmatrix.sync.aligned.m8n8.x4.trans.shared.b16 {%0, %1, %2, %3}, [%4];" : "=r"(r[0]), "=r"(r[1]), "=r"(r[2]), "=r"(r[3]) : "r"(a) : "memory");
}
__device__ __forceinline__ void mma16816(float (&c)[4], uint32_t a0, uint32_t a1, uint32_t a2, uint32_t a3, uint32_t b0, uint32_t b1) {
    asm volatile("mma.sync.aligned.m16n8k16.row.col.f32.bf16.bf16.f32 {%0,%1,%2,%3}, {%4,%5,%6,%7}, {%8,%9}, {%0,%1,%2,%3};"
                 : "+f"(c[0]), "+f"(c[1]), "+f"(c[2]), "+f"(c[3]) : "r"(a0), "r"(a1), "r"(a2), "r"(a3), "r"(b0), "r"(b1));
}
__device__ __forceinline__ void mma1688(float (&c)[4], uint32_t a0, uint32_t a1, uint32_t b0) {
    asm volatile("mma.sync.aligned.m16n8k8.row.col.f32.bf16.bf16.f32 {%0,%1,%2,%3}, {%4,%5}, {%6}, {%0,%1,%2,%3};"
                 : "+f"(c[0]), "+f"(c[1]), "+f"(c[2]), "+f"(c[3]) : "r"(a0), "r"(a1), "r"(b0));
}
constexpr uint32_t SB0 = 1024;
__device__ __forceinline__ uint32_t desc_lo(uint32_t off, uint32_t lbo) { return ((SB0 + off) >> 4) + ((lbo >> 4) << 16); }
constexpr uint32_t H_SW = (1024 >> 4) | (1u << 30), H_H = 128 >> 4, H_U = 1024 >> 4;
__device__ __forceinline__ float ex2(float x) { float r; asm("ex2.approx.ftz.f32 %0, %1;" : "=f"(r) : "f"(x)); return r; }
__device__ __forceinline__ float rsq(float x) { float r; asm("rsqrt.approx.ftz.f32 %0, %1;" : "=f"(r) : "f"(x)); return r; }
__device__ __forceinline__ float rcp(float x) { float r; asm("rcp.approx.ftz.f32 %0, %1;" : "=f"(r) : "f"(x)); return r; }
__device__ __forceinline__ float gelu_half(float h) {
    float y = h * fmaf(h * h, 8.f * 0.0356774081363f, 2.f * 0.7978845608029f), t;
    asm("tanh.approx.f32 %0, %1;" : "=f"(t) : "f"(y));
    return fmaf(h, t, h);
}

template <uint32_t HB, int TB>
__device__ __forceinline__ void wgmma_n56_rs(float (&d)[28], const uint32_t (&a)[4], uint32_t lb, int scale_d) {
    asm volatile("{\n.reg .pred p;\n.reg .b64 db;\nsetp.ne.b32 p, %33, 0;\nmov.b64 db, {%32, %34};\n"
        "wgmma.mma_async.sync.aligned.m64n56k16.f32.bf16.bf16 "
        "{%0, %1, %2, %3, %4, %5, %6, %7, %8, %9, %10, %11, %12, %13, %14, %15, %16, %17, %18, %19, %20, %21, %22, %23, %24, %25, %26, %27}, "
        "{%28, %29, %30, %31}, db, p, 1, 1, %35;\n}\n"
        : "+f"(d[0]), "+f"(d[1]), "+f"(d[2]), "+f"(d[3]), "+f"(d[4]), "+f"(d[5]), "+f"(d[6]), "+f"(d[7]), "+f"(d[8]), "+f"(d[9]), "+f"(d[10]), "+f"(d[11]), "+f"(d[12]), "+f"(d[13]), "+f"(d[14]), "+f"(d[15]), "+f"(d[16]), "+f"(d[17]), "+f"(d[18]), "+f"(d[19]), "+f"(d[20]), "+f"(d[21]), "+f"(d[22]), "+f"(d[23]), "+f"(d[24]), "+f"(d[25]), "+f"(d[26]), "+f"(d[27])
        : "r"(a[0]), "r"(a[1]), "r"(a[2]), "r"(a[3]), "r"(lb), "r"(scale_d), "n"(HB), "n"(TB));
}
template <int TA, uint32_t HA, uint32_t HB>
__device__ __forceinline__ void wgmma_n112(float (&d)[56], uint32_t la, uint32_t lb, int scale_d = 1) {
    asm volatile("{\n.reg .b64 da, db;\n.reg .pred p;\nsetp.ne.b32 p, %61, 0;\nmov.b64 da, {%56, %59};\nmov.b64 db, {%57, %60};\n"
        "wgmma.mma_async.sync.aligned.m64n112k16.f32.bf16.bf16 "
        "{%0, %1, %2, %3, %4, %5, %6, %7, %8, %9, %10, %11, %12, %13, %14, %15, %16, %17, %18, %19, %20, %21, %22, %23, %24, %25, %26, %27, %28, %29, %30, %31, %32, %33, %34, %35, %36, %37, %38, %39, %40, %41, %42, %43, %44, %45, %46, %47, %48, %49, %50, %51, %52, %53, %54, %55}, "
        "da, db, p, 1, 1, %58, 1;\n}\n"
        : "+f"(d[0]), "+f"(d[1]), "+f"(d[2]), "+f"(d[3]), "+f"(d[4]), "+f"(d[5]), "+f"(d[6]), "+f"(d[7]), "+f"(d[8]), "+f"(d[9]), "+f"(d[10]), "+f"(d[11]), "+f"(d[12]), "+f"(d[13]), "+f"(d[14]), "+f"(d[15]), "+f"(d[16]), "+f"(d[17]), "+f"(d[18]), "+f"(d[19]), "+f"(d[20]), "+f"(d[21]), "+f"(d[22]), "+f"(d[23]), "+f"(d[24]), "+f"(d[25]), "+f"(d[26]), "+f"(d[27]), "+f"(d[28]), "+f"(d[29]), "+f"(d[30]), "+f"(d[31]), "+f"(d[32]), "+f"(d[33]), "+f"(d[34]), "+f"(d[35]), "+f"(d[36]), "+f"(d[37]), "+f"(d[38]), "+f"(d[39]), "+f"(d[40]), "+f"(d[41]), "+f"(d[42]), "+f"(d[43]), "+f"(d[44]), "+f"(d[45]), "+f"(d[46]), "+f"(d[47]), "+f"(d[48]), "+f"(d[49]), "+f"(d[50]), "+f"(d[51]), "+f"(d[52]), "+f"(d[53]), "+f"(d[54]), "+f"(d[55])
        : "r"(la), "r"(lb), "n"(TA), "n"(HA), "n"(HB), "r"(scale_d));
}
template <int TA, uint32_t HA, uint32_t HB>
__device__ __forceinline__ void wgmma_n8(float (&d)[4], uint32_t la, uint32_t lb, int scale_d = 1) {
    asm volatile("{\n.reg .b64 da, db;\n.reg .pred p;\nsetp.ne.b32 p, %9, 0;\nmov.b64 da, {%4, %7};\nmov.b64 db, {%5, %8};\n"
        "wgmma.mma_async.sync.aligned.m64n8k16.f32.bf16.bf16 "
        "{%0, %1, %2, %3}, "
        "da, db, p, 1, 1, %6, 1;\n}\n"
        : "+f"(d[0]), "+f"(d[1]), "+f"(d[2]), "+f"(d[3])
        : "r"(la), "r"(lb), "n"(TA), "n"(HA), "n"(HB), "r"(scale_d));
}

__device__ __forceinline__ void send8(const float* a, uint32_t rbuf, uint32_t rbar, uint32_t on) {
    asm volatile("{\n.reg .pred p;\nsetp.ne.u32 p, %6, 0;\n@p st.async.weak.shared::cluster.mbarrier::complete_tx::bytes.v4.b32 [%0], {%1,%2,%3,%4}, [%5];\n}"
                 ::"r"(rbuf), "r"(pack2(a[0], a[1])), "r"(pack2(a[2], a[3])), "r"(pack2(a[4], a[5])), "r"(pack2(a[6], a[7])), "r"(rbar), "r"(on) : "memory");
}
__device__ __forceinline__ void send_half(const float (&a)[56], uint32_t rbuf, uint32_t rbar, int t, uint32_t on) {
#pragma unroll
    for (int i = 0; i < 3; i++) send8(a + 28 + 8 * i, rbuf + i * 2048 + t * 16, rbar, on);
    asm volatile("{\n.reg .pred p;\nsetp.ne.u32 p, %4, 0;\n@p st.async.weak.shared::cluster.mbarrier::complete_tx::bytes.v2.b32 [%0], {%1,%2}, [%3];\n}"
                 ::"r"(rbuf + 6144 + t * 8), "r"(pack2(a[52], a[53])), "r"(pack2(a[54], a[55])), "r"(rbar), "r"(on) : "memory");
}
__device__ __forceinline__ void recv_half(uint32_t (&p)[14], uint32_t buf, int t) {
#pragma unroll
    for (int i = 0; i < 3; i++)
        asm volatile("ld.shared.v4.b32 {%0,%1,%2,%3}, [%4];" : "=r"(p[4 * i]), "=r"(p[4 * i + 1]), "=r"(p[4 * i + 2]), "=r"(p[4 * i + 3]) : "r"(buf + i * 2048 + t * 16) : "memory");
    asm volatile("ld.shared.v2.b32 {%0,%1}, [%2];" : "=r"(p[12]), "=r"(p[13]) : "r"(buf + 6144 + t * 8) : "memory");
}

struct Maps { CUtensorMap xl, x, wqkv, hst, w1, w2, xn, old_, ost, wo; };

__global__ void __cluster_dims__(2, 1, 1) __launch_bounds__(512, 1)
fused_kernel(const __nv_bfloat16* __restrict__ x, const __nv_bfloat16* __restrict__ wqkv,
             const __nv_bfloat16* __restrict__ b1, const __nv_bfloat16* __restrict__ b2, uint8_t* __restrict__ scr,
             uint8_t* __restrict__ out, const __grid_constant__ Maps mp) {
    extern __shared__ __align__(1024) uint8_t smem[];
    const uint32_t sb = smem_u32(smem);
    const uint32_t bar = sb + OFF_BAR;
    const int tid = threadIdx.x, lane = tid & 31;
    const int b = blockIdx.x, z = b & 1, c = b >> 1;
    unsigned* const ctr = reinterpret_cast<unsigned*>(scr + G_CTR);
    if (tid < 112) l2_prefetch(reinterpret_cast<const uint8_t*>(x) + (b * 112 + tid) * 128);
    const int wline = (tid & 127) * 128 + b;
    const bool wfirst = ((wline / 1344) & ~ROT) == 0;
    const uint32_t t_in = clock32();
    TS0(0);
    TG(60);
    const int warp = __shfl_sync(0xffffffffu, tid >> 5, 0);
    const int j = c < 4 ? c : c < 36 ? (c - 4) >> 3 : ((c - 36) * 37) >> 8, q = c < 4 ? 15 : c < 36 ? (c - 4) & 7 : c - 28 - 7 * j;
    const bool g1 = q < 14;
    const int R = q < 8 ? q : (0x27654310u >> (4 * q - 32)) & 7, P = (q >> 3) * 4 + j;
    auto krow = [&](int kb) { const int k = kb + (R & ROT); return (k >= 7 ? k - 7 : k) * 64; };
    auto x_load = [&](int kb) {
        mbar_expect(bar + 8 * (B_FULLQ + kb), 40960);
        tma2d(sb + OFF_A + ((XSLOT >> (4 * kb)) & 7) * 16384, &mp.x, z * D_ + krow(kb), R * 128, bar + 8 * (B_FULLQ + kb));
    };
    auto w_load = [&](int kb) {
        tma3d_mc(sb + OFF_B + ((WSLOT >> (4 * kb)) & 7) * 24576 + z * 12288, &mp.wqkv, (P * 56) & ~15, krow(kb) + z * 32, 0, bar + 8 * (B_FULLQ + kb));
    };
    if (warp == 12 && elect()) {
#pragma unroll
        for (int i = B_FULLQ; i < B_EMPTYQ; i++) mbar_init(bar + 8 * i, 1);
        mbar_expect(bar + 8 * B_LNIN, BLK);
        tma3d(sb + OFF_A, &mp.xl, 0, 16 * b, 0, bar + 8 * B_LNIN);
        x_load(0);
        TS(15);
    }
    auto bar_count = [&](int i) {
        return i < B_FULL ? (i < B_EMPTYQ + 2 ? 16 : 8) + (((i - B_EMPTYQ) & ~1) == (R & 6 & ~ROT) ? 8 : 0) : i < B_EMPTY || i == B_FREE ? 2 : (i < B_AUX || i == B_NONE || i == B_OST) ? 8 : i == B_KV ? 12
               : (i == B_AUX || i == B_HALO) ? 4 : 1;
    };
    if (warp == 13 && elect()) {
#pragma unroll
        for (int i = B_EMPTYQ; i < B_COUNT; i++) mbar_init(bar + 8 * i, bar_count(i));
#pragma unroll
        for (int i = B_RECV1; i < B_EP; i++) mbar_expect(bar + 8 * i, i < B_RECV2 ? 7168 : 8192 - 2048 * z);
    }
    asm volatile("fence.mbarrier_init.release.cluster;" ::: "memory");
    __syncwarp();
    asm volatile("barrier.cluster.arrive.relaxed.aligned;\nbarrier.cluster.wait.aligned;" ::: "memory");
    if (warp == 12 && elect()) { w_load(0); TS(16); }
    auto slot = [](uint32_t r) { return r - 6 * ((r * 43) >> 8); };
    auto phase = [](uint32_t r) { return ((r * 43) >> 8) & 1; };
    const uint32_t r_o = g1 ? 16 : 0, r_u = r_o + 4;
    auto fetch_x = [&](uint32_t i, bool arm = true) {
        const uint32_t s = slot(r_o + i), lb = bar + 8 * (B_LAND + s);
        if (arm) mbar_expect(lb, i < 4 ? 16384 : BLK);
        if (i < 4) tma2d(sb + OFF_A + s * 16384, &mp.old_, 0, (4 * z + i) * S_ + q * 128, lb);
        else bulk_load(sb + OFF_B + s * BLK, scr + G_BIMG + ((14 * z + (i < 11 ? 2 * i : 2 * i - 13)) * 4 + j) * BLK, BLK, lb);
    };
    auto epoch = [&]() { mbar_wait(bar + 8 * B_EP, 0); return *reinterpret_cast<volatile unsigned*>(smem + OFF_EP); };

    if (warp < 8) {
        const int wg = warp >> 2, w4 = warp & 3, t = tid & 127, g = lane >> 2, tq = lane & 3;
        asm volatile("setmaxnreg.inc.sync.aligned.u32 208;");
        uint32_t xa[4];
#pragma unroll
        for (int k = 0; k < 4; k++) xa[k] = sb + OFF_A + (warp * 16 + (lane & 15)) * 128 + (((2 * k + (lane >> 4)) ^ (lane & 7)) << 4);
        {
            const int rg = warp & 1, jq = warp >> 1;
            const uint32_t ex = sb + OFF_LNX + (rg * 8 + g) * 32, ew = ex + jq * 8, ls = sb + OFF_LNST + (rg * 8 + g) * 8;
            uint32_t r[4][4], la[4], ha[4], dep = ex | ew | ls;
#pragma unroll
            for (int i = 0; i < 4; i++) {
                const int cg = 14 * jq + 4 * i + ((lane >> 3) & (i < 3 ? 3 : 1));
                la[i] = sb + OFF_A + (cg >> 3) * 2048 + rg * 1024 + (lane & 7) * 128 + (((cg ^ lane) & 7) << 4);
                int pos = 4 * i + (lane >> 3) + (b >= 64 ? 7 : 0);
                if (pos >= 14) pos -= 14;
                ha[i] = sb + OFF_A + jq * 3584 + rg * 1792 + (lane & 7) * 16 + pos * 128;
                dep |= la[i] | xa[i] | ha[i];
            }
            mbar_wait(bar + 8 * B_LNIN, dep >> 31);
#pragma unroll
            for (int i = 0; i < 4; i++) ldsm4(la[i], r[i]);
            float rs[4] = {0.f, 0.f, 0.f, 0.f}, rt[4] = {0.f, 0.f, 0.f, 0.f}, sq[4], v[28];
            const float sh = bf_lo(__shfl_sync(0xffffffffu, r[0][0], lane & 28));
            mma16816(rs, r[0][0], r[0][1], r[0][2], r[0][3], 0x3F803F80u, 0x3F803F80u);
            mma16816(rt, r[1][0], r[1][1], r[1][2], r[1][3], 0x3F803F80u, 0x3F803F80u);
            mma16816(rs, r[2][0], r[2][1], r[2][2], r[2][3], 0x3F803F80u, 0x3F803F80u);
            mma1688(rt, r[3][0], r[3][1], 0x3F803F80u);
#pragma unroll
            for (int n = 0; n < 14; n++) { v[2 * n] = bf_lo(r[n >> 2][n & 3]) - sh; v[2 * n + 1] = bf_hi(r[n >> 2][n & 3]) - sh; }
#pragma unroll
            for (int n = 0; n < 28; n++) sq[n & 3] = n < 4 ? v[n] * v[n] : fmaf(v[n], v[n], sq[n & 3]);
            const float mq = ((rs[0] + rs[2]) + (rt[0] + rt[2])) * (1.f / 112), dq = mq - sh;
            float m2 = fmaf(-28.f * dq, dq, (sq[0] + sq[1]) + (sq[2] + sq[3]));
            m2 += __shfl_xor_sync(0xffffffffu, m2, 1);
            m2 += __shfl_xor_sync(0xffffffffu, m2, 2);
            asm volatile("st.shared.v2.f32 [%0], {%1, %2};" ::"r"(ew), "f"(mq), "f"(m2) : "memory");
            bar_sync<1, 256>();
            float4 e0, e1;
            asm volatile("ld.shared.v4.f32 {%0,%1,%2,%3}, [%4];" : "=f"(e0.x), "=f"(e0.y), "=f"(e0.z), "=f"(e0.w) : "r"(ex) : "memory");
            asm volatile("ld.shared.v4.f32 {%0,%1,%2,%3}, [%4];" : "=f"(e1.x), "=f"(e1.y), "=f"(e1.z), "=f"(e1.w) : "r"(ex + 16) : "memory");
            const float mean = 0.25f * ((e0.x + e0.z) + (e1.x + e1.z));
            const float d0 = e0.x - mean, d1 = e0.z - mean, d2 = e1.x - mean, d3 = e1.z - mean;
            const float var = fmaxf(((e0.y + e0.w) + (e1.y + e1.w)) * (1.f / D_) + 0.25f * (fmaf(d0, d0, d1 * d1) + fmaf(d2, d2, d3 * d3)), 0.f);
            const float r1 = rsq(var + 1e-5f), sc = rsq(fmaf(1e-5f, var + 1e-5f, var)), of = (sh - mean) * sc;
#pragma unroll
            for (int n = 0; n < 14; n++) r[n >> 2][n & 3] = pack2(fmaf(v[2 * n], sc, of), fmaf(v[2 * n + 1], sc, of));
#pragma unroll
            for (int i = 0; i < 3; i++) stsm4(ha[i], r[i][0], r[i][1], r[i][2], r[i][3]);
            stsm2(ha[3], r[3][0], r[3][1]);
            asm volatile("st.shared.v2.b32 [%0], {%1, %2};" ::"r"(ls), "r"(__float_as_uint(r1)), "r"(split2(-mean)) : "memory");
            TS0(24);
            asm volatile("bar.arrive 10, 288;" ::: "memory");
        }
        float a1[56];
        float rq[2], hb1[2], fb2[2];
        uint32_t qp[14], kp[14];
        const uint32_t ka = sb + OFF_K + warp * 896 + (lane & 7) * 112 + (lane >> 3) * 16;
        const uint32_t va = sb + OFF_V + (warp * 16 + (lane & 15)) * 112 + (lane >> 4) * 16;
        const uint32_t sta = sb + OFF_RSTD + warp * 64 + tq * 8;
        const uint32_t dA = desc_lo(OFF_A + wg * 8192, 16), dH = desc_lo(OFF_B, 1792), dU = desc_lo(OFF_B, 128);
        auto release = [&](uint32_t a) { mbar_arrive_if0(a, lane); };
        auto sched_fence = [&]() { mbar_wait(bar + 8 * B_LNIN, 0); };
        uint32_t rel = bar + 8 * (B_EMPTYQ + 6);
        auto g1_run = [&](uint32_t r0, uint32_t r1, bool gate = false) {
#pragma unroll 1
            for (uint32_t r = g1 ? r0 : r1; r < r1; r++) {
                const uint32_t s = slot(r), n = min(r + 1, 15u);
                if (gate) gate_wait(wg && r == r0);
                if (TSG1) TSD(64 + r);
                wg_fence();
#pragma unroll
                for (int k = 0; k < 4; k++) wgmma_n112<1, H_SW, H_H>(a1, dA + s * 1024 + k * 128, dH + s * 896 + k * 224, k ? 1 : r);
                wg_commit();
                wg_wait<1>();
                release(rel);
                rel = bar + 8 * (B_EMPTY + s);
                mbar_wait(bar + 8 * (B_FULL + slot(n)), phase(n));
            }
        };
        uint32_t solo = g1 && wg;
        asm volatile("" : "+r"(solo));
        solo = __shfl_sync(0xffffffffu, solo, 0);
        auto g1_wait = [&](uint32_t r) { mbar_wait(bar + 8 * (g1 ? B_FULL + r % 6 : B_LNIN), g1 && ((r / 6) & 1)); };
        auto g1_one = [&](uint32_t r) {
#pragma unroll 1
            for (uint32_t n = 0; n < solo; n++) {
                if (TSG1) TSD(64 + r);
                wg_fence();
#pragma unroll
                for (int k = 0; k < 4; k++) wgmma_n112<1, H_SW, H_H>(a1, dA + r % 6 * 1024 + k * 128, dH + r % 6 * 896 + k * 224);
                wg_commit();
                wg_wait<1>();
                release(rel);
                rel = bar + 8 * (B_EMPTY + r % 6);
            }
        };
        auto drain = [&]() { wg_wait<0>(); release(rel); rel = bar + 8 * B_NONE; };
        {
            float aq0[28], aq1[28], aq2[28];
            const uint32_t dW = desc_lo(OFF_B + (P & 1) * 16, 16);
            uint32_t xf[2][4][4];
            const uint32_t rb = mapa(bar + 8 * (B_EMPTYQ - 1), z ^ 1);
            auto fetch = [&](int kb, uint32_t (&f)[4][4]) {
                if (TSG1) TSD(178 + kb);
                mbar_wait(bar + 8 * (B_FULLQ + kb), 0);
                if (TSG1) TSD(170 + kb);
#pragma unroll
                for (int k = 0; k < 4; k++) ldsm4(xa[k] + ((XSLOT >> (4 * kb)) & 7) * 16384, f[k]);
            };
            auto mma = [&](int kb, uint32_t (&f)[4][4], int k0, int k1) {
                const uint32_t d0 = dW + ((WSLOT >> (4 * kb)) & 7) * 1536;
                wg_fence();
#pragma unroll
                for (int k = k0; k < k1; k++) {
                    const uint32_t d = d0 + (k >> 1) * 768 + (k & 1) * 128;
                    const int sc = k > 0 ? 1 : kb;
                    wgmma_n56_rs<H_SW, 1>(aq0, f[k], d, sc);
                    wgmma_n56_rs<H_SW, 1>(aq1, f[k], d + 256, sc);
                    wgmma_n56_rs<H_SW, 1>(aq2, f[k], d + 512, sc);
                }
            };
            auto retire = [&](int kb) {
                wg_commit();
                wg_wait<1>();
                mbar_arrive_if0(bar + 8 * (B_EMPTYQ + kb - 1), lane | (kb < 1));
                asm volatile("{\n.reg .pred p;\nsetp.eq.u32 p, %1, 0;\n@p mbarrier.arrive.shared::cluster.b64 _, [%0];\n}"
                             ::"r"(rb + 8 * kb), "r"(lane | ((uint32_t)(kb - 1) > 1)) : "memory");
            };
            auto stage = [&](int kb, uint32_t (&f)[4][4], uint32_t (&n)[4][4]) {
                mma(kb, f, 0, KS);
                retire(kb);
                fetch(kb + 1, n);
                if (KS < 4) { mma(kb, f, KS, 4); wg_commit(); }
            };
            fetch(0, xf[0]);
#pragma unroll 1
            for (int kb = 0; kb < 6; kb += 2) {
                stage(kb, xf[0], xf[1]);
                stage(kb + 1, xf[1], xf[0]);
            }
            mma(6, xf[0], 0, KS);
            retire(6);
            TS0(2);
            mbar_wait(bar + 8 * B_AUX, 0);
            {
                uint32_t (&f)[4] = xf[1][0];
                const uint2* mt = reinterpret_cast<const uint2*>(smem + OFF_STATS) + warp * 16 + g;
                const uint2 m0 = mt[0], m1 = mt[8];
                const uint32_t sel = tq == 0 ? 0x1010 : tq == 1 ? 0x3232 : 0x4444;
                f[0] = __byte_perm(m0.y, 0, sel); f[1] = __byte_perm(m1.y, 0, sel); f[2] = f[3] = 0;
                rq[0] = __uint_as_float(m0.x); rq[1] = __uint_as_float(m1.x);
                asm volatile("" : "+r"(f[0]), "+r"(f[1]), "+r"(f[2]), "+r"(f[3])::"memory");
                const uint32_t d = desc_lo(OFF_CSB + (P & 1) * 128, 0);
                mma(6, xf[0], KS, 4);
                wgmma_n56_rs<H_H, 0>(aq1, f, d + 64, 1);
                wgmma_n56_rs<H_H, 0>(aq2, f, d + 128, 1);
                wgmma_n56_rs<H_H, 0>(aq0, f, d, 1);
                wg_commit();
            }
            g1_wait(0);
            g1_run(0, wg ? 0 : NE);
            drain();
            pin(aq0); pin(aq1); pin(aq2);
            TSW(3);
            mbar_wait(bar + 8 * (B_EMPTYQ + 5), 0);
#pragma unroll
            for (int i = 0; i < 14; i++) { kp[i] = pack2(aq1[2 * i], aq1[2 * i + 1]); qp[i] = pack2(aq2[2 * i], aq2[2 * i + 1]); }
            stsm4(ka + 896, kp[1], kp[3], kp[5], kp[7]);
            stsm4(ka + 896 + 48, kp[7], kp[9], kp[11], kp[13]);
#pragma unroll
            for (int n = 0; n < 3; n++) stsm4(va + 896 + n * 32, qp[4 * n], qp[4 * n + 1], qp[4 * n + 2], qp[4 * n + 3]);
            stsm2(va + 896 + 96, qp[12], qp[13]);
            __syncwarp();
            mbar_arrive_if0(bar + 8 * B_QKV, tid - 224);
            release(bar + 8 * B_KV);
#pragma unroll
            for (int i = 0; i < 14; i++) qp[i] = pack2(aq0[2 * i], aq0[2 * i + 1]);
            TSW(4);
        }
        g1_run(wg ? 0 : NE, wg ? PRE1 : PRE0);
        {
            uint32_t kf[2][3][4], vf[2][3][4];
            const bool up0 = 2 * tq > g, up1 = 2 * tq + 1 > g, edge = (R | warp) == 0;
            float rk[2][2], fs[2][2], rs[3][2];
            mbar_wait(bar + 8 * (warp ? B_KV : B_HALO), 0);
            const uint32_t tag = *reinterpret_cast<volatile unsigned*>(smem + OFF_EP);
#pragma unroll
            for (int i = 0; i < 2; i++)
                asm volatile("ld.shared.v2.f32 {%0,%1}, [%2];" : "=f"(hb1[i]), "=f"(fb2[i]) : "r"(sb + OFF_BIAS + (warp * 16 + g + 8 * i) * 8) : "memory");
#pragma unroll
            for (int i = 0; i < 3; i++)
                asm volatile("ld.shared.v2.f32 {%0,%1}, [%2];" : "=f"(rs[i][0]), "=f"(rs[i][1]) : "r"(sta + i * 32) : "memory");
#pragma unroll
            for (int hd = 0; hd < 2; hd++) {
                ldsm4(ka + hd * 48, kf[hd][0]);
#pragma unroll
                for (int i = 0; i < 4; i++) { kf[hd][1][i] = kp[6 * hd + 2 * i]; kf[hd][2][i] = kp[6 * hd + 2 * i + 1]; }
                ldsm4t(va + hd * 48, vf[hd][0]); ldsm4t(va + hd * 48 + 32, vf[hd][1]);
                ldsm4t(ka + (OFF_V - OFF_K) + warp * 896 + hd * 48 + 1792, vf[hd][2]);
            }
            const uint32_t q0l = tq < 2 ? qp[6] : 0, q0h = tq < 2 ? qp[7] : 0, q1l = tq < 2 ? 0 : qp[6], q1h = tq < 2 ? 0 : qp[7];
            const uint32_t mk = (up0 ? 0xFFFFu : 0u) | (up1 ? 0xFFFF0000u : 0u);
            g1_run(wg ? PRE1 : PRE0, ATT_STEP);
#pragma unroll
            for (int i = 0; i < 4; i++) {
                rk[i >> 1][i & 1] = ((i & 1) ? up1 : up0) ? rs[i >> 1][i & 1] : rs[(i >> 1) + 1][i & 1];
                fs[i >> 1][i & 1] = rk[i >> 1][i & 1] * (rq[i >> 1] * (0.18898223650461362f * 1.4426950408889634f));
                asm volatile("" : "+f"(fs[i >> 1][i & 1])::"memory");
            }
            drain();
            sched_fence();
            TS0(19);
            float sc[2][3][4];
#pragma unroll
            for (int u = 0; u < 3; u++) {
#pragma unroll
                for (int i = 0; i < 8; i++) sc[i >> 2][u][i & 3] = 0.f;
                mma16816(sc[0][u], qp[0], qp[1], qp[2], qp[3], kf[0][u][0], kf[0][u][1]);
                mma16816(sc[1][u], q1l, q1h, qp[8], qp[9], kf[1][u][0], kf[1][u][1]);
            }
#pragma unroll
            for (int u = 0; u < 3; u++) {
                mma16816(sc[0][u], qp[4], qp[5], q0l, q0h, kf[0][u][2], kf[0][u][3]);
                mma16816(sc[1][u], qp[10], qp[11], qp[12], qp[13], kf[1][u][2], kf[1][u][3]);
            }
            float e[2][2][2], mx[2][2], sm[2][4];
#pragma unroll
            for (int hd = 0; hd < 2; hd++) {
                e[hd][0][0] = (up0 ? sc[hd][0][0] : sc[hd][1][0]) * fs[0][0];
                e[hd][0][1] = (up1 ? sc[hd][0][1] : sc[hd][1][1]) * fs[0][1];
                e[hd][1][0] = (up0 ? sc[hd][1][2] : sc[hd][2][2]) * fs[1][0];
                e[hd][1][1] = (up1 ? sc[hd][1][3] : sc[hd][2][3]) * fs[1][1];
                if (edge && up0) e[hd][0][0] = -1e30f;
                if (edge && up1) e[hd][0][1] = -1e30f;
                mx[hd][0] = fmaxf(e[hd][0][0], e[hd][0][1]);
                mx[hd][1] = fmaxf(e[hd][1][0], e[hd][1][1]);
            }
#pragma unroll
            for (int o = 1; o <= 2; o <<= 1)
#pragma unroll
                for (int i = 0; i < 4; i++) mx[i >> 1][i & 1] = fmaxf(mx[i >> 1][i & 1], __shfl_xor_sync(0xffffffffu, mx[i >> 1][i & 1], o));
            uint32_t pp[2][2], pu[2][2];
#pragma unroll
            for (int i = 0; i < 4; i++) {
                const float p0 = ex2(e[i >> 1][i & 1][0] - mx[i >> 1][i & 1]), p1 = ex2(e[i >> 1][i & 1][1] - mx[i >> 1][i & 1]);
                pp[i >> 1][i & 1] = pack2(p0 * rk[i & 1][0], p1 * rk[i & 1][1]);
                pu[i >> 1][i & 1] = pack2(p0, p1);
            }
            float ov[2][4][4];
#pragma unroll
            for (int hd = 0; hd < 2; hd++)
#pragma unroll
                for (int n = 0; n < 4; n++) {
                    ov[hd][n][0] = ov[hd][n][1] = ov[hd][n][2] = ov[hd][n][3] = 0.f;
                    mma16816(ov[hd][n], pp[hd][0] & mk, 0u, pp[hd][0] & ~mk, pp[hd][1] & mk, vf[hd][n >> 1][2 * (n & 1)], vf[hd][n >> 1][2 * (n & 1) + 1]);
                }
#pragma unroll
            for (int hd = 0; hd < 2; hd++) {
                sm[hd][0] = sm[hd][1] = sm[hd][2] = sm[hd][3] = 0.f;
                mma1688(sm[hd], pu[hd][0], pu[hd][1], 0x3F803F80u);
            }
#pragma unroll
            for (int hd = 0; hd < 2; hd++)
#pragma unroll
                for (int n = 0; n < 4; n++) mma1688(ov[hd][n], 0u, pp[hd][1] & ~mk, vf[hd][2][n]);
            sched_fence();
            TS0(18);
            bar_sync<1, 256>();
            g1_one(ATT_STEP);
#pragma unroll
            for (int i = 0; i < 4; i++) asm volatile("" : "+f"(sm[i >> 1][2 * (i & 1)])::"memory");
            uint32_t op[16];
            op[14] = op[15] = tag & 0x3FFF;
#pragma unroll
            for (int i = 0; i < 4; i++) sm[i >> 1][i & 1] = rcp(sm[i >> 1][2 * (i & 1)]);
#pragma unroll
            for (int n = 0; n < 7; n++) {
                const bool hb = n > 3 || (n == 3 && tq >= 2);
#pragma unroll
                for (int h = 0; h < 2; h++) {
                    const float r = hb ? sm[1][h] : sm[0][h];
                    const float x0 = hb ? ov[1][n >= 3 ? n - 3 : 0][2 * h] : ov[0][n <= 3 ? n : 0][2 * h];
                    const float x1 = hb ? ov[1][n >= 3 ? n - 3 : 0][2 * h + 1] : ov[0][n <= 3 ? n : 0][2 * h + 1];
                    op[2 * n + h] = pack2(x0 * r, x1 * r);
                }
            }
#pragma unroll
            for (int i = 0; i < 14; i++) asm volatile("" : "+r"(op[i])::"memory");
            g1_wait(ATT_STEP + 1);
            if (NQ) { g1_one(ATT_STEP + 1); g1_wait(ATT_STEP + 2); }
#pragma unroll
            for (int n = 0; n < 4; n++) stsm4(xa[n] + OFF_OST, op[4 * n], op[4 * n + 1], op[4 * n + 2], op[4 * n + 3]);
            __syncwarp();
            release(bar + 8 * B_OST);
            g1_one(ATT_STEP + 1 + NQ);
            g1_wait(ATT_STEP + 2 + NQ);
            TSW(5);
        }
        const uint32_t peer = z ^ 1;
        drain();
        g1_run(wg ? ATT_STEP + 2 + NQ : ATT_STEP, 16, true);
        gate_open(wg | !g1);
        mbar_wait(bar + 8 * B_FREE, 0);
        drain();
        pin(a1);
        TSW(6);
        send_half(a1, mapa(sb + OFF_RECV1 + wg * 7168, peer), mapa(bar + 8 * (B_RECV1 + wg), peer), t, g1);
#pragma unroll
        for (int i = 0; i < 28; i++) a1[i] = fmaf(a1[i], 0.5f, hb1[(i >> 1) & 1]);
        pin<0, 28>(a1);
        if (g1) {
            uint32_t p[14];
            const int ub = 2 * q + wg, zz = ub >= 14 ? 1 : 0;
            uint8_t* u0 = scr + G_BIMG + ((8 + ub) * 4 + j) * BLK + (7 * z + 6 * zz) * 1024 + w4 * 256 + lane * 4;
            uint8_t* u1 = u0 - (z & zz ? BLK : 0);
            mbar_wait(bar + 8 * (B_RECV1 + wg), (uint32_t)(((uint64_t)u0 | (uint64_t)u1) >> 63));
            TSW(8);
            recv_half(p, sb + OFF_RECV1 + wg * 7168, t);
#pragma unroll
            for (int i = 0; i < 14; i++) {
                stg32((i < 2 ? u0 : u1) + (i >> 1) * 1024 + (i & 1) * 128,
                      pack2(gelu_half(fmaf(bf_lo(p[i]), 0.5f, a1[2 * i])), gelu_half(fmaf(bf_hi(p[i]), 0.5f, a1[2 * i + 1]))));
            }
            TSW(9);
        }
        float a2[56];
#pragma unroll 1
        for (uint32_t i = 0; i < 4; i++) {
            const uint32_t s = slot(r_o + i);
            mbar_wait(bar + 8 * (B_FULL + s), phase(r_o + i));
            TSD(64 + 17 + i);
            wg_fence();
#pragma unroll
            for (int k = 0; k < 4; k++) wgmma_n112<0, H_SW, H_U>(a2, dA + s * 1024 + k * 2, dU + s * 896 + k * 16, k ? 1 : i);
            wg_commit();
            wg_wait<1>();
            release(rel);
            rel = bar + 8 * (B_EMPTY + s);
        }
        drain();
        TSW(10);
#pragma unroll 1
        for (uint32_t r = r_u; r < r_u + 14; r++) {
            const uint32_t s = slot(r);
            gate_wait(wg && r == r_u + 14 - NS2);
            mbar_wait(bar + 8 * (B_FULL + s), phase(r));
            TSD(85 + r - r_u);
            wg_fence();
#pragma unroll
            for (int k = 0; k < 4; k++) wgmma_n112<1, H_SW, H_U>(a2, dA + s * 1024 + k * 128, dU + s * 896 + k * 16);
            wg_commit();
            wg_wait<1>();
            release(rel);
            rel = bar + 8 * (B_EMPTY + s);
        }
        gate_open(wg);
        mbar_wait(bar + 8 * B_UDONE, 0);
        wg_wait<0>();
        pin(a2);
        TSW(11);
        {
            const uint32_t rbuf = mapa(sb + OFF_RECV2 + wg * 8192 + t * 16, peer) - (z ? 0 : 2048), rbar = mapa(bar + 8 * (B_RECV2 + wg), peer);
#pragma unroll
            for (int i = 3; i >= 0; i--) send8(a2 + 24 + 8 * i, rbuf + i * 2048, rbar, i | z);
            uint32_t xr[4][4];
            mbar_wait(bar + 8 * B_XR, 0);
#pragma unroll
            for (int k = 0; k < 4; k++) ldsm4(xa[k] + slot(r_u + 14) * 16384, xr[k]);
#pragma unroll
            for (int i = 0; i < 32; i++) a2[i] += ((i & 1) ? bf_hi(xr[i >> 3][(i >> 1) & 3]) : bf_lo(xr[i >> 3][(i >> 1) & 3])) + fb2[(i >> 1) & 1];
            pin<0, 32>(a2);
            const uint32_t oa = sb + OFF_OUT + (warp * 16 + (lane >> 3)) * 128 + (((lane ^ (lane >> 3)) & 7) << 4);
            const uint32_t oo = (q * 128 + warp * 16 + (lane >> 3)) * 896 + j * 224 + z * 128 + (lane & 7) * 16;
            uint8_t* og = out + oo;
            mbar_wait(bar + 8 * (B_RECV2 + wg), (oa | oo | (uint32_t)((uint64_t)og >> 32)) >> 31);
            TSW(12);
            uint32_t u[16];
#pragma unroll
            for (int i = 0; i < 4; i++)
                asm volatile("ld.shared.v4.b32 {%0,%1,%2,%3}, [%4];" : "=r"(u[4 * i]), "=r"(u[4 * i + 1]), "=r"(u[4 * i + 2]), "=r"(u[4 * i + 3]) : "r"(sb + OFF_RECV2 + wg * 8192 + i * 2048 + t * 16) : "memory");
#pragma unroll
            for (int e = 0; e < 16; e++) u[e] = pack2(a2[2 * e] + bf_lo(u[e]), a2[2 * e + 1] + bf_hi(u[e]));
#pragma unroll
            for (int i = 0; i < 4; i++) stsm4(xa[i] + OFF_OUT, u[4 * i], u[4 * i + 1], u[4 * i + 2], u[4 * i + 3]);
            __syncwarp();
#pragma unroll
            for (int i = 0; i < 4; i++)
                asm volatile("ld.shared.v4.b32 {%0,%1,%2,%3}, [%4];" : "=r"(u[4 * i]), "=r"(u[4 * i + 1]), "=r"(u[4 * i + 2]), "=r"(u[4 * i + 3]) : "r"((oa ^ ((i & 1) << 6)) + i * 512) : "memory");
            if ((lane & 7) < 8 - 2 * z) {
#pragma unroll
                for (int i = 0; i < 4; i++)
                    asm volatile("st.global.v4.b32 [%0], {%1,%2,%3,%4};" ::"l"(og + i * 3584), "r"(u[4 * i]), "r"(u[4 * i + 1]), "r"(u[4 * i + 2]), "r"(u[4 * i + 3]) : "memory");
            }
        }
        TSW(13);
    } else if (warp < 12) {
        asm volatile("setmaxnreg.dec.sync.aligned.u32 64;");
        const int hw = warp - 8, t = tid & 127;
        reinterpret_cast<uint32_t*>(smem + OFF_ONES)[t] = t < 64 ? 0x3F803F80u : 0;
        fence_async_smem();
        bar_sync<12, 128>();
        while (clock32() - t_in < DLY1) {}
        if (wline < 9408 && !wfirst) l2_prefetch(reinterpret_cast<const uint8_t*>(wqkv) + wline * 128);
        uint8_t* cscell = scr + G_CS + ((P * 8 + R) * 2 + z) * 512 + (t >> 2) * 16;
        if ((lane & 3) == 0) cell_put(cscell, 0, 0, 0);
        uint8_t* cells = scr + G_HALO + ((R * 8 + P) * 2 + z) * 3584 + min(t, 111) * 16;
        cell_put(cells, 0, 0, 0);
        cell_put(cells + 1792, 0, 0, 0);
        const unsigned e1 = epoch();
        const uint32_t bv1 = ldg_u16(b1 + (g1 ? q * 128 : 0) + t), bv2 = ldg_u16(b2 + q * 128 + t);
        {
            const uint32_t da = desc_lo(OFF_B + min((R & 1) * 2 + z, 2) * 4096, 16), db = desc_lo(OFF_ONES, 128);
            float c0[4];
            const int st = R & 6 & ~ROT;
            mbar_wait(bar + 8 * (B_FULLQ + st), 0);
            mbar_wait(bar + 8 * (B_FULLQ + st + 1), 0);
            TSH(47);
            wg_fence();
#pragma unroll
            for (int k = 0; k < 8; k++)
                wgmma_n8<1, H_SW, H_H>(c0, da + ((WSLOT >> (4 * st + (k & 4))) & 7) * 1536 + (k & 2) * 384 + (k & 1) * 128, db + (k >= 4 && R >= 6 ? 16 : 0), k);
            wg_commit();
            wg_wait<0>();
            pin(c0);
            if ((lane & 3) == 0) cell_put(cscell, __float_as_uint(c0[0]), __float_as_uint(c0[2]), e1);
            if (lane < 4) asm volatile("mbarrier.arrive.shared::cluster.b64 _, [%0];" ::"r"(mapa(bar + 8 * (B_EMPTYQ + st + (lane >> 1)), lane & 1)) : "memory");
            TSH(43);
        }
        mbar_wait(bar + 8 * (B_FULLQ + GATHER), 0);
        TSH(39);
        {
            const bool cw = hw < 3;
            const uint8_t* src = cw ? scr + G_CS + P * 8192 + t * 16 : scr + G_STATS + (z * 1024 + R * 128 + lane) * 16;
            uint32_t a[5], d[5], bad;
            do {
                bad = 0;
#pragma unroll
                for (int i = 0; i < 4; i++) bad |= cell_get(src + i * (cw ? 2048 : 512), a[i], d[i], e1);
                if (t >= 120) bad |= cell_get(src - (R ? 512 : 0), a[4], d[4], e1);
            } while (bad);
            TSH(45);
            if (cw) {
                uint4* cb = reinterpret_cast<uint4*>(smem + OFF_CSB) + (t >> 3) * 16 + (t & 7);
                const uint32_t lo = split2((__uint_as_float(a[0]) + __uint_as_float(a[1])) + (__uint_as_float(a[2]) + __uint_as_float(a[3])));
                const uint32_t hi = split2((__uint_as_float(d[0]) + __uint_as_float(d[1])) + (__uint_as_float(d[2]) + __uint_as_float(d[3])));
                cb[0] = make_uint4(lo, lo, 0, 0);
                cb[8] = make_uint4(hi, hi, 0, 0);
            } else {
                uint2* st = reinterpret_cast<uint2*>(smem + OFF_STATS) + lane;
                uint32_t* rd = reinterpret_cast<uint32_t*>(smem + OFF_RSTD) + lane;
#pragma unroll
                for (int i = 0; i < 4; i++) { st[32 * i] = make_uint2(a[i], d[i]); rd[8 + 32 * i] = a[i]; }
                if (t >= 120) rd[-24] = a[4];
            }
            fence_async_smem();
            __syncwarp();
            mbar_arrive_if0(bar + 8 * B_AUX, lane);
            TSH(41);
            reinterpret_cast<float2*>(smem + OFF_BIAS)[t] = make_float2(0.5f * bf_lo(bv1), bf_lo(bv2));
            __syncwarp();
            mbar_arrive_if0(bar + 8 * B_KV, lane);
        }
        {
            uint2* kv = reinterpret_cast<uint2*>(smem + OFF_K) + min(t, 111);
            mbar_wait(bar + 8 * B_QKV, 0);
            uint2 k2 = kv[896], v2 = kv[1792 + (OFF_V - OFF_K) / 8];
            cell_put(cells, k2.x, k2.y, e1);
            cell_put(cells + 1792, v2.x, v2.y, e1);
            k2 = v2 = make_uint2(0, 0);
            if (DH) delay(DH);
            if (R > 0) while (cell_get(cells - 16 * 3584, k2.x, k2.y, e1) | cell_get(cells - 16 * 3584 + 1792, v2.x, v2.y, e1)) {}
            kv[0] = k2;
            kv[(OFF_V - OFF_K) / 8] = v2;
            mbar_wait(bar + 8 * B_KV, 0);
            __syncwarp();
            mbar_arrive_if0(bar + 8 * B_HALO, lane);
            TSH(40);
        }
        if (hw == 3) {
            mbar_wait(bar + 8 * B_OST, 0);
            if (elect()) {
                unsigned* oc = ctr + C_O + (R * 2 + (P >> 2)) * 32;
                asm volatile("mbarrier.arrive.relaxed.cluster.shared::cluster.b64 _, [%0];" ::"r"(mapa(bar + 8 * B_FREE, z ^ 1)) : "memory");
                fence_async_smem();
                tma2d_store(&mp.ost, sb + OFF_OST, z * 64, P * 1024 + R * 128);
                bulk_commit();
                delay(DO);
                red_relaxed(oc, 1);
                TS(21);
                bulk_wait_read();
                TS(20);
                asm volatile("mbarrier.arrive.relaxed.cluster.shared::cluster.b64 _, [%0];" ::"r"(mapa(bar + 8 * B_UDONE, z ^ 1)) : "memory");
            }
        } else {
            const uint32_t tag = e1 & 0x3FFF;
            const uint32_t ca = sb + OFF_A + lane * 128 + ((~lane & 7) << 4) + (lane >> 3) * 4, cb = sb + OFF_B + lane * 132;
            uint32_t par = 0x3F;
#pragma unroll 1
            for (uint32_t i = hw; i < 18;) {
                const uint32_t s = slot(r_o + i);
                const bool isa = i < 4;
                const uint32_t a0 = isa ? ca + s * 16384 : cb + s * BLK, a3 = a0 - (isa ? 0 : (lane & 16) * 132);
                mbar_wait(bar + 8 * (B_LAND + s), (par >> s) & 1);
                par ^= 1 << s;
                bool ok = true;
#pragma unroll
                for (int k = 0; k < 4; k++) {
                    uint32_t v;
                    asm volatile("ld.shared.b32 %0, [%1];" : "=r"(v) : "r"((k < 3 ? a0 : a3) + k * 4096) : "memory");
                    ok &= (v == (isa ? tag : ~0u)) == isa;
                }
                if (__all_sync(0xffffffffu, ok)) {
                    mbar_arrive_if0(bar + 8 * (B_FULL + s), lane);
                    if (i == 0 || i == 4) TS(i ? 30 : 29);
                    i += 3;
                } else if (elect()) {
                    TS(31);
                    fetch_x(i);
                }
            }
        }
    } else {
        asm volatile("setmaxnreg.dec.sync.aligned.u32 32;");
        auto wait_free = [&](uint32_t r, uint32_t first) {
            const uint32_t a = r < 6 ? B_EMPTYQ + ((first >> (4 * r)) & 7) : B_EMPTY + slot(r);
            mbar_wait(bar + 8 * a, r < 6 ? 0 : phase(r) ^ 1);
        };
        if (warp == 12) {
            TS(14);
            if (elect()) {
#pragma unroll 1
                for (int kb = 1; kb < 7; kb++) {
                    if (kb == 1) while (clock32() - t_in < DLY2) {}
                    if (kb >= QDEPTH) { mbar_wait(bar + 8 * (B_FULLQ + kb - QDEPTH), 0); TS(25 + kb - QDEPTH); }
                    if (kb >= 5) mbar_wait(bar + 8 * (B_EMPTYQ + kb - 5), 0);
                    x_load(kb);
                    w_load(kb);
                }
                TS(17);
                ld_relaxed(ctr + C_O + ((q & ~1) + z) * 32);
                mbar_wait(bar + 8 * B_LNFREE, 0);
                if (!g1) {
                    const int ic = (q - 14) * 8 + j * 2 + z, rot = ic >> 3;
                    mbar_wait(bar + 8 * (B_EMPTYQ + 2), 0);
                    mbar_expect(bar + 8 * B_GO, 2 * BLK);
#pragma unroll 1
                    for (int i = 0; i < 2; i++) tma4d(sb + OFF_A + i * BLK, &mp.wo, 0, 0, (z * 2 + i) * 14, ic >> 1, bar + 8 * B_GO);
                    mbar_wait(bar + 8 * B_GO, 0);
#pragma unroll 1
                    for (int i = 0; i < 2; i++) {
                        uint8_t* dst = scr + G_BIMG + (ic * 2 + i) * BLK;
                        bulk_store(dst + rot * 6144, sb + OFF_A + i * BLK, 8192);
                        bulk_store(dst + (rot ^ 1) * 8192, sb + OFF_A + i * BLK + 8192, 6144);
                    }
                    bulk_commit();
                    bulk_wait_all();
                    publish(ctr + C_WO);
                    TS(44);
                }
#pragma unroll 1
                for (uint32_t r = 0; r < r_o; r++) {
                    const uint32_t s = slot(r), fb = bar + 8 * (B_FULL + s);
                    wait_free(r, 0x654320u);
                    mbar_expect(fb, 16384);
                    tma3d(sb + OFF_A + s * 16384, &mp.w1, 0, z * 1024 + r * 64, 2 * q, fb);
                    TS(99 + r);
                }
                mbar_wait(bar + 8 * B_OST, 0);
#pragma unroll 1
                for (uint32_t i = 0; i < 2; i++) {
                    wait_free(r_o + i, 0x654320u);
                    mbar_expect(bar + 8 * (B_LAND + slot(r_o + i)), 16384);
                }
                poll(ctr + C_O + ((q & ~1) + z) * 32, epoch() * 8);
                TS(32);
                fetch_x(0, false);
                fetch_x(1, false);
                TS(99 + 17);
#pragma unroll 1
                for (uint32_t i = 2; i < 4; i++) {
                    wait_free(r_o + i, 0x654320u);
                    fetch_x(i);
                    TS(99 + 17 + i);
                }
#pragma unroll 1
                for (uint32_t i = 0; i < 14; i++) {
                    const uint32_t r = r_u + i, s = slot(r), fb = bar + 8 * (B_FULL + s);
                    wait_free(r, 0x654320u);
                    mbar_expect(fb, 16384);
                    tma3d(sb + OFF_A + s * 16384, &mp.w2, 0, (14 * z + (i < 7 ? 2 * i : 2 * i - 13)) * 64, 2 * q, fb);
                    TS(99 + 21 + i);
                }
                wait_free(r_u + 14, 0);
                mbar_expect(bar + 8 * B_XR, 16384);
                tma2d(sb + OFF_A + slot(r_u + 14) * 16384, &mp.xn, j * 112 + z * 64, q * 128, bar + 8 * B_XR);
            }
        } else if (warp == 13) {
            if (elect()) {
#pragma unroll 1
                for (int ph = g1 ? 0 : 1; ph < 4; ph++) {
                    const uint8_t* src = ph == 0 ? scr + G_HIMG + (64 * z + j) * BLK : scr + G_BIMG + ((ph == 1 ? 4 * z : 6 + 14 * z + ph) * 4 + j) * BLK;
                    const uint32_t r0 = ph == 0 ? 0 : r_o + (ph == 1 ? 0 : 7 * ph - 10), r1 = r_o + (ph == 0 ? 0 : 7 * ph - 3);
#pragma unroll 1
                    for (uint32_t r = r0; r < r1; r++, src += ph < 2 ? 4 * BLK : 8 * BLK) {
                        const uint32_t s = slot(r), fb = bar + 8 * ((ph < 2 ? B_FULL : B_LAND) + s);
                        wait_free(r, 0x644332u);
                        mbar_expect(fb, BLK);
                        mbar_wait(bar + 8 * (B_GO + ph), 0);
                        bulk_load(sb + OFF_B + s * BLK, src, BLK, fb);
                        TS(134 + 16 + (ph > 0) + r - r_o);
                    }
                }
            }
        } else if (warp == 14) {
            uint8_t* stcell = scr + G_STATS + ((lane & 1) * 1024 + 8 * b + (lane >> 1)) * 16;
            if (lane < 16) cell_put(stcell, 0, 0, 0);
            const unsigned ev = ld_relaxed(ctr + C_LN);
            uint8_t* hb = scr + G_HIMG + (b & ~3) * BLK;
            const unsigned e1 = (ev >> 7) + 1;
            if (lane == 0) {
                *reinterpret_cast<volatile unsigned*>(smem + OFF_EP) = e1;
                mbar_arrive(bar + 8 * B_EP);
                TS(36);
            }
            bar_sync<10, 288>();
            if (elect()) {
                fence_async_smem();
                TS(42);
                tma4d_store(&mp.hst, sb + OFF_A, 0, 0, b & 3, b & ~3);
                bulk_commit();
            }
            __syncwarp();
            if (lane < 16) {
                const uint2 v = reinterpret_cast<const uint2*>(smem + OFF_LNST)[lane];
                cell_put(stcell, v.x, v.y, e1);
            }
            bulk_wait_all();
            __syncwarp();
            TS(63);
            unsigned rb = 0;
#pragma unroll
            for (int i = 0; i < 4; i++) rb |= ld_relaxed(reinterpret_cast<const unsigned*>(hb + i * BLK + ((b & 3) * 28 + min(lane, 27)) * 128));
            if (lane == 0) {
                mbar_arrive(bar + 8 * B_LNFREE);
                red_relaxed(ctr + C_LN, 1 + (rb & (sb >> 31)));
                TS(37);
                ld_relaxed(ctr + C_U + z * 64);
                ld_relaxed(ctr + C_U + z * 64 + 32);
#pragma unroll 1
                for (int ph = g1 ? 0 : 1; ph < 4; ph++) {
                    if (ph) mbar_wait(bar + 8 * (ph == 1 ? B_HALO : g1 ? B_RECV1 : B_OST), 0);
                    poll(ctr + ph * 32 + (ph >> 1) * z * 64, e1 * (ph == 0 ? 128 : ph == 1 ? 16 : 56));
                    fence_async_global();
                    mbar_arrive(bar + 8 * (B_GO + ph));
                    if (ph != 1) TS(ph == 0 ? 33 : 32 + ph);
                }
            }
        } else {
            if ((sb & 0x3FFFF) != SB0) __trap();
            if (elect()) {
#pragma unroll 1
                for (int i = 3; i < 10; i++) asm volatile("prefetch.tensormap [%0];" ::"l"(reinterpret_cast<const CUtensorMap*>(&mp) + i) : "memory");
            }
            __syncwarp();
            mbar_watch(bar + 8 * B_KV, 0);
#pragma unroll 1
            for (int i = g1 ? 0 : 8; i < 8; i++) {
                uint32_t l = (7 * z + (q >= 7 ? 6 : 0)) * 8 + (i & 3) * 14 + min(lane >> 1, 13);
                if (l >= 112) l -= 112;
                cell_put(scr + G_BIMG + ((8 + 2 * q + (i >> 2)) * 4 + j) * BLK + l * 128 + (l & 24) * 4 + (lane & 1) * 16, ~0u, ~0u, ~0u);
            }
            __threadfence();
            __syncwarp();
            mbar_arrive_if0(bar + 8 * B_FREE, lane);
            TS(59);
#pragma unroll 1
            for (int i = g1 ? 0 : 2; i < 2; i++) {
                mbar_watch(bar + 8 * (B_RECV1 + i), 0);
                delay(DU);
                if (lane == 0) red_relaxed(ctr + C_U + ((q >= 7 ? 2 : 0) + i) * 32, 1);
                TS(22 + i);
            }
            mbar_watch(bar + 8 * B_RECV2, 0);
            mbar_watch(bar + 8 * (B_RECV2 + 1), 0);
        }
    }
}

typedef CUresult (*EncodeFn)(CUtensorMap*, CUtensorMapDataType, cuuint32_t, void*, const cuuint64_t*, const cuuint64_t*, const cuuint32_t*,
                             const cuuint32_t*, CUtensorMapInterleave, CUtensorMapSwizzle, CUtensorMapL2promotion, CUtensorMapFloatOOBfill);

void encode(EncodeFn fn, CUtensorMap* m, const void* p, int rank, const cuuint64_t* dims, const cuuint64_t* strides, const cuuint32_t* box, bool swz) {
    const cuuint32_t es[4] = {1, 1, 1, 1};
    fn(m, CU_TENSOR_MAP_DATA_TYPE_BFLOAT16, rank, const_cast<void*>(p), dims, strides, box, es, CU_TENSOR_MAP_INTERLEAVE_NONE,
       swz ? CU_TENSOR_MAP_SWIZZLE_128B : CU_TENSOR_MAP_SWIZZLE_NONE, CU_TENSOR_MAP_L2_PROMOTION_L2_128B, CU_TENSOR_MAP_FLOAT_OOB_FILL_NONE);
}

}

extern "C" void kernel_launch(void* const* d_in, const int* in_sizes, int n_in, void* d_out, int out_size) {
    const __nv_bfloat16* x = (const __nv_bfloat16*)d_in[0];
    const __nv_bfloat16* wqkv = (const __nv_bfloat16*)d_in[1];
    const __nv_bfloat16* wo = (const __nv_bfloat16*)d_in[2];
    const __nv_bfloat16* w1 = (const __nv_bfloat16*)d_in[4];
    const __nv_bfloat16* b1 = (const __nv_bfloat16*)d_in[5];
    const __nv_bfloat16* w2 = (const __nv_bfloat16*)d_in[6];
    const __nv_bfloat16* b2 = (const __nv_bfloat16*)d_in[7];

    void* fp = nullptr;
    cudaDriverEntryPointQueryResult qr;
    cudaGetDriverEntryPoint("cuTensorMapEncodeTiled", &fp, cudaEnableDefault, &qr);
    EncodeFn fn = (EncodeFn)fp;
    void* sp = nullptr;
    cudaGetSymbolAddress(&sp, g_scratch);
    uint8_t* scr = (uint8_t*)sp;
    void *o = scr + G_O, *himg = scr + G_HIMG;

    Maps mp;
    { cuuint64_t d[3] = {64, 2048, 7}, s[2] = {896, 128}; cuuint32_t bx[3] = {64, 16, 7}; encode(fn, &mp.xl, x, 3, d, s, bx, true); }
    { cuuint64_t d[2] = {896, 1024}, s[1] = {1792}; cuuint32_t bx[2] = {64, 128}; encode(fn, &mp.x, x, 2, d, s, bx, true); }
    { cuuint64_t d[3] = {448, 448, 3}, s[2] = {2688, 896}; cuuint32_t bx[3] = {64, 32, 3}; encode(fn, &mp.wqkv, wqkv, 3, d, s, bx, true); }
    { cuuint64_t d[3] = {64, 2048, 28}, s[2] = {3584, 128}; cuuint32_t bx[3] = {64, 64, 2}; encode(fn, &mp.w1, w1, 3, d, s, bx, true); }
    { cuuint64_t d[3] = {64, 1792, 32}, s[2] = {4096, 128}; cuuint32_t bx[3] = {64, 64, 2}; encode(fn, &mp.w2, w2, 3, d, s, bx, true); }
    { cuuint64_t d[4] = {64, 28, 4, 128}, s[3] = {128, 3584, BLK}; cuuint32_t bx[4] = {64, 28, 1, 4}; encode(fn, &mp.hst, himg, 4, d, s, bx, false); }
    { cuuint64_t d[2] = {448, 2048}, s[1] = {896}; cuuint32_t bx[2] = {64, 128}; encode(fn, &mp.xn, x, 2, d, s, bx, true); }
    { cuuint64_t d[2] = {64, 8 * 2048}, s[1] = {128}; cuuint32_t bx[2] = {64, 128}; encode(fn, &mp.old_, o, 2, d, s, bx, true); }
    { cuuint64_t d[2] = {128, 8 * 1024}, s[1] = {256}; cuuint32_t bx[2] = {64, 128}; encode(fn, &mp.ost, o, 2, d, s, bx, true); }
    { cuuint64_t d[4] = {8, 56, 56, 8}, s[3] = {896, 16, 56 * 896}; cuuint32_t bx[4] = {8, 64, 14, 1}; encode(fn, &mp.wo, wo, 4, d, s, bx, false); }

    cudaFuncSetAttribute(fused_kernel, cudaFuncAttributeMaxDynamicSharedMemorySize, SMEM_BYTES);
    fused_kernel<<<128, 512, SMEM_BYTES>>>(x, wqkv, b1, b2, scr, (uint8_t*)d_out, mp);
}
```

```cpp
#include <cuda_runtime.h>
#include <cuda.h>
#include <cuda_bf16.h>
#include <stdint.h>

namespace {

constexpr int S_ = 2048, D_ = 448;
constexpr uint32_t BLK = 14336;

constexpr uint32_t G_HIMG = 0;
constexpr uint32_t G_BIMG = G_HIMG + 32 * 4 * BLK;
constexpr uint32_t G_O = G_BIMG + 36 * 4 * BLK;
constexpr uint32_t G_STATS = G_O + 8 * S_ * 128;
constexpr uint32_t G_CS = G_STATS + S_ * 16;
constexpr uint32_t G_HALO = G_CS + 8 * 4 * 2048;
constexpr uint32_t G_CTR = G_HALO + 128 * 3584;
constexpr uint32_t G_END = G_CTR + (192 + 16 * 32) * 4;
__device__ __align__(1024) uint8_t g_scratch[G_END];

constexpr int C_LN = 0, C_WO = 32, C_U = 64, C_O = 192;

#define TSX(sel, id)
#define TS(id)
#define TS0(id)
#define TSH(id)
#define TSW(id)
#define TG(id)

#define TSG1 0
#define TSD(id)
#define QDEPTH 3
#define ROT 6
#define KS 3
#define DLY1 2200
#define DLY2 1600
#define GATHER 3
#define NS2 3
#define NE 2
#define PRE0 8
#define PRE1 5
#define DU 150
#define DO 200
#define DH 400
#define NQ 0
constexpr uint32_t OFF_A = 0;
constexpr uint32_t OFF_B = 98304;
constexpr uint32_t OFF_X = 184320;
constexpr uint32_t OFF_K = 196608;
constexpr uint32_t OFF_V = OFF_K + 9 * 896;
constexpr uint32_t OFF_OST = OFF_X, OFF_RECV2 = OFF_X, OFF_RECV1 = OFF_X + 16384, OFF_OUT = OFF_X + 16384;
constexpr uint32_t OFF_CSB = 221184;
constexpr uint32_t OFF_ONES = OFF_CSB + 3072;
constexpr uint32_t OFF_STATS = OFF_ONES + 512;
constexpr uint32_t OFF_BIAS = OFF_STATS + 1024;
constexpr uint32_t OFF_LNX = OFF_BIAS + 1024;
constexpr uint32_t OFF_RSTD = OFF_LNX + 512;
constexpr uint32_t OFF_LNST = 229376;
constexpr uint32_t OFF_EP = OFF_LNST + 128;
constexpr uint32_t OFF_BAR = OFF_EP + 16;
constexpr uint32_t OFF_TS = OFF_BAR + 8 * 48;
constexpr uint32_t SMEM_BYTES = OFF_TS;

enum : int {
    B_FULLQ = 0, B_LNIN = 7, B_EMPTYQ = 8, B_FULL = 15, B_EMPTY = 21, B_AUX = 27, B_QKV, B_HALO, B_FREE, B_RECV1, B_RECV2 = B_RECV1 + 2,
    B_EP = B_RECV2 + 2, B_OST, B_LNFREE, B_UDONE, B_NONE, B_GO, B_XR = B_GO + 4, B_KV, B_COUNT, B_LAND = B_FULLQ
};
constexpr uint32_t XSLOT = 0x5432154u;
constexpr uint32_t WSLOT = 0x3421034u;
#define ATT_STEP 10

__device__ __forceinline__ uint32_t smem_u32(const void* p) { return (uint32_t)__cvta_generic_to_shared(p); }
__device__ __forceinline__ void mbar_init(uint32_t a, int c) { asm volatile("mbarrier.init.shared::cta.b64 [%0], %1;" ::"r"(a), "r"(c) : "memory"); }
__device__ __forceinline__ void mbar_expect(uint32_t a, uint32_t b) { asm volatile("mbarrier.arrive.expect_tx.shared::cta.b64 _, [%0], %1;" ::"r"(a), "r"(b) : "memory"); }
__device__ __forceinline__ void mbar_arrive(uint32_t a) { asm volatile("mbarrier.arrive.shared::cta.b64 _, [%0];" ::"r"(a) : "memory"); }
__device__ __forceinline__ void mbar_arrive_if0(uint32_t a, uint32_t sel) {
    asm volatile("{\n.reg .pred p;\nsetp.eq.u32 p, %1, 0;\n@p mbarrier.arrive.shared::cta.b64 _, [%0];\n}" ::"r"(a), "r"(sel) : "memory");
}
__device__ __forceinline__ void mbar_wait(uint32_t a, uint32_t parity) {
    asm volatile("{\n.reg .pred p;\nW0:\nmbarrier.try_wait.parity.shared::cta.b64 p, [%0], %1;\n@!p bra W0;\n}\n" ::"r"(a), "r"(parity) : "memory");
}
__device__ __forceinline__ void mbar_watch(uint32_t a, uint32_t parity) {
    asm volatile(
        "{\n.reg .pred p;\n.reg .u32 n;\nmov.u32 n, 0;\n"
        "W0:\nmbarrier.try_wait.parity.shared::cta.b64 p, [%0], %1;\n@p bra W1;\n"
        "add.u32 n, n, 1;\nsetp.lt.u32 p, n, 4194304;\n@p bra W0;\ntrap;\nW1:\n}\n" ::"r"(a), "r"(parity) : "memory");
}
__device__ __forceinline__ bool elect() {
    uint32_t r;
    asm volatile("{\n.reg .pred p;\nelect.sync _|p, 0xffffffff;\nselp.u32 %0, 1, 0, p;\n}" : "=r"(r));
    return r;
}
__device__ __forceinline__ uint32_t mapa(uint32_t a, uint32_t cta) { uint32_t r; asm("mapa.shared::cluster.u32 %0, %1, %2;" : "=r"(r) : "r"(a), "r"(cta)); return r; }
__device__ __forceinline__ void tma2d(uint32_t dst, const CUtensorMap* m, int c0, int c1, uint32_t bar) {
    asm volatile("cp.async.bulk.tensor.2d.shared::cluster.global.mbarrier::complete_tx::bytes [%0], [%1, {%3, %4}], [%2];" ::"r"(dst), "l"(m), "r"(bar), "r"(c0), "r"(c1) : "memory");
}
__device__ __forceinline__ void tma3d(uint32_t dst, const CUtensorMap* m, int c0, int c1, int c2, uint32_t bar) {
    asm volatile("cp.async.bulk.tensor.3d.shared::cluster.global.mbarrier::complete_tx::bytes [%0], [%1, {%3, %4, %5}], [%2];" ::"r"(dst), "l"(m), "r"(bar), "r"(c0), "r"(c1), "r"(c2) : "memory");
}
__device__ __forceinline__ void tma3d_mc(uint32_t dst, const CUtensorMap* m, int c0, int c1, int c2, uint32_t bar) {
    asm volatile("cp.async.bulk.tensor.3d.shared::cluster.global.mbarrier::complete_tx::bytes.multicast::cluster [%0], [%1, {%3, %4, %5}], [%2], %6;"
                 ::"r"(dst), "l"(m), "r"(bar), "r"(c0), "r"(c1), "r"(c2), "h"((uint16_t)3) : "memory");
}
__device__ __forceinline__ void tma2d_store(const CUtensorMap* m, uint32_t src, int c0, int c1) {
    asm volatile("cp.async.bulk.tensor.2d.global.shared::cta.bulk_group [%0, {%2, %3}], [%1];" ::"l"(m), "r"(src), "r"(c0), "r"(c1) : "memory");
}
__device__ __forceinline__ void tma4d_store(const CUtensorMap* m, uint32_t src, int c0, int c1, int c2, int c3) {
    asm volatile("cp.async.bulk.tensor.4d.global.shared::cta.bulk_group [%0, {%2, %3, %4, %5}], [%1];" ::"l"(m), "r"(src), "r"(c0), "r"(c1), "r"(c2), "r"(c3) : "memory");
}
__device__ __forceinline__ void tma4d(uint32_t dst, const CUtensorMap* m, int c0, int c1, int c2, int c3, uint32_t bar) {
    asm volatile("cp.async.bulk.tensor.4d.shared::cluster.global.mbarrier::complete_tx::bytes [%0], [%1, {%3, %4, %5, %6}], [%2];" ::"r"(dst), "l"(m), "r"(bar), "r"(c0), "r"(c1), "r"(c2), "r"(c3) : "memory");
}
__device__ __forceinline__ void bulk_load(uint32_t dst, const void* src, uint32_t bytes, uint32_t bar) {
    asm volatile("cp.async.bulk.shared::cluster.global.mbarrier::complete_tx::bytes [%0], [%1], %2, [%3];" ::"r"(dst), "l"(src), "r"(bytes), "r"(bar) : "memory");
}
__device__ __forceinline__ void bulk_store(void* dst, uint32_t src, uint32_t bytes) {
    asm volatile("cp.async.bulk.global.shared::cta.bulk_group [%0], [%1], %2;" ::"l"(dst), "r"(src), "r"(bytes) : "memory");
}
__device__ __forceinline__ void bulk_commit() { asm volatile("cp.async.bulk.commit_group;" ::: "memory"); }
__device__ __forceinline__ void bulk_wait_all() { asm volatile("cp.async.bulk.wait_group 0;" ::: "memory"); }
__device__ __forceinline__ void bulk_wait_read() { asm volatile("cp.async.bulk.wait_group.read 0;" ::: "memory"); }
__device__ __forceinline__ void l2_prefetch(const void* p) { asm volatile("prefetch.global.L2 [%0];" ::"l"(p)); }
__device__ __forceinline__ void fence_async_smem() { asm volatile("fence.proxy.async.shared::cta;" ::: "memory"); }
__device__ __forceinline__ void fence_async_global() { asm volatile("fence.proxy.async.global;" ::: "memory"); }
__device__ __forceinline__ void red_relaxed(unsigned* p, unsigned v) { asm volatile("red.relaxed.gpu.global.add.u32 [%0], %1;" ::"l"(p), "r"(v) : "memory"); }
__device__ __forceinline__ void publish(unsigned* p) {
    asm volatile("fence.proxy.async.global;\nred.release.gpu.global.add.u32 [%0], 1;" ::"l"(p) : "memory");
}
__device__ __forceinline__ void stg32(void* p, uint32_t v) { asm volatile("st.global.b32 [%0], %1;" ::"l"(p), "r"(v) : "memory"); }
__device__ __forceinline__ unsigned ld_relaxed(const unsigned* p) { unsigned v; asm volatile("ld.relaxed.gpu.global.u32 %0, [%1];" : "=r"(v) : "l"(p) : "memory"); return v; }
__device__ __forceinline__ bool ctr_done(unsigned v, unsigned target) { return ((v - target) & 0x1FFFFFFu) == 0; }
__device__ __forceinline__ uint32_t clock32() { uint32_t c; asm volatile("mov.u32 %0, %%clock;" : "=r"(c)::"memory"); return c; }
__device__ __forceinline__ void delay(uint32_t n) { const uint32_t t0 = clock32(); while (clock32() - t0 < n) {} }
__device__ __forceinline__ void poll(const unsigned* p, unsigned target) { while (!ctr_done(ld_relaxed(p), target)) {} }
__device__ __forceinline__ void cell_put(void* p, uint32_t a, uint32_t b, uint32_t tag) {
    asm volatile("st.relaxed.gpu.global.v4.b32 [%0], {%1, %3, %2, %3};" ::"l"(p), "r"(a), "r"(b), "r"(tag) : "memory");
}
__device__ __forceinline__ uint32_t cell_get(const void* p, uint32_t& a, uint32_t& b, uint32_t tag) {
    uint32_t t0, t1;
    asm volatile("ld.relaxed.gpu.global.v4.b32 {%0, %1, %2, %3}, [%4];" : "=r"(a), "=r"(t0), "=r"(b), "=r"(t1) : "l"(p) : "memory");
    return (t0 ^ tag) | (t1 ^ tag);
}
template <int ID, int N> __device__ __forceinline__ void bar_sync() { asm volatile("bar.sync %0, %1;" ::"n"(ID), "n"(N) : "memory"); }
template <int ID = 4> __device__ __forceinline__ void gate_wait(uint32_t on) { asm volatile("{\n.reg .pred p;\nsetp.ne.u32 p, %0, 0;\n@p bar.sync %1, 256;\n}" ::"r"(on), "n"(ID) : "memory"); }
template <int ID = 4> __device__ __forceinline__ void gate_open(uint32_t off) { asm volatile("{\n.reg .pred p;\nsetp.eq.u32 p, %0, 0;\n@p bar.arrive %1, 256;\n}" ::"r"(off), "n"(ID) : "memory"); }
__device__ __forceinline__ void wg_fence() { asm volatile("wgmma.fence.sync.aligned;" ::: "memory"); }
__device__ __forceinline__ void wg_commit() { asm volatile("wgmma.commit_group.sync.aligned;" ::: "memory"); }
template <int N> __device__ __forceinline__ void wg_wait() { asm volatile("wgmma.wait_group.sync.aligned %0;" ::"n"(N) : "memory"); }
template <int LO = 0, int HI = 56, int N> __device__ __forceinline__ void pin(float (&a)[N]) {
#pragma unroll
    for (int i = LO; i < (HI < N ? HI : N); i++) asm volatile("" : "+f"(a[i])::"memory");
}
__device__ __forceinline__ uint32_t ldg_u16(const void* p) {
    uint32_t v;
    asm volatile("ld.global.nc.u16 %0, [%1];" : "=r"(v) : "l"(p) : "memory");
    return v;
}
__device__ __forceinline__ uint32_t pack2(float lo, float hi) { uint32_t r; asm("cvt.rn.bf16x2.f32 %0, %1, %2;" : "=r"(r) : "f"(hi), "f"(lo)); return r; }
__device__ __forceinline__ float bf_lo(uint32_t v) { return __uint_as_float(v << 16); }
__device__ __forceinline__ float bf_hi(uint32_t v) { return __uint_as_float(v & 0xFFFF0000u); }
__device__ __forceinline__ uint32_t split2(float x) { return pack2(x, x - bf_lo(pack2(x, 0.f))); }
__device__ __forceinline__ void stsm4(uint32_t a, uint32_t r0, uint32_t r1, uint32_t r2, uint32_t r3) {
    asm volatile("stmatrix.sync.aligned.m8n8.x4.shared.b16 [%0], {%1, %2, %3, %4};" ::"r"(a), "r"(r0), "r"(r1), "r"(r2), "r"(r3) : "memory");
}
__device__ __forceinline__ void stsm2(uint32_t a, uint32_t r0, uint32_t r1) {
    asm volatile("stmatrix.sync.aligned.m8n8.x2.shared.b16 [%0], {%1, %2};" ::"r"(a), "r"(r0), "r"(r1) : "memory");
}
__device__ __forceinline__ void ldsm4(uint32_t a, uint32_t (&r)[4]) {
    asm volatile("ldmatrix.sync.aligned.m8n8.x4.shared.b16 {%0, %1, %2, %3}, [%4];" : "=r"(r[0]), "=r"(r[1]), "=r"(r[2]), "=r"(r[3]) : "r"(a) : "memory");
}
__device__ __forceinline__ void ldsm4t(uint32_t a, uint32_t (&r)[4]) {
    asm volatile("ldmatrix.sync.aligned.m8n8.x4.trans.shared.b16 {%0, %1, %2, %3}, [%4];" : "=r"(r[0]), "=r"(r[1]), "=r"(r[2]), "=r"(r[3]) : "r"(a) : "memory");
}
__device__ __forceinline__ void mma16816(float (&c)[4], uint32_t a0, uint32_t a1, uint32_t a2, uint32_t a3, uint32_t b0, uint32_t b1) {
    asm volatile("mma.sync.aligned.m16n8k16.row.col.f32.bf16.bf16.f32 {%0,%1,%2,%3}, {%4,%5,%6,%7}, {%8,%9}, {%0,%1,%2,%3};"
                 : "+f"(c[0]), "+f"(c[1]), "+f"(c[2]), "+f"(c[3]) : "r"(a0), "r"(a1), "r"(a2), "r"(a3), "r"(b0), "r"(b1));
}
__device__ __forceinline__ void mma1688(float (&c)[4], uint32_t a0, uint32_t a1, uint32_t b0) {
    asm volatile("mma.sync.aligned.m16n8k8.row.col.f32.bf16.bf16.f32 {%0,%1,%2,%3}, {%4,%5}, {%6}, {%0,%1,%2,%3};"
                 : "+f"(c[0]), "+f"(c[1]), "+f"(c[2]), "+f"(c[3]) : "r"(a0), "r"(a1), "r"(b0));
}
constexpr uint32_t SB0 = 1024;
__device__ __forceinline__ uint32_t desc_lo(uint32_t off, uint32_t lbo) { return ((SB0 + off) >> 4) + ((lbo >> 4) << 16); }
constexpr uint32_t H_SW = (1024 >> 4) | (1u << 30), H_H = 128 >> 4, H_U = 1024 >> 4;
__device__ __forceinline__ float ex2(float x) { float r; asm("ex2.approx.ftz.f32 %0, %1;" : "=f"(r) : "f"(x)); return r; }
__device__ __forceinline__ float rsq(float x) { float r; asm("rsqrt.approx.ftz.f32 %0, %1;" : "=f"(r) : "f"(x)); return r; }
__device__ __forceinline__ float rcp(float x) { float r; asm("rcp.approx.ftz.f32 %0, %1;" : "=f"(r) : "f"(x)); return r; }
__device__ __forceinline__ float gelu_half(float h) {
    float y = h * fmaf(h * h, 8.f * 0.0356774081363f, 2.f * 0.7978845608029f), t;
    asm("tanh.approx.f32 %0, %1;" : "=f"(t) : "f"(y));
    return fmaf(h, t, h);
}

template <uint32_t HB, int TB>
__device__ __forceinline__ void wgmma_n56_rs(float (&d)[28], const uint32_t (&a)[4], uint32_t lb, int scale_d) {
    asm volatile("{\n.reg .pred p;\n.reg .b64 db;\nsetp.ne.b32 p, %33, 0;\nmov.b64 db, {%32, %34};\n"
        "wgmma.mma_async.sync.aligned.m64n56k16.f32.bf16.bf16 "
        "{%0, %1, %2, %3, %4, %5, %6, %7, %8, %9, %10, %11, %12, %13, %14, %15, %16, %17, %18, %19, %20, %21, %22, %23, %24, %25, %26, %27}, "
        "{%28, %29, %30, %31}, db, p, 1, 1, %35;\n}\n"
        : "+f"(d[0]), "+f"(d[1]), "+f"(d[2]), "+f"(d[3]), "+f"(d[4]), "+f"(d[5]), "+f"(d[6]), "+f"(d[7]), "+f"(d[8]), "+f"(d[9]), "+f"(d[10]), "+f"(d[11]), "+f"(d[12]), "+f"(d[13]), "+f"(d[14]), "+f"(d[15]), "+f"(d[16]), "+f"(d[17]), "+f"(d[18]), "+f"(d[19]), "+f"(d[20]), "+f"(d[21]), "+f"(d[22]), "+f"(d[23]), "+f"(d[24]), "+f"(d[25]), "+f"(d[26]), "+f"(d[27])
        : "r"(a[0]), "r"(a[1]), "r"(a[2]), "r"(a[3]), "r"(lb), "r"(scale_d), "n"(HB), "n"(TB));
}
template <int TA, uint32_t HA, uint32_t HB>
__device__ __forceinline__ void wgmma_n112(float (&d)[56], uint32_t la, uint32_t lb, int scale_d = 1) {
    asm volatile("{\n.reg .b64 da, db;\n.reg .pred p;\nsetp.ne.b32 p, %61, 0;\nmov.b64 da, {%56, %59};\nmov.b64 db, {%57, %60};\n"
        "wgmma.mma_async.sync.aligned.m64n112k16.f32.bf16.bf16 "
        "{%0, %1, %2, %3, %4, %5, %6, %7, %8, %9, %10, %11, %12, %13, %14, %15, %16, %17, %18, %19, %20, %21, %22, %23, %24, %25, %26, %27, %28, %29, %30, %31, %32, %33, %34, %35, %36, %37, %38, %39, %40, %41, %42, %43, %44, %45, %46, %47, %48, %49, %50, %51, %52, %53, %54, %55}, "
        "da, db, p, 1, 1, %58, 1;\n}\n"
        : "+f"(d[0]), "+f"(d[1]), "+f"(d[2]), "+f"(d[3]), "+f"(d[4]), "+f"(d[5]), "+f"(d[6]), "+f"(d[7]), "+f"(d[8]), "+f"(d[9]), "+f"(d[10]), "+f"(d[11]), "+f"(d[12]), "+f"(d[13]), "+f"(d[14]), "+f"(d[15]), "+f"(d[16]), "+f"(d[17]), "+f"(d[18]), "+f"(d[19]), "+f"(d[20]), "+f"(d[21]), "+f"(d[22]), "+f"(d[23]), "+f"(d[24]), "+f"(d[25]), "+f"(d[26]), "+f"(d[27]), "+f"(d[28]), "+f"(d[29]), "+f"(d[30]), "+f"(d[31]), "+f"(d[32]), "+f"(d[33]), "+f"(d[34]), "+f"(d[35]), "+f"(d[36]), "+f"(d[37]), "+f"(d[38]), "+f"(d[39]), "+f"(d[40]), "+f"(d[41]), "+f"(d[42]), "+f"(d[43]), "+f"(d[44]), "+f"(d[45]), "+f"(d[46]), "+f"(d[47]), "+f"(d[48]), "+f"(d[49]), "+f"(d[50]), "+f"(d[51]), "+f"(d[52]), "+f"(d[53]), "+f"(d[54]), "+f"(d[55])
        : "r"(la), "r"(lb), "n"(TA), "n"(HA), "n"(HB), "r"(scale_d));
}
template <int TA, uint32_t HA, uint32_t HB>
__device__ __forceinline__ void wgmma_n8(float (&d)[4], uint32_t la, uint32_t lb, int scale_d = 1) {
    asm volatile("{\n.reg .b64 da, db;\n.reg .pred p;\nsetp.ne.b32 p, %9, 0;\nmov.b64 da, {%4, %7};\nmov.b64 db, {%5, %8};\n"
        "wgmma.mma_async.sync.aligned.m64n8k16.f32.bf16.bf16 "
        "{%0, %1, %2, %3}, "
        "da, db, p, 1, 1, %6, 1;\n}\n"
        : "+f"(d[0]), "+f"(d[1]), "+f"(d[2]), "+f"(d[3])
        : "r"(la), "r"(lb), "n"(TA), "n"(HA), "n"(HB), "r"(scale_d));
}

__device__ __forceinline__ void send8(const float* a, uint32_t rbuf, uint32_t rbar, uint32_t on) {
    asm volatile("{\n.reg .pred p;\nsetp.ne.u32 p, %6, 0;\n@p st.async.weak.shared::cluster.mbarrier::complete_tx::bytes.v4.b32 [%0], {%1,%2,%3,%4}, [%5];\n}"
                 ::"r"(rbuf), "r"(pack2(a[0], a[1])), "r"(pack2(a[2], a[3])), "r"(pack2(a[4], a[5])), "r"(pack2(a[6], a[7])), "r"(rbar), "r"(on) : "memory");
}
__device__ __forceinline__ void send_half(const float (&a)[56], uint32_t rbuf, uint32_t rbar, int t, uint32_t on) {
#pragma unroll
    for (int i = 0; i < 3; i++) send8(a + 28 + 8 * i, rbuf + i * 2048 + t * 16, rbar, on);
    asm volatile("{\n.reg .pred p;\nsetp.ne.u32 p, %4, 0;\n@p st.async.weak.shared::cluster.mbarrier::complete_tx::bytes.v2.b32 [%0], {%1,%2}, [%3];\n}"
                 ::"r"(rbuf + 6144 + t * 8), "r"(pack2(a[52], a[53])), "r"(pack2(a[54], a[55])), "r"(rbar), "r"(on) : "memory");
}
__device__ __forceinline__ void recv_half(uint32_t (&p)[14], uint32_t buf, int t) {
#pragma unroll
    for (int i = 0; i < 3; i++)
        asm volatile("ld.shared.v4.b32 {%0,%1,%2,%3}, [%4];" : "=r"(p[4 * i]), "=r"(p[4 * i + 1]), "=r"(p[4 * i + 2]), "=r"(p[4 * i + 3]) : "r"(buf + i * 2048 + t * 16) : "memory");
    asm volatile("ld.shared.v2.b32 {%0,%1}, [%2];" : "=r"(p[12]), "=r"(p[13]) : "r"(buf + 6144 + t * 8) : "memory");
}

struct Maps { CUtensorMap xl, x, wqkv, hst, w1, w2, xn, old_, ost, wo; };

__global__ void __cluster_dims__(2, 1, 1) __launch_bounds__(512, 1)
fused_kernel(const __nv_bfloat16* __restrict__ x, const __nv_bfloat16* __restrict__ b1, const __nv_bfloat16* __restrict__ b2, uint8_t* __restrict__ scr,
             uint8_t* __restrict__ out, const __grid_constant__ Maps mp) {
    extern __shared__ __align__(1024) uint8_t smem[];
    const uint32_t sb = smem_u32(smem);
    const uint32_t bar = sb + OFF_BAR;
    const int tid = threadIdx.x, lane = tid & 31;
    const int b = blockIdx.x, z = b & 1, c = b >> 1;
    unsigned* const ctr = reinterpret_cast<unsigned*>(scr + G_CTR);
    if (tid < 112) l2_prefetch(reinterpret_cast<const uint8_t*>(x) + (b * 112 + tid) * 128);
    const uint32_t t_in = clock32();
    TS0(0);
    TG(60);
    const int warp = __shfl_sync(0xffffffffu, tid >> 5, 0);
    const int j = c < 4 ? c : c < 36 ? (c - 4) >> 3 : ((c - 36) * 37) >> 8, q = c < 4 ? 15 : c < 36 ? (c - 4) & 7 : c - 28 - 7 * j;
    const bool g1 = q < 14;
    const int R = q < 8 ? q : (0x27654310u >> (4 * q - 32)) & 7, P = (q >> 3) * 4 + j;
    auto krow = [&](int kb) { const int k = kb + (R & ROT); return (k >= 7 ? k - 7 : k) * 64; };
    auto x_load = [&](int kb) {
        mbar_expect(bar + 8 * (B_FULLQ + kb), 40960);
        tma2d(sb + OFF_A + ((XSLOT >> (4 * kb)) & 7) * 16384, &mp.x, z * D_ + krow(kb), R * 128, bar + 8 * (B_FULLQ + kb));
    };
    auto w_load = [&](int kb) {
        tma3d_mc(sb + OFF_B + ((WSLOT >> (4 * kb)) & 7) * 24576 + z * 12288, &mp.wqkv, (P * 56) & ~15, krow(kb) + z * 32, 0, bar + 8 * (B_FULLQ + kb));
    };
    if (warp == 12 && elect()) {
#pragma unroll
        for (int i = B_FULLQ; i < B_EMPTYQ; i++) mbar_init(bar + 8 * i, 1);
        mbar_expect(bar + 8 * B_LNIN, BLK);
        tma3d(sb + OFF_A, &mp.xl, 0, 16 * b, 0, bar + 8 * B_LNIN);
        x_load(0);
        TS(15);
    }
    auto bar_count = [&](int i) {
        return i < B_FULL ? (i < B_EMPTYQ + 2 ? 16 : 8) + (((i - B_EMPTYQ) & ~1) == (R & 6 & ~ROT) ? 8 : 0) : i < B_EMPTY || i == B_FREE ? 2 : (i < B_AUX || i == B_NONE || i == B_OST) ? 8 : i == B_KV ? 12
               : (i == B_AUX || i == B_HALO) ? 4 : 1;
    };
    if (warp == 13 && elect()) {
#pragma unroll
        for (int i = B_EMPTYQ; i < B_COUNT; i++) mbar_init(bar + 8 * i, bar_count(i));
#pragma unroll
        for (int i = B_RECV1; i < B_EP; i++) mbar_expect(bar + 8 * i, i < B_RECV2 ? 7168 : 8192 - 2048 * z);
    }
    asm volatile("fence.mbarrier_init.release.cluster;" ::: "memory");
    __syncwarp();
    asm volatile("barrier.cluster.arrive.relaxed.aligned;\nbarrier.cluster.wait.aligned;" ::: "memory");
    if (warp == 12 && elect()) { w_load(0); TS(16); }
    auto slot = [](uint32_t r) { return r - 6 * ((r * 43) >> 8); };
    auto phase = [](uint32_t r) { return ((r * 43) >> 8) & 1; };
    const uint32_t r_o = g1 ? 16 : 0, r_u = r_o + 4;
    auto fetch_x = [&](uint32_t i, bool arm = true) {
        const uint32_t s = slot(r_o + i), lb = bar + 8 * (B_LAND + s);
        if (arm) mbar_expect(lb, i < 4 ? 16384 : BLK);
        if (i < 4) tma2d(sb + OFF_A + s * 16384, &mp.old_, 0, (4 * z + i) * S_ + q * 128, lb);
        else bulk_load(sb + OFF_B + s * BLK, scr + G_BIMG + ((14 * z + (i < 11 ? 2 * i : 2 * i - 13)) * 4 + j) * BLK, BLK, lb);
    };
    auto epoch = [&]() { mbar_wait(bar + 8 * B_EP, 0); return *reinterpret_cast<volatile unsigned*>(smem + OFF_EP); };

    if (warp < 8) {
        const int wg = warp >> 2, w4 = warp & 3, t = tid & 127, g = lane >> 2, tq = lane & 3;
        asm volatile("setmaxnreg.inc.sync.aligned.u32 208;");
        uint32_t xa[4];
#pragma unroll
        for (int k = 0; k < 4; k++) xa[k] = sb + OFF_A + (warp * 16 + (lane & 15)) * 128 + (((2 * k + (lane >> 4)) ^ (lane & 7)) << 4);
        {
            const int rg = warp & 1, jq = warp >> 1;
            const uint32_t ex = sb + OFF_LNX + (rg * 8 + g) * 32, ew = ex + jq * 8, ls = sb + OFF_LNST + (rg * 8 + g) * 8;
            const uint32_t l0 = sb + OFF_A + rg * 1024 + g * 144;
            uint32_t r[4][4], la[4], ha[4], x0, dep = ex | ew | ls | l0;
#pragma unroll
            for (int i = 0; i < 4; i++) {
                const int cg = 14 * jq + 4 * i + ((lane >> 3) & (i < 3 ? 3 : 1));
                la[i] = sb + OFF_A + (cg >> 3) * 2048 + rg * 1024 + (lane & 7) * 128 + (((cg ^ lane) & 7) << 4);
                int pos = 4 * i + (lane >> 3) + (b >= 64 ? 7 : 0);
                if (pos >= 14) pos -= 14;
                ha[i] = sb + OFF_A + jq * 3584 + rg * 1792 + (lane & 7) * 16 + pos * 128;
                dep |= la[i] | xa[i] | ha[i];
            }
            mbar_wait(bar + 8 * B_LNIN, dep >> 31);
            asm volatile("ld.shared.b32 %0, [%1];" : "=r"(x0) : "r"(l0) : "memory");
#pragma unroll
            for (int i = 0; i < 4; i++) ldsm4(la[i], r[i]);
            float s1[4], s2[4], v[28];
            const float sh = bf_lo(x0);
#pragma unroll
            for (int n = 0; n < 14; n++) { v[2 * n] = bf_lo(r[n >> 2][n & 3]) - sh; v[2 * n + 1] = bf_hi(r[n >> 2][n & 3]) - sh; }
#pragma unroll
            for (int n = 0; n < 28; n++) {
                s1[n & 3] = n < 4 ? v[n] : s1[n & 3] + v[n];
                s2[n & 3] = n < 4 ? v[n] * v[n] : fmaf(v[n], v[n], s2[n & 3]);
            }
            float m1 = (s1[0] + s1[1]) + (s1[2] + s1[3]), m2 = (s2[0] + s2[1]) + (s2[2] + s2[3]);
#pragma unroll
            for (int o = 1; o <= 2; o <<= 1) { m1 += __shfl_xor_sync(0xffffffffu, m1, o); m2 += __shfl_xor_sync(0xffffffffu, m2, o); }
            asm volatile("st.shared.v2.f32 [%0], {%1, %2};" ::"r"(ew), "f"(m1), "f"(m2) : "memory");
            bar_sync<1, 256>();
            float4 e0, e1;
            asm volatile("ld.shared.v4.f32 {%0,%1,%2,%3}, [%4];" : "=f"(e0.x), "=f"(e0.y), "=f"(e0.z), "=f"(e0.w) : "r"(ex) : "memory");
            asm volatile("ld.shared.v4.f32 {%0,%1,%2,%3}, [%4];" : "=f"(e1.x), "=f"(e1.y), "=f"(e1.z), "=f"(e1.w) : "r"(ex + 16) : "memory");
            const float dm = ((e0.x + e0.z) + (e1.x + e1.z)) * (1.f / D_);
            const float var = fmaxf(fmaf(-dm, dm, ((e0.y + e0.w) + (e1.y + e1.w)) * (1.f / D_)), 0.f);
            const float r1 = rsq(var + 1e-5f), sc = rsq(fmaf(1e-5f, var + 1e-5f, var)), of = -dm * sc;
#pragma unroll
            for (int n = 0; n < 14; n++) r[n >> 2][n & 3] = pack2(fmaf(v[2 * n], sc, of), fmaf(v[2 * n + 1], sc, of));
#pragma unroll
            for (int i = 0; i < 3; i++) stsm4(ha[i], r[i][0], r[i][1], r[i][2], r[i][3]);
            stsm2(ha[3], r[3][0], r[3][1]);
            asm volatile("st.shared.v2.b32 [%0], {%1, %2};" ::"r"(ls), "r"(__float_as_uint(r1)), "r"(split2(-(sh + dm))) : "memory");
            TS0(24);
            asm volatile("bar.arrive 10, 288;" ::: "memory");
        }
        float a1[56];
        float rq[2], hb1[2], fb2[2];
        uint32_t qp[14], kp[14];
        const uint32_t ka = sb + OFF_K + warp * 896 + (lane & 7) * 112 + (lane >> 3) * 16;
        const uint32_t va = sb + OFF_V + (warp * 16 + (lane & 15)) * 112 + (lane >> 4) * 16;
        const uint32_t sta = sb + OFF_RSTD + warp * 64 + tq * 8;
        const uint32_t dA = desc_lo(OFF_A + wg * 8192, 16), dH = desc_lo(OFF_B, 1792), dU = desc_lo(OFF_B, 128);
        auto release = [&](uint32_t a) { mbar_arrive_if0(a, lane); };
        auto sched_fence = [&]() { mbar_wait(bar + 8 * B_LNIN, 0); };
        uint32_t rel = bar + 8 * (B_EMPTYQ + 6);
        auto g1_run = [&](uint32_t r0, uint32_t r1, bool gate = false) {
#pragma unroll 1
            for (uint32_t r = g1 ? r0 : r1; r < r1; r++) {
                const uint32_t s = slot(r), n = min(r + 1, 15u);
                if (gate) gate_wait(wg && r == r0);
                if (TSG1) TSD(64 + r);
                wg_fence();
#pragma unroll
                for (int k = 0; k < 4; k++) wgmma_n112<1, H_SW, H_H>(a1, dA + s * 1024 + k * 128, dH + s * 896 + k * 224, k ? 1 : r);
                wg_commit();
                wg_wait<1>();
                release(rel);
                rel = bar + 8 * (B_EMPTY + s);
                mbar_wait(bar + 8 * (B_FULL + slot(n)), phase(n));
            }
        };
        uint32_t solo = g1 && wg;
        asm volatile("" : "+r"(solo));
        solo = __shfl_sync(0xffffffffu, solo, 0);
        auto g1_wait = [&](uint32_t r) { mbar_wait(bar + 8 * (g1 ? B_FULL + r % 6 : B_LNIN), g1 && ((r / 6) & 1)); };
        auto g1_one = [&](uint32_t r) {
#pragma unroll 1
            for (uint32_t n = 0; n < solo; n++) {
                if (TSG1) TSD(64 + r);
                wg_fence();
#pragma unroll
                for (int k = 0; k < 4; k++) wgmma_n112<1, H_SW, H_H>(a1, dA + r % 6 * 1024 + k * 128, dH + r % 6 * 896 + k * 224);
                wg_commit();
                wg_wait<1>();
                release(rel);
                rel = bar + 8 * (B_EMPTY + r % 6);
            }
        };
        auto drain = [&]() { wg_wait<0>(); release(rel); rel = bar + 8 * B_NONE; };
        {
            float aq0[28], aq1[28], aq2[28];
            const uint32_t dW = desc_lo(OFF_B + (P & 1) * 16, 16);
            uint32_t xf[2][4][4];
            const uint32_t rb = mapa(bar + 8 * (B_EMPTYQ - 1), z ^ 1);
            auto fetch = [&](int kb, uint32_t (&f)[4][4]) {
                if (TSG1) TSD(178 + kb);
                mbar_wait(bar + 8 * (B_FULLQ + kb), 0);
                if (TSG1) TSD(170 + kb);
#pragma unroll
                for (int k = 0; k < 4; k++) ldsm4(xa[k] + ((XSLOT >> (4 * kb)) & 7) * 16384, f[k]);
            };
            auto mma = [&](int kb, uint32_t (&f)[4][4], int k0, int k1) {
                const uint32_t d0 = dW + ((WSLOT >> (4 * kb)) & 7) * 1536;
                wg_fence();
#pragma unroll
                for (int k = k0; k < k1; k++) {
                    const uint32_t d = d0 + (k >> 1) * 768 + (k & 1) * 128;
                    const int sc = k > 0 ? 1 : kb;
                    wgmma_n56_rs<H_SW, 1>(aq0, f[k], d, sc);
                    wgmma_n56_rs<H_SW, 1>(aq1, f[k], d + 256, sc);
                    wgmma_n56_rs<H_SW, 1>(aq2, f[k], d + 512, sc);
                }
            };
            auto retire = [&](int kb) {
                wg_commit();
                wg_wait<1>();
                mbar_arrive_if0(bar + 8 * (B_EMPTYQ + kb - 1), lane | (kb < 1));
                asm volatile("{\n.reg .pred p;\nsetp.eq.u32 p, %1, 0;\n@p mbarrier.arrive.shared::cluster.b64 _, [%0];\n}"
                             ::"r"(rb + 8 * kb), "r"(lane | ((uint32_t)(kb - 1) > 1)) : "memory");
            };
            auto stage = [&](int kb, uint32_t (&f)[4][4], uint32_t (&n)[4][4]) {
                mma(kb, f, 0, KS);
                retire(kb);
                fetch(kb + 1, n);
                if (KS < 4) { mma(kb, f, KS, 4); wg_commit(); }
            };
            fetch(0, xf[0]);
#pragma unroll 1
            for (int kb = 0; kb < 6; kb += 2) {
                stage(kb, xf[0], xf[1]);
                stage(kb + 1, xf[1], xf[0]);
            }
            mma(6, xf[0], 0, KS);
            retire(6);
            TS0(2);
            mbar_wait(bar + 8 * B_AUX, 0);
            {
                uint32_t (&f)[4] = xf[1][0];
                const uint2* mt = reinterpret_cast<const uint2*>(smem + OFF_STATS) + warp * 16 + g;
                const uint2 m0 = mt[0], m1 = mt[8];
                const uint32_t sel = tq == 0 ? 0x1010 : tq == 1 ? 0x3232 : 0x4444;
                f[0] = __byte_perm(m0.y, 0, sel); f[1] = __byte_perm(m1.y, 0, sel); f[2] = f[3] = 0;
                rq[0] = __uint_as_float(m0.x); rq[1] = __uint_as_float(m1.x);
                asm volatile("" : "+r"(f[0]), "+r"(f[1]), "+r"(f[2]), "+r"(f[3])::"memory");
                const uint32_t d = desc_lo(OFF_CSB + (P & 1) * 128, 0);
                mma(6, xf[0], KS, 4);
                wgmma_n56_rs<H_H, 0>(aq1, f, d + 64, 1);
                wgmma_n56_rs<H_H, 0>(aq2, f, d + 128, 1);
                wgmma_n56_rs<H_H, 0>(aq0, f, d, 1);
                wg_commit();
            }
            g1_wait(0);
            g1_run(0, wg ? 0 : NE);
            drain();
            pin(aq0); pin(aq1); pin(aq2);
            TSW(3);
            mbar_wait(bar + 8 * (B_EMPTYQ + 5), 0);
#pragma unroll
            for (int i = 0; i < 14; i++) { kp[i] = pack2(aq1[2 * i], aq1[2 * i + 1]); qp[i] = pack2(aq2[2 * i], aq2[2 * i + 1]); }
            stsm4(ka + 896, kp[1], kp[3], kp[5], kp[7]);
            stsm4(ka + 896 + 48, kp[7], kp[9], kp[11], kp[13]);
#pragma unroll
            for (int n = 0; n < 3; n++) stsm4(va + 896 + n * 32, qp[4 * n], qp[4 * n + 1], qp[4 * n + 2], qp[4 * n + 3]);
            stsm2(va + 896 + 96, qp[12], qp[13]);
            __syncwarp();
            mbar_arrive_if0(bar + 8 * B_QKV, tid - 224);
            release(bar + 8 * B_KV);
#pragma unroll
            for (int i = 0; i < 14; i++) qp[i] = pack2(aq0[2 * i], aq0[2 * i + 1]);
            TSW(4);
        }
        g1_run(wg ? 0 : NE, wg ? PRE1 : PRE0);
        {
            uint32_t kf[2][3][4], vf[2][3][4];
            const bool up0 = 2 * tq > g, up1 = 2 * tq + 1 > g, edge = (R | warp) == 0;
            float rk[2][2], fs[2][2], rs[3][2];
            mbar_wait(bar + 8 * (warp ? B_KV : B_HALO), 0);
            const uint32_t tag = *reinterpret_cast<volatile unsigned*>(smem + OFF_EP);
#pragma unroll
            for (int i = 0; i < 2; i++)
                asm volatile("ld.shared.v2.f32 {%0,%1}, [%2];" : "=f"(hb1[i]), "=f"(fb2[i]) : "r"(sb + OFF_BIAS + (warp * 16 + g + 8 * i) * 8) : "memory");
#pragma unroll
            for (int i = 0; i < 3; i++)
                asm volatile("ld.shared.v2.f32 {%0,%1}, [%2];" : "=f"(rs[i][0]), "=f"(rs[i][1]) : "r"(sta + i * 32) : "memory");
#pragma unroll
            for (int hd = 0; hd < 2; hd++) {
                ldsm4(ka + hd * 48, kf[hd][0]);
#pragma unroll
                for (int i = 0; i < 4; i++) { kf[hd][1][i] = kp[6 * hd + 2 * i]; kf[hd][2][i] = kp[6 * hd + 2 * i + 1]; }
                ldsm4t(va + hd * 48, vf[hd][0]); ldsm4t(va + hd * 48 + 32, vf[hd][1]);
                ldsm4t(ka + (OFF_V - OFF_K) + warp * 896 + hd * 48 + 1792, vf[hd][2]);
            }
            const uint32_t q0l = tq < 2 ? qp[6] : 0, q0h = tq < 2 ? qp[7] : 0, q1l = tq < 2 ? 0 : qp[6], q1h = tq < 2 ? 0 : qp[7];
            const uint32_t mk = (up0 ? 0xFFFFu : 0u) | (up1 ? 0xFFFF0000u : 0u);
            g1_run(wg ? PRE1 : PRE0, ATT_STEP);
#pragma unroll
            for (int i = 0; i < 4; i++) {
                rk[i >> 1][i & 1] = ((i & 1) ? up1 : up0) ? rs[i >> 1][i & 1] : rs[(i >> 1) + 1][i & 1];
                fs[i >> 1][i & 1] = rk[i >> 1][i & 1] * (rq[i >> 1] * (0.18898223650461362f * 1.4426950408889634f));
                asm volatile("" : "+f"(fs[i >> 1][i & 1])::"memory");
            }
            drain();
            sched_fence();
            TS0(19);
            float sc[2][3][4];
#pragma unroll
            for (int u = 0; u < 3; u++) {
#pragma unroll
                for (int i = 0; i < 8; i++) sc[i >> 2][u][i & 3] = 0.f;
                mma16816(sc[0][u], qp[0], qp[1], qp[2], qp[3], kf[0][u][0], kf[0][u][1]);
                mma16816(sc[1][u], q1l, q1h, qp[8], qp[9], kf[1][u][0], kf[1][u][1]);
            }
#pragma unroll
            for (int u = 0; u < 3; u++) {
                mma16816(sc[0][u], qp[4], qp[5], q0l, q0h, kf[0][u][2], kf[0][u][3]);
                mma16816(sc[1][u], qp[10], qp[11], qp[12], qp[13], kf[1][u][2], kf[1][u][3]);
            }
            float e[2][2][2], mx[2][2], sm[2][4];
#pragma unroll
            for (int hd = 0; hd < 2; hd++) {
                e[hd][0][0] = (up0 ? sc[hd][0][0] : sc[hd][1][0]) * fs[0][0];
                e[hd][0][1] = (up1 ? sc[hd][0][1] : sc[hd][1][1]) * fs[0][1];
                e[hd][1][0] = (up0 ? sc[hd][1][2] : sc[hd][2][2]) * fs[1][0];
                e[hd][1][1] = (up1 ? sc[hd][1][3] : sc[hd][2][3]) * fs[1][1];
                if (edge && up0) e[hd][0][0] = -1e30f;
                if (edge && up1) e[hd][0][1] = -1e30f;
                mx[hd][0] = fmaxf(e[hd][0][0], e[hd][0][1]);
                mx[hd][1] = fmaxf(e[hd][1][0], e[hd][1][1]);
            }
#pragma unroll
            for (int o = 1; o <= 2; o <<= 1)
#pragma unroll
                for (int i = 0; i < 4; i++) mx[i >> 1][i & 1] = fmaxf(mx[i >> 1][i & 1], __shfl_xor_sync(0xffffffffu, mx[i >> 1][i & 1], o));
            uint32_t pp[2][2], pu[2][2];
#pragma unroll
            for (int i = 0; i < 4; i++) {
                const float p0 = ex2(e[i >> 1][i & 1][0] - mx[i >> 1][i & 1]), p1 = ex2(e[i >> 1][i & 1][1] - mx[i >> 1][i & 1]);
                pp[i >> 1][i & 1] = pack2(p0 * rk[i & 1][0], p1 * rk[i & 1][1]);
                pu[i >> 1][i & 1] = pack2(p0, p1);
            }
            float ov[2][4][4];
#pragma unroll
            for (int hd = 0; hd < 2; hd++)
#pragma unroll
                for (int n = 0; n < 4; n++) {
                    ov[hd][n][0] = ov[hd][n][1] = ov[hd][n][2] = ov[hd][n][3] = 0.f;
                    mma16816(ov[hd][n], pp[hd][0] & mk, 0u, pp[hd][0] & ~mk, pp[hd][1] & mk, vf[hd][n >> 1][2 * (n & 1)], vf[hd][n >> 1][2 * (n & 1) + 1]);
                }
#pragma unroll
            for (int hd = 0; hd < 2; hd++) {
                sm[hd][0] = sm[hd][1] = sm[hd][2] = sm[hd][3] = 0.f;
                mma1688(sm[hd], pu[hd][0], pu[hd][1], 0x3F803F80u);
            }
#pragma unroll
            for (int hd = 0; hd < 2; hd++)
#pragma unroll
                for (int n = 0; n < 4; n++) mma1688(ov[hd][n], 0u, pp[hd][1] & ~mk, vf[hd][2][n]);
            sched_fence();
            TS0(18);
            bar_sync<1, 256>();
            g1_one(ATT_STEP);
#pragma unroll
            for (int i = 0; i < 4; i++) asm volatile("" : "+f"(sm[i >> 1][2 * (i & 1)])::"memory");
            uint32_t op[16];
            op[14] = op[15] = tag & 0x3FFF;
#pragma unroll
            for (int i = 0; i < 4; i++) sm[i >> 1][i & 1] = rcp(sm[i >> 1][2 * (i & 1)]);
#pragma unroll
            for (int n = 0; n < 7; n++) {
                const bool hb = n > 3 || (n == 3 && tq >= 2);
#pragma unroll
                for (int h = 0; h < 2; h++) {
                    const float r = hb ? sm[1][h] : sm[0][h];
                    const float x0 = hb ? ov[1][n >= 3 ? n - 3 : 0][2 * h] : ov[0][n <= 3 ? n : 0][2 * h];
                    const float x1 = hb ? ov[1][n >= 3 ? n - 3 : 0][2 * h + 1] : ov[0][n <= 3 ? n : 0][2 * h + 1];
                    op[2 * n + h] = pack2(x0 * r, x1 * r);
                }
            }
#pragma unroll
            for (int i = 0; i < 14; i++) asm volatile("" : "+r"(op[i])::"memory");
            g1_wait(ATT_STEP + 1);
            if (NQ) { g1_one(ATT_STEP + 1); g1_wait(ATT_STEP + 2); }
#pragma unroll
            for (int n = 0; n < 4; n++) stsm4(xa[n] + OFF_OST, op[4 * n], op[4 * n + 1], op[4 * n + 2], op[4 * n + 3]);
            __syncwarp();
            release(bar + 8 * B_OST);
            g1_one(ATT_STEP + 1 + NQ);
            g1_wait(ATT_STEP + 2 + NQ);
            TSW(5);
        }
        const uint32_t peer = z ^ 1;
        drain();
        g1_run(wg ? ATT_STEP + 2 + NQ : ATT_STEP, 16, true);
        gate_open(wg | !g1);
        mbar_wait(bar + 8 * B_FREE, 0);
        drain();
        pin(a1);
        TSW(6);
        send_half(a1, mapa(sb + OFF_RECV1 + wg * 7168, peer), mapa(bar + 8 * (B_RECV1 + wg), peer), t, g1);
#pragma unroll
        for (int i = 0; i < 28; i++) a1[i] = fmaf(a1[i], 0.5f, hb1[(i >> 1) & 1]);
        pin<0, 28>(a1);
        if (g1) {
            uint32_t p[14];
            const int ub = 2 * q + wg, zz = ub >= 14 ? 1 : 0;
            uint8_t* u0 = scr + G_BIMG + ((8 + ub) * 4 + j) * BLK + (7 * z + 6 * zz) * 1024 + w4 * 256 + lane * 4;
            uint8_t* u1 = u0 - (z & zz ? BLK : 0);
            mbar_wait(bar + 8 * (B_RECV1 + wg), (uint32_t)(((uint64_t)u0 | (uint64_t)u1) >> 63));
            TSW(8);
            recv_half(p, sb + OFF_RECV1 + wg * 7168, t);
#pragma unroll
            for (int i = 0; i < 14; i++) {
                stg32((i < 2 ? u0 : u1) + (i >> 1) * 1024 + (i & 1) * 128,
                      pack2(gelu_half(fmaf(bf_lo(p[i]), 0.5f, a1[2 * i])), gelu_half(fmaf(bf_hi(p[i]), 0.5f, a1[2 * i + 1]))));
            }
            TSW(9);
        }
        float a2[56];
#pragma unroll 1
        for (uint32_t i = 0; i < 4; i++) {
            const uint32_t s = slot(r_o + i);
            mbar_wait(bar + 8 * (B_FULL + s), phase(r_o + i));
            TSD(64 + 17 + i);
            wg_fence();
#pragma unroll
            for (int k = 0; k < 4; k++) wgmma_n112<0, H_SW, H_U>(a2, dA + s * 1024 + k * 2, dU + s * 896 + k * 16, k ? 1 : i);
            wg_commit();
            wg_wait<1>();
            release(rel);
            rel = bar + 8 * (B_EMPTY + s);
        }
        drain();
        TSW(10);
#pragma unroll 1
        for (uint32_t r = r_u; r < r_u + 14; r++) {
            const uint32_t s = slot(r);
            gate_wait(wg && r == r_u + 14 - NS2);
            mbar_wait(bar + 8 * (B_FULL + s), phase(r));
            TSD(85 + r - r_u);
            wg_fence();
#pragma unroll
            for (int k = 0; k < 4; k++) wgmma_n112<1, H_SW, H_U>(a2, dA + s * 1024 + k * 128, dU + s * 896 + k * 16);
            wg_commit();
            wg_wait<1>();
            release(rel);
            rel = bar + 8 * (B_EMPTY + s);
        }
        gate_open(wg);
        mbar_wait(bar + 8 * B_UDONE, 0);
        wg_wait<0>();
        pin(a2);
        TSW(11);
        {
            const uint32_t rbuf = mapa(sb + OFF_RECV2 + wg * 8192 + t * 16, peer) - (z ? 0 : 2048), rbar = mapa(bar + 8 * (B_RECV2 + wg), peer);
#pragma unroll
            for (int i = 3; i >= 0; i--) send8(a2 + 24 + 8 * i, rbuf + i * 2048, rbar, i | z);
            uint32_t xr[4][4];
            mbar_wait(bar + 8 * B_XR, 0);
#pragma unroll
            for (int k = 0; k < 4; k++) ldsm4(xa[k] + slot(r_u + 14) * 16384, xr[k]);
#pragma unroll
            for (int i = 0; i < 32; i++) a2[i] += ((i & 1) ? bf_hi(xr[i >> 3][(i >> 1) & 3]) : bf_lo(xr[i >> 3][(i >> 1) & 3])) + fb2[(i >> 1) & 1];
            pin<0, 32>(a2);
            const uint32_t oa = sb + OFF_OUT + (warp * 16 + (lane >> 3)) * 128 + (((lane ^ (lane >> 3)) & 7) << 4);
            const uint32_t oo = (q * 128 + warp * 16 + (lane >> 3)) * 896 + j * 224 + z * 128 + (lane & 7) * 16;
            uint8_t* og = out + oo;
            mbar_wait(bar + 8 * (B_RECV2 + wg), (oa | oo | (uint32_t)((uint64_t)og >> 32)) >> 31);
            TSW(12);
            uint32_t u[16];
#pragma unroll
            for (int i = 0; i < 4; i++)
                asm volatile("ld.shared.v4.b32 {%0,%1,%2,%3}, [%4];" : "=r"(u[4 * i]), "=r"(u[4 * i + 1]), "=r"(u[4 * i + 2]), "=r"(u[4 * i + 3]) : "r"(sb + OFF_RECV2 + wg * 8192 + i * 2048 + t * 16) : "memory");
#pragma unroll
            for (int e = 0; e < 16; e++) u[e] = pack2(a2[2 * e] + bf_lo(u[e]), a2[2 * e + 1] + bf_hi(u[e]));
#pragma unroll
            for (int i = 0; i < 4; i++) stsm4(xa[i] + OFF_OUT, u[4 * i], u[4 * i + 1], u[4 * i + 2], u[4 * i + 3]);
            __syncwarp();
#pragma unroll
            for (int i = 0; i < 4; i++)
                asm volatile("ld.shared.v4.b32 {%0,%1,%2,%3}, [%4];" : "=r"(u[4 * i]), "=r"(u[4 * i + 1]), "=r"(u[4 * i + 2]), "=r"(u[4 * i + 3]) : "r"((oa ^ ((i & 1) << 6)) + i * 512) : "memory");
            if ((lane & 7) < 8 - 2 * z) {
#pragma unroll
                for (int i = 0; i < 4; i++)
                    asm volatile("st.global.v4.b32 [%0], {%1,%2,%3,%4};" ::"l"(og + i * 3584), "r"(u[4 * i]), "r"(u[4 * i + 1]), "r"(u[4 * i + 2]), "r"(u[4 * i + 3]) : "memory");
            }
        }
        TSW(13);
    } else if (warp < 12) {
        asm volatile("setmaxnreg.dec.sync.aligned.u32 64;");
        const int hw = warp - 8, t = tid & 127;
        reinterpret_cast<uint32_t*>(smem + OFF_ONES)[t] = t < 64 ? 0x3F803F80u : 0;
        fence_async_smem();
        bar_sync<12, 128>();
        while (clock32() - t_in < DLY1) {}
        uint8_t* cscell = scr + G_CS + ((P * 8 + R) * 2 + z) * 512 + (t >> 2) * 16;
        if ((lane & 3) == 0) cell_put(cscell, 0, 0, 0);
        uint8_t* cells = scr + G_HALO + ((R * 8 + P) * 2 + z) * 3584 + min(t, 111) * 16;
        cell_put(cells, 0, 0, 0);
        cell_put(cells + 1792, 0, 0, 0);
        const unsigned e1 = epoch();
        const uint32_t bv1 = ldg_u16(b1 + (g1 ? q * 128 : 0) + t), bv2 = ldg_u16(b2 + q * 128 + t);
        {
            const uint32_t da = desc_lo(OFF_B + min((R & 1) * 2 + z, 2) * 4096, 16), db = desc_lo(OFF_ONES, 128);
            float c0[4];
            const int st = R & 6 & ~ROT;
            mbar_wait(bar + 8 * (B_FULLQ + st), 0);
            mbar_wait(bar + 8 * (B_FULLQ + st + 1), 0);
            TSH(47);
            wg_fence();
#pragma unroll
            for (int k = 0; k < 8; k++)
                wgmma_n8<1, H_SW, H_H>(c0, da + ((WSLOT >> (4 * st + (k & 4))) & 7) * 1536 + (k & 2) * 384 + (k & 1) * 128, db + (k >= 4 && R >= 6 ? 16 : 0), k);
            wg_commit();
            wg_wait<0>();
            pin(c0);
            if ((lane & 3) == 0) cell_put(cscell, __float_as_uint(c0[0]), __float_as_uint(c0[2]), e1);
            if (lane < 4) asm volatile("mbarrier.arrive.shared::cluster.b64 _, [%0];" ::"r"(mapa(bar + 8 * (B_EMPTYQ + st + (lane >> 1)), lane & 1)) : "memory");
            TSH(43);
        }
        mbar_wait(bar + 8 * (B_FULLQ + GATHER), 0);
        TSH(39);
        {
            const bool cw = hw < 3;
            const uint8_t* src = cw ? scr + G_CS + P * 8192 + t * 16 : scr + G_STATS + (z * 1024 + R * 128 + lane) * 16;
            uint32_t a[5], d[5], bad;
            do {
                bad = 0;
#pragma unroll
                for (int i = 0; i < 4; i++) bad |= cell_get(src + i * (cw ? 2048 : 512), a[i], d[i], e1);
                if (t >= 120) bad |= cell_get(src - (R ? 512 : 0), a[4], d[4], e1);
            } while (bad);
            TSH(45);
            if (cw) {
                uint4* cb = reinterpret_cast<uint4*>(smem + OFF_CSB) + (t >> 3) * 16 + (t & 7);
                const uint32_t lo = split2((__uint_as_float(a[0]) + __uint_as_float(a[1])) + (__uint_as_float(a[2]) + __uint_as_float(a[3])));
                const uint32_t hi = split2((__uint_as_float(d[0]) + __uint_as_float(d[1])) + (__uint_as_float(d[2]) + __uint_as_float(d[3])));
                cb[0] = make_uint4(lo, lo, 0, 0);
                cb[8] = make_uint4(hi, hi, 0, 0);
            } else {
                uint2* st = reinterpret_cast<uint2*>(smem + OFF_STATS) + lane;
                uint32_t* rd = reinterpret_cast<uint32_t*>(smem + OFF_RSTD) + lane;
#pragma unroll
                for (int i = 0; i < 4; i++) { st[32 * i] = make_uint2(a[i], d[i]); rd[8 + 32 * i] = a[i]; }
                if (t >= 120) rd[-24] = a[4];
            }
            fence_async_smem();
            __syncwarp();
            mbar_arrive_if0(bar + 8 * B_AUX, lane);
            TSH(41);
            reinterpret_cast<float2*>(smem + OFF_BIAS)[t] = make_float2(0.5f * bf_lo(bv1), bf_lo(bv2));
            __syncwarp();
            mbar_arrive_if0(bar + 8 * B_KV, lane);
        }
        {
            uint2* kv = reinterpret_cast<uint2*>(smem + OFF_K) + min(t, 111);
            mbar_wait(bar + 8 * B_QKV, 0);
            uint2 k2 = kv[896], v2 = kv[1792 + (OFF_V - OFF_K) / 8];
            cell_put(cells, k2.x, k2.y, e1);
            cell_put(cells + 1792, v2.x, v2.y, e1);
            k2 = v2 = make_uint2(0, 0);
            if (DH) delay(DH);
            if (R > 0) while (cell_get(cells - 16 * 3584, k2.x, k2.y, e1) | cell_get(cells - 16 * 3584 + 1792, v2.x, v2.y, e1)) {}
            kv[0] = k2;
            kv[(OFF_V - OFF_K) / 8] = v2;
            mbar_wait(bar + 8 * B_KV, 0);
            __syncwarp();
            mbar_arrive_if0(bar + 8 * B_HALO, lane);
            TSH(40);
        }
        if (hw == 3) {
            mbar_wait(bar + 8 * B_OST, 0);
            if (elect()) {
                unsigned* oc = ctr + C_O + (R * 2 + (P >> 2)) * 32;
                asm volatile("mbarrier.arrive.relaxed.cluster.shared::cluster.b64 _, [%0];" ::"r"(mapa(bar + 8 * B_FREE, z ^ 1)) : "memory");
                fence_async_smem();
                tma2d_store(&mp.ost, sb + OFF_OST, z * 64, P * 1024 + R * 128);
                bulk_commit();
                delay(DO);
                red_relaxed(oc, 1);
                TS(21);
                bulk_wait_read();
                TS(20);
                asm volatile("mbarrier.arrive.relaxed.cluster.shared::cluster.b64 _, [%0];" ::"r"(mapa(bar + 8 * B_UDONE, z ^ 1)) : "memory");
            }
        } else {
            const uint32_t tag = e1 & 0x3FFF;
            const uint32_t ca = sb + OFF_A + lane * 128 + ((~lane & 7) << 4) + (lane >> 3) * 4, cb = sb + OFF_B + lane * 132;
            uint32_t par = 0x3F;
#pragma unroll 1
            for (uint32_t i = hw; i < 18;) {
                const uint32_t s = slot(r_o + i);
                const bool isa = i < 4;
                const uint32_t a0 = isa ? ca + s * 16384 : cb + s * BLK, a3 = a0 - (isa ? 0 : (lane & 16) * 132);
                mbar_wait(bar + 8 * (B_LAND + s), (par >> s) & 1);
                par ^= 1 << s;
                bool ok = true;
#pragma unroll
                for (int k = 0; k < 4; k++) {
                    uint32_t v;
                    asm volatile("ld.shared.b32 %0, [%1];" : "=r"(v) : "r"((k < 3 ? a0 : a3) + k * 4096) : "memory");
                    ok &= (v == (isa ? tag : ~0u)) == isa;
                }
                if (__all_sync(0xffffffffu, ok)) {
                    mbar_arrive_if0(bar + 8 * (B_FULL + s), lane);
                    if (i == 0 || i == 4) TS(i ? 30 : 29);
                    i += 3;
                } else if (elect()) {
                    TS(31);
                    fetch_x(i);
                }
            }
        }
    } else {
        asm volatile("setmaxnreg.dec.sync.aligned.u32 32;");
        auto wait_free = [&](uint32_t r, uint32_t first) {
            const uint32_t a = r < 6 ? B_EMPTYQ + ((first >> (4 * r)) & 7) : B_EMPTY + slot(r);
            mbar_wait(bar + 8 * a, r < 6 ? 0 : phase(r) ^ 1);
        };
        if (warp == 12) {
            TS(14);
            if (elect()) {
#pragma unroll 1
                for (int kb = 1; kb < 7; kb++) {
                    if (kb == 1) while (clock32() - t_in < DLY2) {}
                    if (kb >= QDEPTH) { mbar_wait(bar + 8 * (B_FULLQ + kb - QDEPTH), 0); TS(25 + kb - QDEPTH); }
                    if (kb >= 5) mbar_wait(bar + 8 * (B_EMPTYQ + kb - 5), 0);
                    x_load(kb);
                    w_load(kb);
                }
                TS(17);
                ld_relaxed(ctr + C_O + ((q & ~1) + z) * 32);
                mbar_wait(bar + 8 * B_LNFREE, 0);
                if (!g1) {
                    const int ic = (q - 14) * 8 + j * 2 + z, rot = ic >> 3;
                    mbar_wait(bar + 8 * (B_EMPTYQ + 2), 0);
                    mbar_expect(bar + 8 * B_GO, 2 * BLK);
#pragma unroll 1
                    for (int i = 0; i < 2; i++) tma4d(sb + OFF_A + i * BLK, &mp.wo, 0, 0, (z * 2 + i) * 14, ic >> 1, bar + 8 * B_GO);
                    mbar_wait(bar + 8 * B_GO, 0);
#pragma unroll 1
                    for (int i = 0; i < 2; i++) {
                        uint8_t* dst = scr + G_BIMG + (ic * 2 + i) * BLK;
                        bulk_store(dst + rot * 6144, sb + OFF_A + i * BLK, 8192);
                        bulk_store(dst + (rot ^ 1) * 8192, sb + OFF_A + i * BLK + 8192, 6144);
                    }
                    bulk_commit();
                    bulk_wait_all();
                    publish(ctr + C_WO);
                    TS(44);
                }
#pragma unroll 1
                for (uint32_t r = 0; r < r_o; r++) {
                    const uint32_t s = slot(r), fb = bar + 8 * (B_FULL + s);
                    wait_free(r, 0x654320u);
                    mbar_expect(fb, 16384);
                    tma3d(sb + OFF_A + s * 16384, &mp.w1, 0, z * 1024 + r * 64, 2 * q, fb);
                    TS(99 + r);
                }
                mbar_wait(bar + 8 * B_OST, 0);
#pragma unroll 1
                for (uint32_t i = 0; i < 2; i++) {
                    wait_free(r_o + i, 0x654320u);
                    mbar_expect(bar + 8 * (B_LAND + slot(r_o + i)), 16384);
                }
                poll(ctr + C_O + ((q & ~1) + z) * 32, epoch() * 8);
                TS(32);
                fetch_x(0, false);
                fetch_x(1, false);
                TS(99 + 17);
#pragma unroll 1
                for (uint32_t i = 2; i < 4; i++) {
                    wait_free(r_o + i, 0x654320u);
                    fetch_x(i);
                    TS(99 + 17 + i);
                }
#pragma unroll 1
                for (uint32_t i = 0; i < 14; i++) {
                    const uint32_t r = r_u + i, s = slot(r), fb = bar + 8 * (B_FULL + s);
                    wait_free(r, 0x654320u);
                    mbar_expect(fb, 16384);
                    tma3d(sb + OFF_A + s * 16384, &mp.w2, 0, (14 * z + (i < 7 ? 2 * i : 2 * i - 13)) * 64, 2 * q, fb);
                    TS(99 + 21 + i);
                }
                wait_free(r_u + 14, 0);
                mbar_expect(bar + 8 * B_XR, 16384);
                tma2d(sb + OFF_A + slot(r_u + 14) * 16384, &mp.xn, j * 112 + z * 64, q * 128, bar + 8 * B_XR);
            }
        } else if (warp == 13) {
            if (elect()) {
#pragma unroll 1
                for (int ph = g1 ? 0 : 1; ph < 4; ph++) {
                    const uint8_t* src = ph == 0 ? scr + G_HIMG + (64 * z + j) * BLK : scr + G_BIMG + ((ph == 1 ? 4 * z : 6 + 14 * z + ph) * 4 + j) * BLK;
                    const uint32_t r0 = ph == 0 ? 0 : r_o + (ph == 1 ? 0 : 7 * ph - 10), r1 = r_o + (ph == 0 ? 0 : 7 * ph - 3);
#pragma unroll 1
                    for (uint32_t r = r0; r < r1; r++, src += ph < 2 ? 4 * BLK : 8 * BLK) {
                        const uint32_t s = slot(r), fb = bar + 8 * ((ph < 2 ? B_FULL : B_LAND) + s);
                        wait_free(r, 0x644332u);
                        mbar_expect(fb, BLK);
                        mbar_wait(bar + 8 * (B_GO + ph), 0);
                        bulk_load(sb + OFF_B + s * BLK, src, BLK, fb);
                        TS(134 + 16 + (ph > 0) + r - r_o);
                    }
                }
            }
        } else if (warp == 14) {
            uint8_t* stcell = scr + G_STATS + ((lane & 1) * 1024 + 8 * b + (lane >> 1)) * 16;
            if (lane < 16) cell_put(stcell, 0, 0, 0);
            const unsigned ev = ld_relaxed(ctr + C_LN);
            uint8_t* hb = scr + G_HIMG + (b & ~3) * BLK;
            const unsigned e1 = (ev >> 7) + 1;
            if (lane == 0) {
                *reinterpret_cast<volatile unsigned*>(smem + OFF_EP) = e1;
                mbar_arrive(bar + 8 * B_EP);
                TS(36);
            }
            bar_sync<10, 288>();
            if (elect()) {
                fence_async_smem();
                TS(42);
                tma4d_store(&mp.hst, sb + OFF_A, 0, 0, b & 3, b & ~3);
                bulk_commit();
            }
            __syncwarp();
            if (lane < 16) {
                const uint2 v = reinterpret_cast<const uint2*>(smem + OFF_LNST)[lane];
                cell_put(stcell, v.x, v.y, e1);
            }
            bulk_wait_all();
            __syncwarp();
            TS(63);
            unsigned rb = 0;
#pragma unroll
            for (int i = 0; i < 4; i++) rb |= ld_relaxed(reinterpret_cast<const unsigned*>(hb + i * BLK + ((b & 3) * 28 + min(lane, 27)) * 128));
            if (lane == 0) {
                mbar_arrive(bar + 8 * B_LNFREE);
                red_relaxed(ctr + C_LN, 1 + (rb & (sb >> 31)));
                TS(37);
                ld_relaxed(ctr + C_U + z * 64);
                ld_relaxed(ctr + C_U + z * 64 + 32);
#pragma unroll 1
                for (int ph = g1 ? 0 : 1; ph < 4; ph++) {
                    if (ph) mbar_wait(bar + 8 * (ph == 1 ? B_HALO : g1 ? B_RECV1 : B_OST), 0);
                    poll(ctr + ph * 32 + (ph >> 1) * z * 64, e1 * (ph == 0 ? 128 : ph == 1 ? 16 : 56));
                    fence_async_global();
                    mbar_arrive(bar + 8 * (B_GO + ph));
                    if (ph != 1) TS(ph == 0 ? 33 : 32 + ph);
                }
            }
        } else {
            if ((sb & 0x3FFFF) != SB0) __trap();
            if (elect()) {
#pragma unroll 1
                for (int i = 3; i < 10; i++) asm volatile("prefetch.tensormap [%0];" ::"l"(reinterpret_cast<const CUtensorMap*>(&mp) + i) : "memory");
            }
            __syncwarp();
            mbar_watch(bar + 8 * B_KV, 0);
#pragma unroll 1
            for (int i = g1 ? 0 : 8; i < 8; i++) {
                uint32_t l = (7 * z + (q >= 7 ? 6 : 0)) * 8 + (i & 3) * 14 + min(lane >> 1, 13);
                if (l >= 112) l -= 112;
                cell_put(scr + G_BIMG + ((8 + 2 * q + (i >> 2)) * 4 + j) * BLK + l * 128 + (l & 24) * 4 + (lane & 1) * 16, ~0u, ~0u, ~0u);
            }
            __threadfence();
            __syncwarp();
            mbar_arrive_if0(bar + 8 * B_FREE, lane);
            TS(59);
#pragma unroll 1
            for (int i = g1 ? 0 : 2; i < 2; i++) {
                mbar_watch(bar + 8 * (B_RECV1 + i), 0);
                delay(DU);
                if (lane == 0) red_relaxed(ctr + C_U + ((q >= 7 ? 2 : 0) + i) * 32, 1);
                TS(22 + i);
            }
            mbar_watch(bar + 8 * B_RECV2, 0);
            mbar_watch(bar + 8 * (B_RECV2 + 1), 0);
        }
    }
}

typedef CUresult (*EncodeFn)(CUtensorMap*, CUtensorMapDataType, cuuint32_t, void*, const cuuint64_t*, const cuuint64_t*, const cuuint32_t*,
                             const cuuint32_t*, CUtensorMapInterleave, CUtensorMapSwizzle, CUtensorMapL2promotion, CUtensorMapFloatOOBfill);

void encode(EncodeFn fn, CUtensorMap* m, const void* p, int rank, const cuuint64_t* dims, const cuuint64_t* strides, const cuuint32_t* box, bool swz) {
    const cuuint32_t es[4] = {1, 1, 1, 1};
    fn(m, CU_TENSOR_MAP_DATA_TYPE_BFLOAT16, rank, const_cast<void*>(p), dims, strides, box, es, CU_TENSOR_MAP_INTERLEAVE_NONE,
       swz ? CU_TENSOR_MAP_SWIZZLE_128B : CU_TENSOR_MAP_SWIZZLE_NONE, CU_TENSOR_MAP_L2_PROMOTION_L2_128B, CU_TENSOR_MAP_FLOAT_OOB_FILL_NONE);
}

}

extern "C" void kernel_launch(void* const* d_in, const int* in_sizes, int n_in, void* d_out, int out_size) {
    const __nv_bfloat16* x = (const __nv_bfloat16*)d_in[0];
    const __nv_bfloat16* wqkv = (const __nv_bfloat16*)d_in[1];
    const __nv_bfloat16* wo = (const __nv_bfloat16*)d_in[2];
    const __nv_bfloat16* w1 = (const __nv_bfloat16*)d_in[4];
    const __nv_bfloat16* b1 = (const __nv_bfloat16*)d_in[5];
    const __nv_bfloat16* w2 = (const __nv_bfloat16*)d_in[6];
    const __nv_bfloat16* b2 = (const __nv_bfloat16*)d_in[7];

    void* fp = nullptr;
    cudaDriverEntryPointQueryResult qr;
    cudaGetDriverEntryPoint("cuTensorMapEncodeTiled", &fp, cudaEnableDefault, &qr);
    EncodeFn fn = (EncodeFn)fp;
    void* sp = nullptr;
    cudaGetSymbolAddress(&sp, g_scratch);
    uint8_t* scr = (uint8_t*)sp;
    void *o = scr + G_O, *himg = scr + G_HIMG;

    Maps mp;
    { cuuint64_t d[3] = {64, 2048, 7}, s[2] = {896, 128}; cuuint32_t bx[3] = {64, 16, 7}; encode(fn, &mp.xl, x, 3, d, s, bx, true); }
    { cuuint64_t d[2] = {896, 1024}, s[1] = {1792}; cuuint32_t bx[2] = {64, 128}; encode(fn, &mp.x, x, 2, d, s, bx, true); }
    { cuuint64_t d[3] = {448, 448, 3}, s[2] = {2688, 896}; cuuint32_t bx[3] = {64, 32, 3}; encode(fn, &mp.wqkv, wqkv, 3, d, s, bx, true); }
    { cuuint64_t d[3] = {64, 2048, 28}, s[2] = {3584, 128}; cuuint32_t bx[3] = {64, 64, 2}; encode(fn, &mp.w1, w1, 3, d, s, bx, true); }
    { cuuint64_t d[3] = {64, 1792, 32}, s[2] = {4096, 128}; cuuint32_t bx[3] = {64, 64, 2}; encode(fn, &mp.w2, w2, 3, d, s, bx, true); }
    { cuuint64_t d[4] = {64, 28, 4, 128}, s[3] = {128, 3584, BLK}; cuuint32_t bx[4] = {64, 28, 1, 4}; encode(fn, &mp.hst, himg, 4, d, s, bx, false); }
    { cuuint64_t d[2] = {448, 2048}, s[1] = {896}; cuuint32_t bx[2] = {64, 128}; encode(fn, &mp.xn, x, 2, d, s, bx, true); }
    { cuuint64_t d[2] = {64, 8 * 2048}, s[1] = {128}; cuuint32_t bx[2] = {64, 128}; encode(fn, &mp.old_, o, 2, d, s, bx, true); }
    { cuuint64_t d[2] = {128, 8 * 1024}, s[1] = {256}; cuuint32_t bx[2] = {64, 128}; encode(fn, &mp.ost, o, 2, d, s, bx, true); }
    { cuuint64_t d[4] = {8, 56, 56, 8}, s[3] = {896, 16, 56 * 896}; cuuint32_t bx[4] = {8, 64, 14, 1}; encode(fn, &mp.wo, wo, 4, d, s, bx, false); }

    cudaFuncSetAttribute(fused_kernel, cudaFuncAttributeMaxDynamicSharedMemorySize, SMEM_BYTES);
    fused_kernel<<<128, 512, SMEM_BYTES>>>(x, b1, b2, scr, (uint8_t*)d_out, mp);
}
```

```cpp
#include <cuda_runtime.h>
#include <cuda.h>
#include <cuda_bf16.h>
#include <stdint.h>

namespace {

constexpr int S_ = 2048, D_ = 448;
constexpr uint32_t BLK = 14336;

constexpr uint32_t G_HIMG = 0;
constexpr uint32_t G_BIMG = G_HIMG + 32 * 4 * BLK;
constexpr uint32_t G_O = G_BIMG + 36 * 4 * BLK;
constexpr uint32_t G_STATS = G_O + 8 * S_ * 128;
constexpr uint32_t G_CS = G_STATS + S_ * 16;
constexpr uint32_t G_HALO = G_CS + 8 * 4 * 2048;
constexpr uint32_t G_CTR = G_HALO + 128 * 3584;
constexpr uint32_t G_END = G_CTR + (192 + 16 * 32) * 4;
__device__ __align__(1024) uint8_t g_scratch[G_END];

constexpr int C_LN = 0, C_WO = 32, C_U = 64, C_O = 192;

#define TSX(sel, id)
#define TS(id)
#define TS0(id)
#define TSH(id)
#define TSW(id)
#define TG(id)

#define TSG1 0
#define TSD(id)
#define QDEPTH 3
#define ROT 6
#define KS 3
#define DLY1 2200
#define DLY2 1600
#define GATHER 3
#define NS2 3
#define NE 2
#define PRE0 9
#define PRE1 6
#define DU 120
#define DO 200
#define DH 400
#define EXP 2
#define BU 2
#define B1 3
#define GX 1
#define GL 0
#define SPW 1
#define OW 1
#define GS 12
#define OU 4
#define SI 1
#define MX 12
#define NQ 0
constexpr uint32_t OFF_A = 0;
constexpr uint32_t OFF_B = 98304;
constexpr uint32_t OFF_X = 184320;
constexpr uint32_t OFF_K = 196608;
constexpr uint32_t OFF_V = OFF_K + 9 * 896;
constexpr uint32_t OFF_OST = OFF_X, OFF_RECV2 = OFF_X, OFF_RECV1 = OFF_X + 16384, OFF_OUT = OFF_X + 16384;
constexpr uint32_t OFF_SA = OFF_X, OFF_SB = OFF_RECV1 + BLK;
constexpr uint32_t OFF_CSB = 221184;
constexpr uint32_t OFF_ONES = OFF_CSB + 3072;
constexpr uint32_t OFF_STATS = OFF_ONES + 512;
constexpr uint32_t OFF_BIAS = OFF_STATS + 1024;
constexpr uint32_t OFF_LNX = OFF_BIAS + 1024;
constexpr uint32_t OFF_RSTD = OFF_LNX + 512;
constexpr uint32_t OFF_LNST = 229376;
constexpr uint32_t OFF_EP = OFF_LNST + 128;
constexpr uint32_t OFF_BAR = OFF_EP + 16;
constexpr uint32_t OFF_TS = OFF_BAR + 8 * 48;
constexpr uint32_t SMEM_BYTES = OFF_TS;

enum : int {
    B_FULLQ = 0, B_LNIN = 7, B_EMPTYQ = 8, B_FULL = 15, B_EMPTY = 22, B_AUX = 29, B_QKV, B_HALO, B_FREE, B_RECV1, B_RECV2 = B_RECV1 + 2,
    B_EP = B_RECV2 + 2, B_OST, B_LNFREE, B_UDONE, B_NONE, B_GO, B_XR = B_GO + 4, B_KV, B_COUNT, B_LAND = B_FULLQ
};
constexpr uint32_t XSLOT = 0x5432154u;
constexpr uint32_t WSLOT = 0x3421034u;
#define ATT_STEP 10

__device__ __forceinline__ uint32_t smem_u32(const void* p) { return (uint32_t)__cvta_generic_to_shared(p); }
__device__ __forceinline__ void mbar_init(uint32_t a, int c) { asm volatile("mbarrier.init.shared::cta.b64 [%0], %1;" ::"r"(a), "r"(c) : "memory"); }
__device__ __forceinline__ void mbar_expect(uint32_t a, uint32_t b) { asm volatile("mbarrier.arrive.expect_tx.shared::cta.b64 _, [%0], %1;" ::"r"(a), "r"(b) : "memory"); }
__device__ __forceinline__ void mbar_arrive(uint32_t a) { asm volatile("mbarrier.arrive.shared::cta.b64 _, [%0];" ::"r"(a) : "memory"); }
__device__ __forceinline__ void mbar_arrive_if0(uint32_t a, uint32_t sel) {
    asm volatile("{\n.reg .pred p;\nsetp.eq.u32 p, %1, 0;\n@p mbarrier.arrive.shared::cta.b64 _, [%0];\n}" ::"r"(a), "r"(sel) : "memory");
}
__device__ __forceinline__ void mbar_wait(uint32_t a, uint32_t parity) {
    asm volatile("{\n.reg .pred p;\nW0:\nmbarrier.try_wait.parity.shared::cta.b64 p, [%0], %1;\n@!p bra W0;\n}\n" ::"r"(a), "r"(parity) : "memory");
}
__device__ __forceinline__ void mbar_wait_if0(uint32_t a, uint32_t parity, uint32_t sel) {
    asm volatile("{\n.reg .pred p;\nsetp.ne.u32 p, %2, 0;\nW0:\n@!p mbarrier.try_wait.parity.shared::cta.b64 p, [%0], %1;\n@!p bra W0;\n}\n" ::"r"(a), "r"(parity), "r"(sel) : "memory");
}
__device__ __forceinline__ void mbar_watch(uint32_t a, uint32_t parity) {
    asm volatile(
        "{\n.reg .pred p;\n.reg .u32 n;\nmov.u32 n, 0;\n"
        "W0:\nmbarrier.try_wait.parity.shared::cta.b64 p, [%0], %1;\n@p bra W1;\n"
        "add.u32 n, n, 1;\nsetp.lt.u32 p, n, 4194304;\n@p bra W0;\ntrap;\nW1:\n}\n" ::"r"(a), "r"(parity) : "memory");
}
__device__ __forceinline__ bool elect() {
    uint32_t r;
    asm volatile("{\n.reg .pred p;\nelect.sync _|p, 0xffffffff;\nselp.u32 %0, 1, 0, p;\n}" : "=r"(r));
    return r;
}
__device__ __forceinline__ uint32_t mapa(uint32_t a, uint32_t cta) { uint32_t r; asm("mapa.shared::cluster.u32 %0, %1, %2;" : "=r"(r) : "r"(a), "r"(cta)); return r; }
__device__ __forceinline__ void tma2d(uint32_t dst, const CUtensorMap* m, int c0, int c1, uint32_t bar) {
    asm volatile("cp.async.bulk.tensor.2d.shared::cluster.global.mbarrier::complete_tx::bytes [%0], [%1, {%3, %4}], [%2];" ::"r"(dst), "l"(m), "r"(bar), "r"(c0), "r"(c1) : "memory");
}
__device__ __forceinline__ void tma3d(uint32_t dst, const CUtensorMap* m, int c0, int c1, int c2, uint32_t bar) {
    asm volatile("cp.async.bulk.tensor.3d.shared::cluster.global.mbarrier::complete_tx::bytes [%0], [%1, {%3, %4, %5}], [%2];" ::"r"(dst), "l"(m), "r"(bar), "r"(c0), "r"(c1), "r"(c2) : "memory");
}
__device__ __forceinline__ void tma3d_mc(uint32_t dst, const CUtensorMap* m, int c0, int c1, int c2, uint32_t bar) {
    asm volatile("cp.async.bulk.tensor.3d.shared::cluster.global.mbarrier::complete_tx::bytes.multicast::cluster [%0], [%1, {%3, %4, %5}], [%2], %6;"
                 ::"r"(dst), "l"(m), "r"(bar), "r"(c0), "r"(c1), "r"(c2), "h"((uint16_t)3) : "memory");
}
__device__ __forceinline__ void tma2d_store(const CUtensorMap* m, uint32_t src, int c0, int c1) {
    asm volatile("cp.async.bulk.tensor.2d.global.shared::cta.bulk_group [%0, {%2, %3}], [%1];" ::"l"(m), "r"(src), "r"(c0), "r"(c1) : "memory");
}
__device__ __forceinline__ void tma4d_store(const CUtensorMap* m, uint32_t src, int c0, int c1, int c2, int c3) {
    asm volatile("cp.async.bulk.tensor.4d.global.shared::cta.bulk_group [%0, {%2, %3, %4, %5}], [%1];" ::"l"(m), "r"(src), "r"(c0), "r"(c1), "r"(c2), "r"(c3) : "memory");
}
__device__ __forceinline__ void tma4d(uint32_t dst, const CUtensorMap* m, int c0, int c1, int c2, int c3, uint32_t bar) {
    asm volatile("cp.async.bulk.tensor.4d.shared::cluster.global.mbarrier::complete_tx::bytes [%0], [%1, {%3, %4, %5, %6}], [%2];" ::"r"(dst), "l"(m), "r"(bar), "r"(c0), "r"(c1), "r"(c2), "r"(c3) : "memory");
}
__device__ __forceinline__ void bulk_load(uint32_t dst, const void* src, uint32_t bytes, uint32_t bar) {
    asm volatile("cp.async.bulk.shared::cluster.global.mbarrier::complete_tx::bytes [%0], [%1], %2, [%3];" ::"r"(dst), "l"(src), "r"(bytes), "r"(bar) : "memory");
}
__device__ __forceinline__ void bulk_store(void* dst, uint32_t src, uint32_t bytes) {
    asm volatile("cp.async.bulk.global.shared::cta.bulk_group [%0], [%1], %2;" ::"l"(dst), "r"(src), "r"(bytes) : "memory");
}
__device__ __forceinline__ void bulk_commit() { asm volatile("cp.async.bulk.commit_group;" ::: "memory"); }
__device__ __forceinline__ void bulk_wait_all() { asm volatile("cp.async.bulk.wait_group 0;" ::: "memory"); }
__device__ __forceinline__ void bulk_wait_read() { asm volatile("cp.async.bulk.wait_group.read 0;" ::: "memory"); }
__device__ __forceinline__ void l2_prefetch(const void* p) { asm volatile("prefetch.global.L2 [%0];" ::"l"(p)); }
__device__ __forceinline__ void fence_async_smem() { asm volatile("fence.proxy.async.shared::cta;" ::: "memory"); }
__device__ __forceinline__ void fence_async_global() { asm volatile("fence.proxy.async.global;" ::: "memory"); }
__device__ __forceinline__ void red_relaxed(unsigned* p, unsigned v) { asm volatile("red.relaxed.gpu.global.add.u32 [%0], %1;" ::"l"(p), "r"(v) : "memory"); }
__device__ __forceinline__ void publish(unsigned* p) {
    asm volatile("fence.proxy.async.global;\nred.release.gpu.global.add.u32 [%0], 1;" ::"l"(p) : "memory");
}
__device__ __forceinline__ void stg32(void* p, uint32_t v) { asm volatile("st.global.b32 [%0], %1;" ::"l"(p), "r"(v) : "memory"); }
__device__ __forceinline__ unsigned ld_relaxed(const unsigned* p) { unsigned v; asm volatile("ld.relaxed.gpu.global.u32 %0, [%1];" : "=r"(v) : "l"(p) : "memory"); return v; }
__device__ __forceinline__ bool ctr_done(unsigned v, unsigned target) { return ((v - target) & 0x1FFFFFFu) == 0; }
__device__ __forceinline__ uint32_t clock32() { uint32_t c; asm volatile("mov.u32 %0, %%clock;" : "=r"(c)::"memory"); return c; }
__device__ __forceinline__ void delay(uint32_t n) { const uint32_t t0 = clock32(); while (clock32() - t0 < n) {} }
__device__ __forceinline__ void poll(const unsigned* p, unsigned target) { while (!ctr_done(ld_relaxed(p), target)) {} }
__device__ __forceinline__ void cell_put(void* p, uint32_t a, uint32_t b, uint32_t tag) {
    asm volatile("st.relaxed.gpu.global.v4.b32 [%0], {%1, %3, %2, %3};" ::"l"(p), "r"(a), "r"(b), "r"(tag) : "memory");
}
__device__ __forceinline__ uint32_t cell_get(const void* p, uint32_t& a, uint32_t& b, uint32_t tag) {
    uint32_t t0, t1;
    asm volatile("ld.relaxed.gpu.global.v4.b32 {%0, %1, %2, %3}, [%4];" : "=r"(a), "=r"(t0), "=r"(b), "=r"(t1) : "l"(p) : "memory");
    return (t0 ^ tag) | (t1 ^ tag);
}
template <int ID, int N> __device__ __forceinline__ void bar_sync() { asm volatile("bar.sync %0, %1;" ::"n"(ID), "n"(N) : "memory"); }
template <int ID = 4> __device__ __forceinline__ void gate_wait(uint32_t on) { asm volatile("{\n.reg .pred p;\nsetp.ne.u32 p, %0, 0;\n@p bar.sync %1, 256;\n}" ::"r"(on), "n"(ID) : "memory"); }
template <int ID = 4> __device__ __forceinline__ void gate_open(uint32_t off) { asm volatile("{\n.reg .pred p;\nsetp.eq.u32 p, %0, 0;\n@p bar.arrive %1, 256;\n}" ::"r"(off), "n"(ID) : "memory"); }
__device__ __forceinline__ void wg_fence() { asm volatile("wgmma.fence.sync.aligned;" ::: "memory"); }
__device__ __forceinline__ void wg_commit() { asm volatile("wgmma.commit_group.sync.aligned;" ::: "memory"); }
template <int N> __device__ __forceinline__ void wg_wait() { asm volatile("wgmma.wait_group.sync.aligned %0;" ::"n"(N) : "memory"); }
template <int LO = 0, int HI = 56, int N> __device__ __forceinline__ void pin(float (&a)[N]) {
#pragma unroll
    for (int i = LO; i < (HI < N ? HI : N); i++) asm volatile("" : "+f"(a[i])::"memory");
}
__device__ __forceinline__ uint32_t ldg_u16(const void* p) {
    uint32_t v;
    asm volatile("ld.global.nc.u16 %0, [%1];" : "=r"(v) : "l"(p) : "memory");
    return v;
}
__device__ __forceinline__ uint32_t pack2(float lo, float hi) { uint32_t r; asm("cvt.rn.bf16x2.f32 %0, %1, %2;" : "=r"(r) : "f"(hi), "f"(lo)); return r; }
__device__ __forceinline__ float bf_lo(uint32_t v) { return __uint_as_float(v << 16); }
__device__ __forceinline__ float bf_hi(uint32_t v) { return __uint_as_float(v & 0xFFFF0000u); }
__device__ __forceinline__ uint32_t split2(float x) { return pack2(x, x - bf_lo(pack2(x, 0.f))); }
__device__ __forceinline__ void stsm4(uint32_t a, uint32_t r0, uint32_t r1, uint32_t r2, uint32_t r3) {
    asm volatile("stmatrix.sync.aligned.m8n8.x4.shared.b16 [%0], {%1, %2, %3, %4};" ::"r"(a), "r"(r0), "r"(r1), "r"(r2), "r"(r3) : "memory");
}
__device__ __forceinline__ void stsm2(uint32_t a, uint32_t r0, uint32_t r1) {
    asm volatile("stmatrix.sync.aligned.m8n8.x2.shared.b16 [%0], {%1, %2};" ::"r"(a), "r"(r0), "r"(r1) : "memory");
}
__device__ __forceinline__ void ldsm4(uint32_t a, uint32_t (&r)[4]) {
    asm volatile("ldmatrix.sync.aligned.m8n8.x4.shared.b16 {%0, %1, %2, %3}, [%4];" : "=r"(r[0]), "=r"(r[1]), "=r"(r[2]), "=r"(r[3]) : "r"(a) : "memory");
}
__device__ __forceinline__ void ldsm4t(uint32_t a, uint32_t (&r)[4]) {
    asm volatile("ldmatrix.sync.aligned.m8n8.x4.trans.shared.b16 {%0, %1, %2, %3}, [%4];" : "=r"(r[0]), "=r"(r[1]), "=r"(r[2]), "=r"(r[3]) : "r"(a) : "memory");
}
__device__ __forceinline__ void mma16816(float (&c)[4], uint32_t a0, uint32_t a1, uint32_t a2, uint32_t a3, uint32_t b0, uint32_t b1) {
    asm volatile("mma.sync.aligned.m16n8k16.row.col.f32.bf16.bf16.f32 {%0,%1,%2,%3}, {%4,%5,%6,%7}, {%8,%9}, {%0,%1,%2,%3};"
                 : "+f"(c[0]), "+f"(c[1]), "+f"(c[2]), "+f"(c[3]) : "r"(a0), "r"(a1), "r"(a2), "r"(a3), "r"(b0), "r"(b1));
}
__device__ __forceinline__ void mma1688(float (&c)[4], uint32_t a0, uint32_t a1, uint32_t b0) {
    asm volatile("mma.sync.aligned.m16n8k8.row.col.f32.bf16.bf16.f32 {%0,%1,%2,%3}, {%4,%5}, {%6}, {%0,%1,%2,%3};"
                 : "+f"(c[0]), "+f"(c[1]), "+f"(c[2]), "+f"(c[3]) : "r"(a0), "r"(a1), "r"(b0));
}
constexpr uint32_t SB0 = 1024;
__device__ __forceinline__ uint32_t desc_lo(uint32_t off, uint32_t lbo) { return ((SB0 + off) >> 4) + ((lbo >> 4) << 16); }
constexpr uint32_t H_SW = (1024 >> 4) | (1u << 30), H_H = 128 >> 4, H_U = 1024 >> 4;
__device__ __forceinline__ float ex2(float x) { float r; asm("ex2.approx.ftz.f32 %0, %1;" : "=f"(r) : "f"(x)); return r; }
__device__ __forceinline__ float rsq(float x) { float r; asm("rsqrt.approx.ftz.f32 %0, %1;" : "=f"(r) : "f"(x)); return r; }
__device__ __forceinline__ float rcp(float x) { float r; asm("rcp.approx.ftz.f32 %0, %1;" : "=f"(r) : "f"(x)); return r; }
__device__ __forceinline__ float gelu_half(float h) {
    float y = h * fmaf(h * h, 8.f * 0.0356774081363f, 2.f * 0.7978845608029f), t;
    asm("tanh.approx.f32 %0, %1;" : "=f"(t) : "f"(y));
    return fmaf(h, t, h);
}

template <uint32_t HB, int TB>
__device__ __forceinline__ void wgmma_n56_rs(float (&d)[28], const uint32_t (&a)[4], uint32_t lb, int scale_d) {
    asm volatile("{\n.reg .pred p;\n.reg .b64 db;\nsetp.ne.b32 p, %33, 0;\nmov.b64 db, {%32, %34};\n"
        "wgmma.mma_async.sync.aligned.m64n56k16.f32.bf16.bf16 "
        "{%0, %1, %2, %3, %4, %5, %6, %7, %8, %9, %10, %11, %12, %13, %14, %15, %16, %17, %18, %19, %20, %21, %22, %23, %24, %25, %26, %27}, "
        "{%28, %29, %30, %31}, db, p, 1, 1, %35;\n}\n"
        : "+f"(d[0]), "+f"(d[1]), "+f"(d[2]), "+f"(d[3]), "+f"(d[4]), "+f"(d[5]), "+f"(d[6]), "+f"(d[7]), "+f"(d[8]), "+f"(d[9]), "+f"(d[10]), "+f"(d[11]), "+f"(d[12]), "+f"(d[13]), "+f"(d[14]), "+f"(d[15]), "+f"(d[16]), "+f"(d[17]), "+f"(d[18]), "+f"(d[19]), "+f"(d[20]), "+f"(d[21]), "+f"(d[22]), "+f"(d[23]), "+f"(d[24]), "+f"(d[25]), "+f"(d[26]), "+f"(d[27])
        : "r"(a[0]), "r"(a[1]), "r"(a[2]), "r"(a[3]), "r"(lb), "r"(scale_d), "n"(HB), "n"(TB));
}
template <int TA, uint32_t HA, uint32_t HB>
__device__ __forceinline__ void wgmma_n112(float (&d)[56], uint32_t la, uint32_t lb, int scale_d = 1) {
    asm volatile("{\n.reg .b64 da, db;\n.reg .pred p;\nsetp.ne.b32 p, %61, 0;\nmov.b64 da, {%56, %59};\nmov.b64 db, {%57, %60};\n"
        "wgmma.mma_async.sync.aligned.m64n112k16.f32.bf16.bf16 "
        "{%0, %1, %2, %3, %4, %5, %6, %7, %8, %9, %10, %11, %12, %13, %14, %15, %16, %17, %18, %19, %20, %21, %22, %23, %24, %25, %26, %27, %28, %29, %30, %31, %32, %33, %34, %35, %36, %37, %38, %39, %40, %41, %42, %43, %44, %45, %46, %47, %48, %49, %50, %51, %52, %53, %54, %55}, "
        "da, db, p, 1, 1, %58, 1;\n}\n"
        : "+f"(d[0]), "+f"(d[1]), "+f"(d[2]), "+f"(d[3]), "+f"(d[4]), "+f"(d[5]), "+f"(d[6]), "+f"(d[7]), "+f"(d[8]), "+f"(d[9]), "+f"(d[10]), "+f"(d[11]), "+f"(d[12]), "+f"(d[13]), "+f"(d[14]), "+f"(d[15]), "+f"(d[16]), "+f"(d[17]), "+f"(d[18]), "+f"(d[19]), "+f"(d[20]), "+f"(d[21]), "+f"(d[22]), "+f"(d[23]), "+f"(d[24]), "+f"(d[25]), "+f"(d[26]), "+f"(d[27]), "+f"(d[28]), "+f"(d[29]), "+f"(d[30]), "+f"(d[31]), "+f"(d[32]), "+f"(d[33]), "+f"(d[34]), "+f"(d[35]), "+f"(d[36]), "+f"(d[37]), "+f"(d[38]), "+f"(d[39]), "+f"(d[40]), "+f"(d[41]), "+f"(d[42]), "+f"(d[43]), "+f"(d[44]), "+f"(d[45]), "+f"(d[46]), "+f"(d[47]), "+f"(d[48]), "+f"(d[49]), "+f"(d[50]), "+f"(d[51]), "+f"(d[52]), "+f"(d[53]), "+f"(d[54]), "+f"(d[55])
        : "r"(la), "r"(lb), "n"(TA), "n"(HA), "n"(HB), "r"(scale_d));
}
template <int TA, uint32_t HA, uint32_t HB>
__device__ __forceinline__ void wgmma_n8(float (&d)[4], uint32_t la, uint32_t lb, int scale_d = 1) {
    asm volatile("{\n.reg .b64 da, db;\n.reg .pred p;\nsetp.ne.b32 p, %9, 0;\nmov.b64 da, {%4, %7};\nmov.b64 db, {%5, %8};\n"
        "wgmma.mma_async.sync.aligned.m64n8k16.f32.bf16.bf16 "
        "{%0, %1, %2, %3}, "
        "da, db, p, 1, 1, %6, 1;\n}\n"
        : "+f"(d[0]), "+f"(d[1]), "+f"(d[2]), "+f"(d[3])
        : "r"(la), "r"(lb), "n"(TA), "n"(HA), "n"(HB), "r"(scale_d));
}

__device__ __forceinline__ void send4(uint32_t rbuf, uint32_t rbar, uint32_t w0, uint32_t w1, uint32_t w2, uint32_t w3, uint32_t on) {
    asm volatile("{\n.reg .pred p;\nsetp.ne.u32 p, %6, 0;\n@p st.async.weak.shared::cluster.mbarrier::complete_tx::bytes.v4.b32 [%0], {%1,%2,%3,%4}, [%5];\n}"
                 ::"r"(rbuf), "r"(w0), "r"(w1), "r"(w2), "r"(w3), "r"(rbar), "r"(on) : "memory");
}
__device__ __forceinline__ void send_half(const float (&a)[56], uint32_t rbuf, uint32_t rbar, int t, uint32_t on) {
#pragma unroll
    for (int i = 28; i < 52; i += 8)
        send4(rbuf + (i - 28) * 256 + t * 16, rbar, pack2(a[i], a[i + 1]), pack2(a[i + 2], a[i + 3]), pack2(a[i + 4], a[i + 5]), pack2(a[i + 6], a[i + 7]), on);
    asm volatile("{\n.reg .pred p;\nsetp.ne.u32 p, %4, 0;\n@p st.async.weak.shared::cluster.mbarrier::complete_tx::bytes.v2.b32 [%0], {%1,%2}, [%3];\n}"
                 ::"r"(rbuf + 6144 + t * 8), "r"(pack2(a[52], a[53])), "r"(pack2(a[54], a[55])), "r"(rbar), "r"(on) : "memory");
}
__device__ __forceinline__ void recv_half(uint32_t (&p)[14], uint32_t buf, int t) {
#pragma unroll
    for (int i = 0; i < 3; i++)
        asm volatile("ld.shared.v4.b32 {%0,%1,%2,%3}, [%4];" : "=r"(p[4 * i]), "=r"(p[4 * i + 1]), "=r"(p[4 * i + 2]), "=r"(p[4 * i + 3]) : "r"(buf + i * 2048 + t * 16) : "memory");
    asm volatile("ld.shared.v2.b32 {%0,%1}, [%2];" : "=r"(p[12]), "=r"(p[13]) : "r"(buf + 6144 + t * 8) : "memory");
}

struct Maps { CUtensorMap xl, x, wqkv, hst, w1, w2, xn, old_, ost, wo; };

__global__ void __cluster_dims__(2, 1, 1) __launch_bounds__(512, 1)
fused_kernel(const __nv_bfloat16* __restrict__ x, const __nv_bfloat16* __restrict__ b1, const __nv_bfloat16* __restrict__ b2, uint8_t* __restrict__ scr,
             uint8_t* __restrict__ out, const __grid_constant__ Maps mp) {
    extern __shared__ __align__(1024) uint8_t smem[];
    const uint32_t sb = smem_u32(smem);
    const uint32_t bar = sb + OFF_BAR;
    const int tid = threadIdx.x, lane = tid & 31;
    const int b = blockIdx.x, z = b & 1, c = b >> 1;
    unsigned* const ctr = reinterpret_cast<unsigned*>(scr + G_CTR);
    if (tid < 112) l2_prefetch(reinterpret_cast<const uint8_t*>(x) + (b * 112 + tid) * 128);
    const uint32_t t_in = clock32();
    TS0(0);
    TG(60);
    const int warp = __shfl_sync(0xffffffffu, tid >> 5, 0);
    const int j = c < 4 ? c : c < 36 ? (c - 4) >> 3 : ((c - 36) * 37) >> 8, q = c < 4 ? 15 : c < 36 ? (c - 4) & 7 : c - 28 - 7 * j;
    const bool g1 = q < 14;
    const int R = q < 8 ? q : (0x27654310u >> (4 * q - 32)) & 7, P = (q >> 3) * 4 + j;
    auto krow = [&](int kb) { const int k = kb + (R & ROT); return (k >= 7 ? k - 7 : k) * 64; };
    auto x_load = [&](int kb) {
        mbar_expect(bar + 8 * (B_FULLQ + kb), 40960);
        tma2d(sb + OFF_A + ((XSLOT >> (4 * kb)) & 7) * 16384, &mp.x, z * D_ + krow(kb), R * 128, bar + 8 * (B_FULLQ + kb));
    };
    auto w_load = [&](int kb) {
        tma3d_mc(sb + OFF_B + ((WSLOT >> (4 * kb)) & 7) * 24576 + z * 12288, &mp.wqkv, (P * 56) & ~15, krow(kb) + z * 32, 0, bar + 8 * (B_FULLQ + kb));
    };
    if (warp == 12 && elect()) {
#pragma unroll
        for (int i = B_FULLQ; i < B_EMPTYQ; i++) mbar_init(bar + 8 * i, 1);
        mbar_expect(bar + 8 * B_LNIN, BLK);
        tma3d(sb + OFF_A, &mp.xl, 0, 16 * b, 0, bar + 8 * B_LNIN);
        x_load(0);
        TS(15);
    }
    auto bar_count = [&](int i) {
        return i < B_FULL ? (i < B_EMPTYQ + 2 ? 16 : 8) + (((i - B_EMPTYQ) & ~1) == (R & 6 & ~ROT) ? 8 : 0) : i < B_EMPTY || i == B_FREE ? 2 : (i < B_AUX || i == B_NONE || i == B_OST) ? 8 : i == B_KV ? 12
               : (i == B_AUX || i == B_HALO) ? 4 : 1;
    };
    if (warp == 13 && elect()) {
#pragma unroll
        for (int i = B_EMPTYQ; i < B_COUNT; i++) mbar_init(bar + 8 * i, bar_count(i));
#pragma unroll
        for (int i = B_RECV1; i < B_EP; i++) mbar_expect(bar + 8 * i, i < B_RECV2 ? 7168 : 8192 - 2048 * z);
    }
    asm volatile("fence.mbarrier_init.release.cluster;" ::: "memory");
    __syncwarp();
    asm volatile("barrier.cluster.arrive.relaxed.aligned;\nbarrier.cluster.wait.aligned;" ::: "memory");
    if (warp == 12 && elect()) { w_load(0); TS(16); }
    auto slot = [](uint32_t r) { return r - 6 * ((r * 43) >> 8); };
    auto phase = [](uint32_t r) { return ((r * 43) >> 8) & 1; };
    const uint32_t r_o = g1 ? 16 : 0, r_u = r_o + 3;
    auto xslot = [&](uint32_t i) { return i == SI ? 6 : slot(r_o + i - (i > SI)); };
    auto aoff = [](uint32_t s) { return s == 6 ? OFF_SA - OFF_A : s * 16384; };
    auto fetch_x = [&](uint32_t i, bool arm = true) {
        const uint32_t s = xslot(i), lb = bar + 8 * (B_LAND + s);
        if (arm) mbar_expect(lb, i < 4 ? 16384 : BLK);
        if (i < 4) tma2d(sb + OFF_A + aoff(s), &mp.old_, 0, (4 * z + i) * S_ + q * 128, lb);
        else bulk_load(sb + OFF_B + s * BLK, scr + G_BIMG + ((14 * z + (i < 11 ? 2 * i : 2 * i - 13)) * 4 + j) * BLK, BLK, lb);
    };
    auto epoch = [&]() { mbar_wait(bar + 8 * B_EP, 0); return *reinterpret_cast<volatile unsigned*>(smem + OFF_EP); };

    if (warp < 8) {
        const int wg = warp >> 2, w4 = warp & 3, t = tid & 127, g = lane >> 2, tq = lane & 3;
        asm volatile("setmaxnreg.inc.sync.aligned.u32 208;");
        uint32_t xa[4];
#pragma unroll
        for (int k = 0; k < 4; k++) xa[k] = sb + OFF_A + (warp * 16 + (lane & 15)) * 128 + (((2 * k + (lane >> 4)) ^ (lane & 7)) << 4);
        {
            const int rg = warp & 1, jq = warp >> 1;
            const uint32_t ex = sb + OFF_LNX + (rg * 8 + g) * 32, ew = ex + jq * 8, ls = sb + OFF_LNST + (rg * 8 + g) * 8;
            const uint32_t l0 = sb + OFF_A + rg * 1024 + g * 144;
            uint32_t r[4][4], la[4], ha[4], x0, dep = ex | ew | ls | l0;
#pragma unroll
            for (int i = 0; i < 4; i++) {
                const int cg = 14 * jq + 4 * i + ((lane >> 3) & (i < 3 ? 3 : 1));
                la[i] = sb + OFF_A + (cg >> 3) * 2048 + rg * 1024 + (lane & 7) * 128 + (((cg ^ lane) & 7) << 4);
                int pos = 4 * i + (lane >> 3) + (b >= 64 ? 7 : 0);
                if (pos >= 14) pos -= 14;
                ha[i] = sb + OFF_A + jq * 3584 + rg * 1792 + (lane & 7) * 16 + pos * 128;
                dep |= la[i] | xa[i] | ha[i];
            }
            mbar_wait(bar + 8 * B_LNIN, dep >> 31);
            asm volatile("ld.shared.b32 %0, [%1];" : "=r"(x0) : "r"(l0) : "memory");
#pragma unroll
            for (int i = 0; i < 4; i++) ldsm4(la[i], r[i]);
            float s1[4], s2[4], v[28];
            const float sh = bf_lo(x0);
#pragma unroll
            for (int n = 0; n < 14; n++) { v[2 * n] = bf_lo(r[n >> 2][n & 3]) - sh; v[2 * n + 1] = bf_hi(r[n >> 2][n & 3]) - sh; }
#pragma unroll
            for (int n = 0; n < 28; n++) {
                s1[n & 3] = n < 4 ? v[n] : s1[n & 3] + v[n];
                s2[n & 3] = n < 4 ? v[n] * v[n] : fmaf(v[n], v[n], s2[n & 3]);
            }
            float m1 = (s1[0] + s1[1]) + (s1[2] + s1[3]), m2 = (s2[0] + s2[1]) + (s2[2] + s2[3]);
#pragma unroll
            for (int o = 1; o <= 2; o <<= 1) { m1 += __shfl_xor_sync(0xffffffffu, m1, o); m2 += __shfl_xor_sync(0xffffffffu, m2, o); }
            asm volatile("st.shared.v2.f32 [%0], {%1, %2};" ::"r"(ew), "f"(m1), "f"(m2) : "memory");
            bar_sync<1, 256>();
            float4 e0, e1;
            asm volatile("ld.shared.v4.f32 {%0,%1,%2,%3}, [%4];" : "=f"(e0.x), "=f"(e0.y), "=f"(e0.z), "=f"(e0.w) : "r"(ex) : "memory");
            asm volatile("ld.shared.v4.f32 {%0,%1,%2,%3}, [%4];" : "=f"(e1.x), "=f"(e1.y), "=f"(e1.z), "=f"(e1.w) : "r"(ex + 16) : "memory");
            const float dm = ((e0.x + e0.z) + (e1.x + e1.z)) * (1.f / D_);
            const float var = fmaxf(fmaf(-dm, dm, ((e0.y + e0.w) + (e1.y + e1.w)) * (1.f / D_)), 0.f);
            const float r1 = rsq(var + 1e-5f), sc = rsq(fmaf(1e-5f, var + 1e-5f, var)), of = -dm * sc;
#pragma unroll
            for (int n = 0; n < 14; n++) r[n >> 2][n & 3] = pack2(fmaf(v[2 * n], sc, of), fmaf(v[2 * n + 1], sc, of));
#pragma unroll
            for (int i = 0; i < 3; i++) stsm4(ha[i], r[i][0], r[i][1], r[i][2], r[i][3]);
            stsm2(ha[3], r[3][0], r[3][1]);
            asm volatile("st.shared.v2.b32 [%0], {%1, %2};" ::"r"(ls), "r"(__float_as_uint(r1)), "r"(split2(-(sh + dm))) : "memory");
            TS0(24);
            asm volatile("bar.arrive 10, 288;" ::: "memory");
        }
        float a1[56];
        float rq[2], hb1[2], fb2[2];
        uint32_t qp[14], kp[14];
        const uint32_t ka = sb + OFF_K + warp * 896 + (lane & 7) * 112 + (lane >> 3) * 16;
        const uint32_t va = sb + OFF_V + (warp * 16 + (lane & 15)) * 112 + (lane >> 4) * 16;
        const uint32_t sta = sb + OFF_RSTD + warp * 64 + tq * 8;
        const uint32_t dA = desc_lo(OFF_A + wg * 8192, 16), dH = desc_lo(OFF_B, 1792), dU = desc_lo(OFF_B, 128);
        auto release = [&](uint32_t a) { mbar_arrive_if0(a, lane); };
        auto sched_fence = [&]() { mbar_wait(bar + 8 * B_LNIN, 0); };
        uint32_t rel = bar + 8 * (B_EMPTYQ + 6);
        auto g1_step = [&](uint32_t s, uint32_t acc) {
            wg_fence();
#pragma unroll
            for (int k = 0; k < 4; k++) wgmma_n112<1, H_SW, H_H>(a1, dA + s * 1024 + k * 128, dH + s * 896 + k * 224, k ? 1 : acc);
            wg_commit();
            wg_wait<1>();
            release(rel);
            rel = bar + 8 * (B_EMPTY + s);
        };
        auto g1_run = [&](uint32_t r0, uint32_t r1, bool last = false) {
#pragma unroll 1
            for (uint32_t r = g1 ? r0 : r1; r < r1; r++) {
                if (TSG1) TSD(64 + r);
                g1_step(slot(r), r);
                const bool end = last && r + 1 == r1;
                mbar_wait(bar + 8 * (end ? B_FREE : B_FULL + slot(r + 1)), !end && phase(r + 1));
            }
        };
        auto g1_wait = [&](uint32_t r) { mbar_wait(bar + 8 * (g1 ? B_FULL + r % 6 : B_LNIN), g1 && ((r / 6) & 1)); };
        auto drain = [&]() { wg_wait<0>(); release(rel); rel = bar + 8 * B_NONE; };
        {
            float aq0[28], aq1[28], aq2[28];
            const uint32_t dW = desc_lo(OFF_B + (P & 1) * 16, 16);
            uint32_t xf[2][4][4];
            const uint32_t rb = mapa(bar + 8 * (B_EMPTYQ - 1), z ^ 1);
            auto fetch = [&](int kb, uint32_t (&f)[4][4]) {
                if (TSG1) TSD(178 + kb);
                mbar_wait(bar + 8 * (B_FULLQ + kb), 0);
                if (TSG1) TSD(170 + kb);
#pragma unroll
                for (int k = 0; k < 4; k++) ldsm4(xa[k] + ((XSLOT >> (4 * kb)) & 7) * 16384, f[k]);
            };
            auto mma = [&](int kb, uint32_t (&f)[4][4], int k0, int k1) {
                const uint32_t d0 = dW + ((WSLOT >> (4 * kb)) & 7) * 1536;
                wg_fence();
#pragma unroll
                for (int k = k0; k < k1; k++) {
                    const uint32_t d = d0 + (k >> 1) * 768 + (k & 1) * 128;
                    const int sc = k > 0 ? 1 : kb;
                    wgmma_n56_rs<H_SW, 1>(aq0, f[k], d, sc);
                    wgmma_n56_rs<H_SW, 1>(aq1, f[k], d + 256, sc);
                    wgmma_n56_rs<H_SW, 1>(aq2, f[k], d + 512, sc);
                }
            };
            auto retire = [&](int kb) {
                wg_commit();
                wg_wait<1>();
                mbar_arrive_if0(bar + 8 * (B_EMPTYQ + kb - 1), lane | (kb < 1));
                asm volatile("{\n.reg .pred p;\nsetp.eq.u32 p, %1, 0;\n@p mbarrier.arrive.shared::cluster.b64 _, [%0];\n}"
                             ::"r"(rb + 8 * kb), "r"(lane | ((uint32_t)(kb - 1) > 1)) : "memory");
            };
            auto stage = [&](int kb, uint32_t (&f)[4][4], uint32_t (&n)[4][4]) {
                mma(kb, f, 0, KS);
                retire(kb);
                fetch(kb + 1, n);
                if (KS < 4) { mma(kb, f, KS, 4); wg_commit(); }
            };
            fetch(0, xf[0]);
#pragma unroll 1
            for (int kb = 0; kb < 6; kb += 2) {
                stage(kb, xf[0], xf[1]);
                stage(kb + 1, xf[1], xf[0]);
            }
            mma(6, xf[0], 0, KS);
            retire(6);
            TS0(2);
            mbar_wait(bar + 8 * B_AUX, 0);
            {
                uint32_t (&f)[4] = xf[1][0];
                const uint2* mt = reinterpret_cast<const uint2*>(smem + OFF_STATS) + warp * 16 + g;
                const uint2 m0 = mt[0], m1 = mt[8];
                const uint32_t sel = tq == 0 ? 0x1010 : tq == 1 ? 0x3232 : 0x4444;
                f[0] = __byte_perm(m0.y, 0, sel); f[1] = __byte_perm(m1.y, 0, sel); f[2] = f[3] = 0;
                rq[0] = __uint_as_float(m0.x); rq[1] = __uint_as_float(m1.x);
                asm volatile("" : "+r"(f[0]), "+r"(f[1]), "+r"(f[2]), "+r"(f[3])::"memory");
                const uint32_t d = desc_lo(OFF_CSB + (P & 1) * 128, 0);
                mma(6, xf[0], KS, 4);
                wgmma_n56_rs<H_H, 0>(aq1, f, d + 64, 1);
                wgmma_n56_rs<H_H, 0>(aq2, f, d + 128, 1);
                wgmma_n56_rs<H_H, 0>(aq0, f, d, 1);
                wg_commit();
            }
            if (MX & 2) mbar_wait_if0(bar + 8 * B_FULL, 0, wg || !g1);
            else g1_wait(0);
            g1_run(0, wg ? 0 : NE);
            drain();
            pin(aq0); pin(aq1); pin(aq2);
            TSW(3);
            mbar_wait(bar + 8 * (B_EMPTYQ + 5), 0);
#pragma unroll
            for (int i = 0; i < 14; i++) { kp[i] = pack2(aq1[2 * i], aq1[2 * i + 1]); qp[i] = pack2(aq2[2 * i], aq2[2 * i + 1]); }
            stsm4(ka + 896, kp[1], kp[3], kp[5], kp[7]);
            stsm4(ka + 896 + 48, kp[7], kp[9], kp[11], kp[13]);
#pragma unroll
            for (int n = 0; n < 3; n++) stsm4(va + 896 + n * 32, qp[4 * n], qp[4 * n + 1], qp[4 * n + 2], qp[4 * n + 3]);
            stsm2(va + 896 + 96, qp[12], qp[13]);
            __syncwarp();
            mbar_arrive_if0(bar + 8 * B_QKV, tid - 224);
            release(bar + 8 * B_KV);
#pragma unroll
            for (int i = 0; i < 14; i++) qp[i] = pack2(aq0[2 * i], aq0[2 * i + 1]);
            TSW(4);
        }
        if (MX & 2) mbar_wait_if0(bar + 8 * B_FULL, 0, !wg || !g1);
        g1_run(wg ? 0 : NE, wg ? PRE1 : PRE0);
        {
            uint32_t kf[2][3][4], vf[2][3][4];
            const bool up0 = 2 * tq > g, up1 = 2 * tq + 1 > g, edge = (R | warp) == 0;
            float rk[2][2], fs[2][2], rs[3][2];
            mbar_wait(bar + 8 * (warp ? B_KV : B_HALO), 0);
            const uint32_t tag = *reinterpret_cast<volatile unsigned*>(smem + OFF_EP);
#pragma unroll
            for (int i = 0; i < 2; i++)
                asm volatile("ld.shared.v2.f32 {%0,%1}, [%2];" : "=f"(hb1[i]), "=f"(fb2[i]) : "r"(sb + OFF_BIAS + (warp * 16 + g + 8 * i) * 8) : "memory");
#pragma unroll
            for (int i = 0; i < 3; i++)
                asm volatile("ld.shared.v2.f32 {%0,%1}, [%2];" : "=f"(rs[i][0]), "=f"(rs[i][1]) : "r"(sta + i * 32) : "memory");
#pragma unroll
            for (int hd = 0; hd < 2; hd++) {
                ldsm4(ka + hd * 48, kf[hd][0]);
#pragma unroll
                for (int i = 0; i < 4; i++) { kf[hd][1][i] = kp[6 * hd + 2 * i]; kf[hd][2][i] = kp[6 * hd + 2 * i + 1]; }
                ldsm4t(va + hd * 48, vf[hd][0]); ldsm4t(va + hd * 48 + 32, vf[hd][1]);
                ldsm4t(ka + (OFF_V - OFF_K) + warp * 896 + hd * 48 + 1792, vf[hd][2]);
            }
            const uint32_t q0l = tq < 2 ? qp[6] : 0, q0h = tq < 2 ? qp[7] : 0, q1l = tq < 2 ? 0 : qp[6], q1h = tq < 2 ? 0 : qp[7];
            const uint32_t mk = (up0 ? 0xFFFFu : 0u) | (up1 ? 0xFFFF0000u : 0u);
            g1_run(wg ? PRE1 : PRE0, ATT_STEP);
#pragma unroll
            for (int i = 0; i < 4; i++) {
                rk[i >> 1][i & 1] = ((i & 1) ? up1 : up0) ? rs[i >> 1][i & 1] : rs[(i >> 1) + 1][i & 1];
                fs[i >> 1][i & 1] = rk[i >> 1][i & 1] * (rq[i >> 1] * (0.18898223650461362f * 1.4426950408889634f));
                asm volatile("" : "+f"(fs[i >> 1][i & 1])::"memory");
            }
            uint32_t zr[4] = {0, 0, 0, 0}, oa[4];
#pragma unroll
            for (int i = 0; i < 4; i++) {
                if (MX & 8) zr[i] = (lane + i) * (sb >> 31);
                oa[i] = xa[i] + OFF_OST;
            }
            if (MX & 4) {
                uint32_t dep = q0l | q0h | q1l | q1h | mk;
#pragma unroll
                for (int i = 0; i < 4; i++) dep |= __float_as_uint(fs[i >> 1][i & 1]) | oa[i] | zr[i];
                asm volatile("{\n.reg .pred p;\nsetp.ne.u32 p, %0, 0;\n@p trap;\n}" ::"r"(dep & (sb >> 31)) : "memory");
            }
            drain();
            if (MX & 16) sched_fence();
            bar_sync<1, 256>();
            TS0(19);
            float sc[2][3][4];
#pragma unroll
            for (int u = 0; u < 3; u++) {
#pragma unroll
                for (int i = 0; i < 8; i++) sc[i >> 2][u][i & 3] = 0.f;
                mma16816(sc[0][u], qp[0], qp[1], qp[2], qp[3], kf[0][u][0], kf[0][u][1]);
                mma16816(sc[1][u], q1l, q1h, qp[8], qp[9], kf[1][u][0], kf[1][u][1]);
            }
#pragma unroll
            for (int u = 0; u < 3; u++) {
                mma16816(sc[0][u], qp[4], qp[5], q0l, q0h, kf[0][u][2], kf[0][u][3]);
                mma16816(sc[1][u], qp[10], qp[11], qp[12], qp[13], kf[1][u][2], kf[1][u][3]);
            }
            float e[2][2][2], mx[2][2], sm[2][4];
#pragma unroll
            for (int hd = 0; hd < 2; hd++) {
                e[hd][0][0] = (up0 ? sc[hd][0][0] : sc[hd][1][0]) * fs[0][0];
                e[hd][0][1] = (up1 ? sc[hd][0][1] : sc[hd][1][1]) * fs[0][1];
                e[hd][1][0] = (up0 ? sc[hd][1][2] : sc[hd][2][2]) * fs[1][0];
                e[hd][1][1] = (up1 ? sc[hd][1][3] : sc[hd][2][3]) * fs[1][1];
                if (edge && up0) e[hd][0][0] = -1e30f;
                if (edge && up1) e[hd][0][1] = -1e30f;
                mx[hd][0] = fmaxf(e[hd][0][0], e[hd][0][1]);
                mx[hd][1] = fmaxf(e[hd][1][0], e[hd][1][1]);
            }
#pragma unroll
            for (int o = 1; o <= 2; o <<= 1)
#pragma unroll
                for (int i = 0; i < 4; i++) mx[i >> 1][i & 1] = fmaxf(mx[i >> 1][i & 1], __shfl_xor_sync(0xffffffffu, mx[i >> 1][i & 1], o));
            uint32_t pp[2][2], pu[2][2];
#pragma unroll
            for (int i = 0; i < 4; i++) {
                const float p0 = ex2(e[i >> 1][i & 1][0] - mx[i >> 1][i & 1]), p1 = ex2(e[i >> 1][i & 1][1] - mx[i >> 1][i & 1]);
                pp[i >> 1][i & 1] = pack2(p0 * rk[i & 1][0], p1 * rk[i & 1][1]);
                pu[i >> 1][i & 1] = pack2(p0, p1);
            }
            float ov[2][4][4];
#pragma unroll
            for (int hd = 0; hd < 2; hd++)
#pragma unroll
                for (int n = 0; n < 4; n++) {
                    ov[hd][n][0] = ov[hd][n][1] = ov[hd][n][2] = ov[hd][n][3] = 0.f;
                    mma16816(ov[hd][n], pp[hd][0] & mk, zr[hd], pp[hd][0] & ~mk, pp[hd][1] & mk, vf[hd][n >> 1][2 * (n & 1)], vf[hd][n >> 1][2 * (n & 1) + 1]);
                }
#pragma unroll
            for (int hd = 0; hd < 2; hd++) {
                sm[hd][0] = sm[hd][1] = sm[hd][2] = sm[hd][3] = 0.f;
                mma1688(sm[hd], pu[hd][0], pu[hd][1], 0x3F803F80u);
            }
#pragma unroll
            for (int hd = 0; hd < 2; hd++)
#pragma unroll
                for (int n = 0; n < 4; n++) mma1688(ov[hd][n], zr[2 + hd], pp[hd][1] & ~mk, vf[hd][2][n]);
            TS0(18);
            uint32_t op[16];
            op[14] = op[15] = tag & 0x3FFF;
#pragma unroll
            for (int i = 0; i < 4; i++) sm[i >> 1][i & 1] = rcp(sm[i >> 1][2 * (i & 1)]);
#pragma unroll
            for (int n = 0; n < 7; n++) {
                const bool hb = n > 3 || (n == 3 && tq >= 2);
#pragma unroll
                for (int h = 0; h < 2; h++) {
                    const float r = hb ? sm[1][h] : sm[0][h];
                    const float x0 = hb ? ov[1][n >= 3 ? n - 3 : 0][2 * h] : ov[0][n <= 3 ? n : 0][2 * h];
                    const float x1 = hb ? ov[1][n >= 3 ? n - 3 : 0][2 * h + 1] : ov[0][n <= 3 ? n : 0][2 * h + 1];
                    op[2 * n + h] = pack2(x0 * r, x1 * r);
                }
            }
#pragma unroll
            for (int n = 0; n < 4; n++) stsm4(oa[n], op[4 * n], op[4 * n + 1], op[4 * n + 2], op[4 * n + 3]);
            __syncwarp();
            uint32_t seen = 0;
            if (OW & 4) asm volatile("ld.shared.b32 %0, [%1];" : "=r"(seen) : "r"(sb + OFF_OST) : "memory");
            mbar_arrive_if0(bar + 8 * B_OST, lane | (seen & (sb >> 31)));
            if (OW & 1) mbar_wait(bar + 8 * B_OST, 0);
            else bar_sync<1, 256>();
            TSW(5);
        }
        const uint32_t peer = z ^ 1;
        g1_run(ATT_STEP, wg ? GS : 16, true);
        gate_open(wg | !g1);
        drain();
#pragma unroll 1
        for (uint32_t r = g1 && wg ? GS : 16; r < 16; r++) {
            gate_wait(r == GS);
            g1_step(GS < 12 ? slot(r) : r - 12, 1);
        }
        drain();
        pin(a1);
        TSW(6);
        float hh[28];
        if (!(MX & 1)) {
            send_half(a1, mapa(sb + OFF_RECV1 + wg * 7168, peer), mapa(bar + 8 * (B_RECV1 + wg), peer), t, g1);
#pragma unroll
            for (int i = 0; i < 28; i++) hh[i] = fmaf(a1[i], 0.5f, hb1[(i >> 1) & 1]);
            pin(hh);
        }
        if (g1) {
            uint32_t nil = 0;
            if (MX & 1) {
                send_half(a1, mapa(sb + OFF_RECV1 + wg * 7168, peer), mapa(bar + 8 * (B_RECV1 + wg), peer), t, 1);
                nil = clock32() & (sb >> 31);
#pragma unroll
                for (int i = 0; i < 28; i++) hh[i] = fmaf(a1[i], __uint_as_float(0x3F000000u | nil), hb1[(i >> 1) & 1]);
                pin(hh);
            }
            uint32_t p[14];
            uint8_t* ub = scr + G_BIMG + ((8 + 2 * q + wg) * 4 + j) * BLK + w4 * 256 + (lane | nil) * 4;
            uint8_t *u0 = ub + (q < 7 ? 7 : 13) * z * 1024, *u1 = ub + (q < 7 ? 7 : 1) * z * 1024, *u2 = u1 + (q < 7 || z ? 0 : 6144);
            uint32_t any = 0;
#pragma unroll
            for (int i = 0; i < 0; i++) any |= __float_as_uint(hh[i]);
            const uint32_t ord = (uint32_t)(((uint64_t)u0 | (uint64_t)u1 | (uint64_t)u2) >> 63);
            mbar_wait(bar + 8 * (B_RECV1 + wg), OU & 4 ? __any_sync(0xffffffffu, ord) : ord);
            TSW(8);
            recv_half(p, sb + OFF_RECV1 + wg * 7168, t);
            float y[28];
            const float half = __uint_as_float(0x3F000000u | (GL ? (p[0] | p[4] | p[8] | p[12]) & (sb >> 31) : 0));
            auto pre = [&](int lo, int hi) {
#pragma unroll
                for (int i = lo; i < hi; i++) {
                    hh[i] = fmaf((i & 1) ? bf_hi(p[i >> 1]) : bf_lo(p[i >> 1]), i < GL ? half : 0.5f, hh[i]);
                    y[i] = hh[i] * fmaf(hh[i] * hh[i], 8.f * 0.0356774081363f, 2.f * 0.7978845608029f);
                }
            };
            auto th = [&](int lo, int hi) {
#pragma unroll
                for (int i = lo; i < hi; i++) asm volatile("tanh.approx.f32 %0, %0;" : "+f"(y[i]));
            };
            auto post = [&](int lo, int hi) {
#pragma unroll
                for (int i = lo / 2; i < hi / 2; i++)
                    stg32((i < 2 ? u0 : i < 4 ? u1 : u2) + (i >> 1) * 1024 + (i & 1) * 128, pack2(fmaf(hh[2 * i], y[2 * i], hh[2 * i]), fmaf(hh[2 * i + 1], y[2 * i + 1], hh[2 * i + 1])));
            };
            auto postp = [&](int lo, int hi, float tok) {
#pragma unroll
                for (int i = lo / 2; i < hi / 2; i++) {
                    asm("{\n.reg .pred p;\nsetp.eq.u32 p, %4, 0;\n@p fma.rn.f32 %0, %2, %0, %2;\n@p fma.rn.f32 %1, %3, %1, %3;\n}"
                        : "+f"(y[2 * i]), "+f"(y[2 * i + 1]) : "f"(hh[2 * i]), "f"(hh[2 * i + 1]), "r"(__float_as_uint(tok) & (sb >> 31)));
                    stg32((i < 2 ? u0 : i < 4 ? u1 : u2) + (i >> 1) * 1024 + (i & 1) * 128, pack2(y[2 * i], y[2 * i + 1]));
                }
            };
            if (GX == 1) { pre(0, 28); th(0, 28); post(0, 28); }
            if (GX == 2) { pre(0, 28); const float k = y[27]; th(0, 28); postp(0, 28, k); }
            if (GX == 3) { pre(0, 28); const float k = y[19]; th(0, 28); postp(0, 28, k); }
            if (GX == 4) { pre(0, 28); float k[28]; for (int i = 0; i < 28; i++) k[i] = y[i]; th(0, 28);
#pragma unroll
                for (int i = 0; i < 28; i += 4) postp(i, i + 4, k[min(i + 9, 27)]); }
            if (GX == 5) { pre(0, 28); float k[28]; for (int i = 0; i < 28; i++) k[i] = y[i]; th(0, 28); postp(0, 8, k[15]); postp(8, 28, k[27]); }
            if (GX == 6) {
#pragma unroll
                for (int i = 0; i < 36; i += 4) { float k = y[27]; if (i < 28) { pre(i, i + 4); k = y[i + 3]; th(i, i + 4); } if (i >= 8) postp(i - 8, i - 4, i < 28 ? k : 0.f); }
            }
            TSW(9);
        }
        float a2[56];
        if (OU & 1) __syncwarp();
#pragma unroll 1
        for (uint32_t i = 0; i < 4; i++) {
            const uint32_t s = ((SI == 2 ? (g1 ? 0x0654u : 0x2610u) : (g1 ? 0x0564u : 0x2160u)) >> (4 * i)) & 7, da = dA + (aoff(s) >> 4), db = dU + (i == SI ? (OFF_SB - OFF_B) >> 4 : s * 896);
            mbar_wait(bar + 8 * (B_FULL + s), g1 && i == 3);
            TSD(64 + 17 + i);
            wg_fence();
#pragma unroll
            for (int k = 0; k < 4; k++) wgmma_n112<0, H_SW, H_U>(a2, da + k * 2, db + k * 16, k ? 1 : i);
            wg_commit();
            wg_wait<1>();
            release(rel);
            rel = bar + 8 * (B_EMPTY + s);
        }
        drain();
        TSW(10);
#pragma unroll 1
        for (uint32_t r = r_u; r < r_u + 14 - (BU && wg ? NS2 : 0); r++) {
            const uint32_t s = slot(r);
            if (!BU) gate_wait(wg && r == r_u + 14 - NS2);
            mbar_wait(bar + 8 * (B_FULL + s), phase(r));
            TSD(85 + r - r_u);
            wg_fence();
#pragma unroll
            for (int k = 0; k < 4; k++) wgmma_n112<1, H_SW, H_U>(a2, dA + s * 1024 + k * 128, dU + s * 896 + k * 16);
            wg_commit();
            wg_wait<1>();
            release(rel);
            rel = bar + 8 * (B_EMPTY + s);
        }
        if (BU) {
            uint32_t late = wg;
            asm volatile("" : "+r"(late));
            late = __shfl_sync(0xffffffffu, late, 0);
            const uint32_t s = slot(r_u + 14 - NS2);
            gate_open(wg);
            mbar_wait(bar + 8 * B_UDONE, 0);
            if (BU == 1) gate_wait(wg);
            if (BU < 3) {
#pragma unroll 1
            for (uint32_t n = 0; n < late; n++) {
                if (BU == 2) bar_sync<4, 256>();
                wg_fence();
#pragma unroll
                for (int k = 0; k < 4 * NS2; k++) wgmma_n112<1, H_SW, H_U>(a2, dA + (s + k / 4) * 1024 + k % 4 * 128, dU + (s + k / 4) * 896 + k % 4 * 16);
                wg_commit();
            }
            } else {
#pragma unroll 1
            for (uint32_t n = s; n < s + wg * NS2; n++) {
                gate_wait(n == s);
                wg_fence();
#pragma unroll
                for (int k = 0; k < 4; k++) wgmma_n112<1, H_SW, H_U>(a2, dA + n * 1024 + k * 128, dU + n * 896 + k * 16);
                wg_commit();
            }
            }
        } else gate_open(wg);
        {
            uint32_t ln = lane | (EXP & 2 ? clock32() & (sb >> 31) : 0);
            const uint32_t un = warp * 2048 + (ln ^ ((ln >> 3) & 1)) * 16;
            const uint32_t rbuf = mapa(sb + OFF_RECV2, peer), rbar = mapa(bar + 8 * (B_RECV2 + wg), peer);
            uint32_t xr[4][4], u[4][4], sa[4], la, lb, lx;
            uint8_t *o0, *o1;
#pragma unroll
            for (int i = 0; i < 4; i++) sa[i] = rbuf + (un ^ (i & 1) * 32) + i * 512;
            auto addr = [&]() {
                la = sb + warp * 2048 + (ln & 1) * 512 + (ln & 6) * 32 + (((ln >> 3) ^ (ln >> 2 & 1) ^ (ln << 1)) & 3) * 16;
                lb = la - (z & ~ln) * 1024;
                lx = sb + OFF_A + slot(r_u + 14) * 16384 + (warp * 16 + (ln >> 3)) * 128 + (((ln ^ (ln >> 3)) & 7) << 4);
                o1 = out + ((q * 128 + warp * 16 + (ln >> 3)) * 896 + j * 224 + z * 96 + (ln & 7) * 16);
                o0 = o1 + (ln & 2 ? -32 : 32);
            };
            if (EXP & 1) addr();
            if (EXP & 2) asm volatile("{\n.reg .pred p;\nsetp.lt.s32 p, %0, 0;\n@p trap;\n}" ::"r"(sa[0] | sa[1] | sa[2] | sa[3] | rbar | (EXP & 1 ? lb | lx | (uint32_t)((uint64_t)o0 >> 32) : 0)) : "memory");
            wg_wait<0>();
            pin(a2);
            TSW(11);
            auto word = [&](int n, int h) { return pack2(a2[4 * n + 2 * h], a2[4 * n + 2 * h + 1]); };
            send4(sa[1], rbar, word(12, 0), word(13, 0), word(10, 0), word(11, 0), 1);
            send4(sa[3], rbar, word(10, 1), word(11, 1), word(12, 1), word(13, 1), 1);
            send4(sa[0], rbar, word(8, 0), word(9, 0), z ? word(0, 0) : word(8, 1), z ? word(1, 0) : word(9, 1), 1);
            send4(sa[2], rbar, word(0, 1), word(1, 1), word(8, 1), word(9, 1), z);
            const uint32_t nil = clock32() & (sb >> 31);
            const float one = __uint_as_float(0x3F800000u | nil);
#pragma unroll
            for (int i = 0; i < 32; i++) a2[i] = fmaf(a2[i], one, fb2[(i >> 1) & 1]);
#pragma unroll
            for (int i = 0; i < 4; i++) {
                const int n = i % 2 * 4 + (~i & 2), h = i / 2;
                asm volatile("st.shared.v4.b32 [%0], {%1,%2,%3,%4};" ::"r"(sb + OFF_OUT + (un ^ (i & 1) * 32) + i * 512), "r"(word(n, h)), "r"(word(n + 1, h)),
                             "r"(word(n ^ 2, h)), "r"(word(n ^ 3, h)) : "memory");
            }
            if (!(EXP & 1)) { ln |= nil; addr(); }
            auto add_x = [&]() {
#pragma unroll
                for (int i = 0; i < 16; i++) asm("add.rn.bf16x2 %0, %0, %1;" : "+r"(u[i >> 2][i & 3]) : "r"(xr[i >> 2][i & 3]));
            };
            __syncwarp();
#pragma unroll
            for (int i = 0; i < 4; i++) ldsm4(la + OFF_OUT + i / 2 * 1024 + i % 2 * 256, u[i]);
            mbar_wait(bar + 8 * B_XR, 0);
#pragma unroll
            for (int i = 0; i < 4; i++)
                asm volatile("ld.shared.v4.b32 {%0,%1,%2,%3}, [%4];" : "=r"(xr[i][0]), "=r"(xr[i][1]), "=r"(xr[i][2]), "=r"(xr[i][3])
                             : "r"((lx ^ (i % 2 * 64 + (~i & 2) * 16)) + i * 512) : "memory");
            add_x();
            mbar_wait(bar + 8 * (B_RECV2 + wg), (lb | (uint32_t)((uint64_t)o0 >> 32)) >> 31);
            TSW(12);
#pragma unroll
            for (int i = 0; i < 4; i++) ldsm4((i < 2 ? la : lb) + OFF_RECV2 + i / 2 * 1024 + i % 2 * 256, xr[i]);
            add_x();
#pragma unroll
            for (int i = 0; i < 4; i++)
                asm volatile("{\n.reg .pred p;\nsetp.ge.u32 p, %5, %6;\n@p st.global.v4.b32 [%0], {%1,%2,%3,%4};\n}"
                             ::"l"((i < 2 ? o0 : o1) + i * 3584), "r"(u[i][0]), "r"(u[i][1]), "r"(u[i][2]), "r"(u[i][3]), "r"((lane & 6) ^ (~i & 2)), "r"(z) : "memory");
        }
        TSW(13);
    } else if (warp < 12) {
        asm volatile("setmaxnreg.dec.sync.aligned.u32 64;");
        const int hw = warp - 8, t = tid & 127;
        reinterpret_cast<uint32_t*>(smem + OFF_ONES)[t] = t < 64 ? 0x3F803F80u : 0;
        fence_async_smem();
        bar_sync<12, 128>();
        while (clock32() - t_in < DLY1) {}
        uint8_t* cscell = scr + G_CS + ((P * 8 + R) * 2 + z) * 512 + (t >> 2) * 16;
        if ((lane & 3) == 0) cell_put(cscell, 0, 0, 0);
        uint8_t* cells = scr + G_HALO + ((R * 8 + P) * 2 + z) * 3584 + min(t, 111) * 16;
        cell_put(cells, 0, 0, 0);
        cell_put(cells + 1792, 0, 0, 0);
        const unsigned e1 = epoch();
        const uint32_t bv1 = ldg_u16(b1 + (g1 ? q * 128 : 0) + t), bv2 = ldg_u16(b2 + q * 128 + t);
        {
            const uint32_t da = desc_lo(OFF_B + min((R & 1) * 2 + z, 2) * 4096, 16), db = desc_lo(OFF_ONES, 128);
            float c0[4];
            const int st = R & 6 & ~ROT;
            mbar_wait(bar + 8 * (B_FULLQ + st), 0);
            mbar_wait(bar + 8 * (B_FULLQ + st + 1), 0);
            TSH(47);
            wg_fence();
#pragma unroll
            for (int k = 0; k < 8; k++)
                wgmma_n8<1, H_SW, H_H>(c0, da + ((WSLOT >> (4 * st + (k & 4))) & 7) * 1536 + (k & 2) * 384 + (k & 1) * 128, db + (k >= 4 && R >= 6 ? 16 : 0), k);
            wg_commit();
            wg_wait<0>();
            pin(c0);
            if ((lane & 3) == 0) cell_put(cscell, __float_as_uint(c0[0]), __float_as_uint(c0[2]), e1);
            if (lane < 4) asm volatile("mbarrier.arrive.shared::cluster.b64 _, [%0];" ::"r"(mapa(bar + 8 * (B_EMPTYQ + st + (lane >> 1)), lane & 1)) : "memory");
            TSH(43);
        }
        mbar_wait(bar + 8 * (B_FULLQ + GATHER), 0);
        TSH(39);
        {
            const bool cw = hw < 3;
            const uint8_t* src = cw ? scr + G_CS + P * 8192 + t * 16 : scr + G_STATS + (z * 1024 + R * 128 + lane) * 16;
            uint32_t a[5], d[5], bad;
            do {
                bad = 0;
#pragma unroll
                for (int i = 0; i < 4; i++) bad |= cell_get(src + i * (cw ? 2048 : 512), a[i], d[i], e1);
                if (t >= 120) bad |= cell_get(src - (R ? 512 : 0), a[4], d[4], e1);
            } while (bad);
            TSH(45);
            if (cw) {
                uint4* cb = reinterpret_cast<uint4*>(smem + OFF_CSB) + (t >> 3) * 16 + (t & 7);
                const uint32_t lo = split2((__uint_as_float(a[0]) + __uint_as_float(a[1])) + (__uint_as_float(a[2]) + __uint_as_float(a[3])));
                const uint32_t hi = split2((__uint_as_float(d[0]) + __uint_as_float(d[1])) + (__uint_as_float(d[2]) + __uint_as_float(d[3])));
                cb[0] = make_uint4(lo, lo, 0, 0);
                cb[8] = make_uint4(hi, hi, 0, 0);
            } else {
                uint2* st = reinterpret_cast<uint2*>(smem + OFF_STATS) + lane;
                uint32_t* rd = reinterpret_cast<uint32_t*>(smem + OFF_RSTD) + lane;
#pragma unroll
                for (int i = 0; i < 4; i++) { st[32 * i] = make_uint2(a[i], d[i]); rd[8 + 32 * i] = a[i]; }
                if (t >= 120) rd[-24] = a[4];
            }
            fence_async_smem();
            __syncwarp();
            mbar_arrive_if0(bar + 8 * B_AUX, lane);
            TSH(41);
            reinterpret_cast<float2*>(smem + OFF_BIAS)[t] = make_float2(0.5f * bf_lo(bv1), bf_lo(bv2));
            __syncwarp();
            mbar_arrive_if0(bar + 8 * B_KV, lane);
        }
        {
            uint2* kv = reinterpret_cast<uint2*>(smem + OFF_K) + min(t, 111);
            mbar_wait(bar + 8 * B_QKV, 0);
            uint2 k2 = kv[896], v2 = kv[1792 + (OFF_V - OFF_K) / 8];
            cell_put(cells, k2.x, k2.y, e1);
            cell_put(cells + 1792, v2.x, v2.y, e1);
            k2 = v2 = make_uint2(0, 0);
            if (DH) delay(DH);
            if (R > 0) while (cell_get(cells - 16 * 3584, k2.x, k2.y, e1) | cell_get(cells - 16 * 3584 + 1792, v2.x, v2.y, e1)) {}
            kv[0] = k2;
            kv[(OFF_V - OFF_K) / 8] = v2;
            mbar_wait(bar + 8 * B_KV, 0);
            __syncwarp();
            mbar_arrive_if0(bar + 8 * B_HALO, lane);
            TSH(40);
        }
        if (hw == 3) {
            mbar_wait(bar + 8 * B_OST, 0);
            if (elect()) {
                unsigned* oc = ctr + C_O + (R * 2 + (P >> 2)) * 32;
                TS(38);
                fence_async_smem();
                TS(46);
                tma2d_store(&mp.ost, sb + OFF_OST, z * 64, P * 1024 + R * 128);
                bulk_commit();
                TS(7);
                asm volatile("mbarrier.arrive.relaxed.cluster.shared::cluster.b64 _, [%0];" ::"r"(mapa(bar + 8 * B_FREE, z ^ 1)) : "memory");
                if (DO) delay(DO);
                red_relaxed(oc, 1);
                TS(21);
                mbar_wait(bar + 8 * B_LNIN, 0);
                bulk_wait_read();
                mbar_arrive(bar + 8 * B_LNFREE);
                TS(20);
                mbar_wait(bar + 8 * (B_EMPTY + 6), 0);
                asm volatile("mbarrier.arrive.relaxed.cluster.shared::cluster.b64 _, [%0];" ::"r"(mapa(bar + 8 * B_UDONE, z ^ 1)) : "memory");
            }
        } else {
            const uint32_t tag = e1 & 0x3FFF;
            const uint32_t ca = sb + OFF_A + lane * 128 + ((~lane & 7) << 4) + (lane >> 3) * 4, cb = sb + OFF_B + lane * 132;
            uint32_t par = 0x7F;
#pragma unroll 1
            for (uint32_t i = SI == 2 || !hw ? hw : 3 - hw; i < 18;) {
                const uint32_t s = xslot(i);
                const bool isa = i < 4;
                const uint32_t a0 = isa ? ca + aoff(s) : cb + s * BLK, a3 = a0 - (isa ? 0 : (lane & 16) * 132);
                mbar_wait(bar + 8 * (B_LAND + s), (par >> s) & 1);
                par ^= 1 << s;
                bool ok = true;
#pragma unroll
                for (int k = 0; k < 4; k++) {
                    uint32_t v;
                    asm volatile("ld.shared.b32 %0, [%1];" : "=r"(v) : "r"((k < 3 ? a0 : a3) + k * 4096) : "memory");
                    ok &= (v == (isa ? tag : ~0u)) == isa;
                }
                if (__all_sync(0xffffffffu, ok)) {
                    mbar_arrive_if0(bar + 8 * (B_FULL + s), lane);
                    if (i == 0 || i == 4) TS(i ? 30 : 29);
                    i += i < SI ? 4 : i == SI ? 3 - SI : 3;
                } else if (elect()) {
                    TS(31);
                    fetch_x(i);
                }
            }
        }
    } else {
        asm volatile("setmaxnreg.dec.sync.aligned.u32 32;");
        auto wait_free = [&](uint32_t r, uint32_t first) {
            const uint32_t a = r < 6 ? B_EMPTYQ + ((first >> (4 * r)) & 7) : B_EMPTY + slot(r);
            mbar_wait(bar + 8 * a, r < 6 ? 0 : phase(r) ^ 1);
        };
        if (warp == 12) {
            TS(14);
            if (elect()) {
#pragma unroll 1
                for (int kb = 1; kb < 7; kb++) {
                    if (kb == 1) while (clock32() - t_in < DLY2) {}
                    if (kb >= QDEPTH) { mbar_wait(bar + 8 * (B_FULLQ + kb - QDEPTH), 0); TS(25 + kb - QDEPTH); }
                    if (kb >= 5) mbar_wait(bar + 8 * (B_EMPTYQ + kb - 5), 0);
                    x_load(kb);
                    w_load(kb);
                }
                TS(17);
                mbar_wait(bar + 8 * B_LNFREE, 0);
                if (!g1) {
                    const int ic = (q - 14) * 8 + j * 2 + z, rot = ic >> 3;
                    mbar_wait(bar + 8 * (B_EMPTYQ + 2), 0);
                    mbar_expect(bar + 8 * B_GO, 2 * BLK);
#pragma unroll 1
                    for (int i = 0; i < 2; i++) tma4d(sb + OFF_A + i * BLK, &mp.wo, 0, 0, (z * 2 + i) * 14, ic >> 1, bar + 8 * B_GO);
                    mbar_wait(bar + 8 * B_GO, 0);
#pragma unroll 1
                    for (int i = 0; i < 2; i++) {
                        uint8_t* dst = scr + G_BIMG + (ic * 2 + i) * BLK;
                        bulk_store(dst, sb + OFF_A + i * BLK, 2048);
                        bulk_store(dst + 2048 + rot * 6144, sb + OFF_A + i * BLK + 2048, 6144);
                        bulk_store(dst + 8192 - rot * 6144, sb + OFF_A + i * BLK + 8192, 6144);
                    }
                    bulk_commit();
                    bulk_wait_all();
                    publish(ctr + C_WO);
                    TS(44);
                }
#pragma unroll 1
                for (uint32_t r = 0; r < r_o; r++) {
                    const uint32_t s = slot(r), fb = bar + 8 * (B_FULL + s);
                    wait_free(r, 0x654320u);
                    mbar_expect(fb, 16384);
                    tma3d(sb + OFF_A + s * 16384, &mp.w1, 0, z * 1024 + r * 64, 2 * q, fb);
                    TS(99 + r);
                }
                mbar_wait(bar + 8 * B_OST, 0);
                mbar_expect(bar + 8 * (B_LAND + 6), 16384);
#pragma unroll 1
                for (uint32_t i = 0; i < SI; i++) {
                    wait_free(r_o + i, 0x654320u);
                    mbar_expect(bar + 8 * (B_LAND + slot(r_o + i)), 16384);
                }
                poll(ctr + C_O + ((q & ~1) + z) * 32, epoch() * 8);
                TS(32);
                fetch_x(0, false);
                if (SI == 2) fetch_x(1, false);
                mbar_wait(bar + 8 * B_LNFREE, 1);
                fetch_x(SI, false);
                TS(99 + 17);
#pragma unroll 1
                for (uint32_t i = SI; i < 3; i++) {
                    wait_free(r_o + i, 0x654320u);
                    fetch_x(i + 1);
                }
                TS(99 + 20);
#pragma unroll 1
                for (uint32_t i = 0; i < 14; i++) {
                    const uint32_t r = r_u + i, s = slot(r), fb = bar + 8 * (B_FULL + s);
                    wait_free(r, 0x654320u);
                    mbar_expect(fb, 16384);
                    tma3d(sb + OFF_A + s * 16384, &mp.w2, 0, (14 * z + (i < 7 ? 2 * i : 2 * i - 13)) * 64, 2 * q, fb);
                    TS(99 + 21 + i);
                }
                wait_free(r_u + 14, 0);
                mbar_expect(bar + 8 * B_XR, 16384);
                tma2d(sb + OFF_A + slot(r_u + 14) * 16384, &mp.xn, j * 112 + z * 48, q * 128, bar + 8 * B_XR);
            }
        } else if (warp == 13) {
            if (elect()) {
#pragma unroll 1
                for (int ph = g1 ? 0 : 1; ph < 4; ph++) {
                    const uint8_t* src = ph == 0 ? scr + G_HIMG + (64 * z + j) * BLK : scr + G_BIMG + ((ph == 1 ? 4 * z : 6 + 14 * z + ph) * 4 + j) * BLK;
                    const uint32_t r0 = ph == 0 ? 0 : r_o + (ph == 1 ? 0 : 7 * ph - 11), r1 = r_o + (ph == 0 ? 0 : 7 * ph - 4);
                    if (ph == 1) {
                        mbar_wait(bar + 8 * (SPW == 0 && g1 ? B_LNIN : SPW < 2 ? B_OST : B_LNFREE), SPW == 2);
                        mbar_expect(bar + 8 * (B_FULL + 6), BLK);
                        mbar_wait(bar + 8 * (B_GO + 1), 0);
                        bulk_load(sb + OFF_SB, src + 4 * SI * BLK, BLK, bar + 8 * (B_FULL + 6));
                    }
#pragma unroll 1
                    for (uint32_t r = r0; r < r1; r++, src += r <= r_o || r == r_o + 3 - SI ? 4 * BLK : 8 * BLK) {
                        const uint32_t s = slot(r), fb = bar + 8 * ((ph < 2 ? B_FULL : B_LAND) + s);
                        wait_free(r, 0x644332u);
                        mbar_expect(fb, BLK);
                        mbar_wait(bar + 8 * (B_GO + ph), 0);
                        bulk_load(sb + OFF_B + s * BLK, src, BLK, fb);
                        TS(134 + 16 + 2 * (ph > 0) + r - r_o);
                    }
                }
            }
        } else if (warp == 14) {
            uint8_t* stcell = scr + G_STATS + ((lane & 1) * 1024 + 8 * b + (lane >> 1)) * 16;
            if (lane < 16) cell_put(stcell, 0, 0, 0);
            const unsigned ev = ld_relaxed(ctr + C_LN);
            uint8_t* hb = scr + G_HIMG + (b & ~3) * BLK;
            const unsigned e1 = (ev >> 7) + 1;
            if (lane == 0) {
                *reinterpret_cast<volatile unsigned*>(smem + OFF_EP) = e1;
                mbar_arrive(bar + 8 * B_EP);
                TS(36);
            }
            bar_sync<10, 288>();
            if (elect()) {
                fence_async_smem();
                TS(42);
                tma4d_store(&mp.hst, sb + OFF_A, 0, 0, b & 3, b & ~3);
                bulk_commit();
            }
            __syncwarp();
            if (lane < 16) {
                const uint2 v = reinterpret_cast<const uint2*>(smem + OFF_LNST)[lane];
                cell_put(stcell, v.x, v.y, e1);
            }
            bulk_wait_all();
            __syncwarp();
            TS(63);
            unsigned rb = 0;
#pragma unroll
            for (int i = 0; i < 4; i++) rb |= ld_relaxed(reinterpret_cast<const unsigned*>(hb + i * BLK + ((b & 3) * 28 + min(lane, 27)) * 128));
            if (lane == 0) {
                mbar_arrive(bar + 8 * B_LNFREE);
                red_relaxed(ctr + C_LN, 1 + (rb & (sb >> 31)));
                TS(37);
#pragma unroll 1
                for (int ph = g1 ? 0 : 1; ph < 4; ph++) {
                    if (ph) mbar_wait(bar + 8 * (ph == 1 ? B_HALO : g1 ? B_RECV1 : B_OST), 0);
                    poll(ctr + ph * 32 + (ph >> 1) * z * 64, e1 * (ph == 0 ? 128 : ph == 1 ? 16 : 56));
                    fence_async_global();
                    mbar_arrive(bar + 8 * (B_GO + ph));
                    if (ph != 1) TS(ph == 0 ? 33 : 32 + ph);
                }
            }
        } else {
            if ((sb & 0x3FFFF) != SB0) __trap();
            if (elect()) {
#pragma unroll 1
                for (int i = 3; i < 10; i++) asm volatile("prefetch.tensormap [%0];" ::"l"(reinterpret_cast<const CUtensorMap*>(&mp) + i) : "memory");
            }
            __syncwarp();
            mbar_watch(bar + 8 * B_KV, 0);
#pragma unroll 1
            for (int i = g1 ? 0 : 8; i < 8; i++) {
                uint32_t l = 56 * z + (i & 3) * 14 + min(lane >> 1, 13);
                if (q >= 7 && l >= 16) l += l < 64 ? 48 : -48;
                cell_put(scr + G_BIMG + ((8 + 2 * q + (i >> 2)) * 4 + j) * BLK + l * 128 + (l & 24) * 4 + (lane & 1) * 16, ~0u, ~0u, ~0u);
            }
            __threadfence();
            __syncwarp();
            mbar_arrive_if0(bar + 8 * B_FREE, lane);
            TS(59);
#pragma unroll 1
            for (int i = g1 ? 0 : 2; i < 2; i++) {
                mbar_watch(bar + 8 * (B_RECV1 + i), 0);
                delay(DU);
                if (lane == 0) red_relaxed(ctr + C_U + ((q >= 7 ? 2 : 0) + i) * 32, 1);
                TS(22 + i);
            }
            mbar_watch(bar + 8 * B_FREE, 0);
            mbar_watch(bar + 8 * B_RECV2, 0);
            mbar_watch(bar + 8 * (B_RECV2 + 1), 0);
        }
    }
}

typedef CUresult (*EncodeFn)(CUtensorMap*, CUtensorMapDataType, cuuint32_t, void*, const cuuint64_t*, const cuuint64_t*, const cuuint32_t*,
                             const cuuint32_t*, CUtensorMapInterleave, CUtensorMapSwizzle, CUtensorMapL2promotion, CUtensorMapFloatOOBfill);

void encode(EncodeFn fn, CUtensorMap* m, const void* p, int rank, const cuuint64_t* dims, const cuuint64_t* strides, const cuuint32_t* box, bool swz) {
    const cuuint32_t es[4] = {1, 1, 1, 1};
    fn(m, CU_TENSOR_MAP_DATA_TYPE_BFLOAT16, rank, const_cast<void*>(p), dims, strides, box, es, CU_TENSOR_MAP_INTERLEAVE_NONE,
       swz ? CU_TENSOR_MAP_SWIZZLE_128B : CU_TENSOR_MAP_SWIZZLE_NONE, CU_TENSOR_MAP_L2_PROMOTION_L2_128B, CU_TENSOR_MAP_FLOAT_OOB_FILL_NONE);
}

}

extern "C" void kernel_launch(void* const* d_in, const int* in_sizes, int n_in, void* d_out, int out_size) {
    const __nv_bfloat16* x = (const __nv_bfloat16*)d_in[0];
    const __nv_bfloat16* wqkv = (const __nv_bfloat16*)d_in[1];
    const __nv_bfloat16* wo = (const __nv_bfloat16*)d_in[2];
    const __nv_bfloat16* w1 = (const __nv_bfloat16*)d_in[4];
    const __nv_bfloat16* b1 = (const __nv_bfloat16*)d_in[5];
    const __nv_bfloat16* w2 = (const __nv_bfloat16*)d_in[6];
    const __nv_bfloat16* b2 = (const __nv_bfloat16*)d_in[7];

    void* fp = nullptr;
    cudaDriverEntryPointQueryResult qr;
    cudaGetDriverEntryPoint("cuTensorMapEncodeTiled", &fp, cudaEnableDefault, &qr);
    EncodeFn fn = (EncodeFn)fp;
    void* sp = nullptr;
    cudaGetSymbolAddress(&sp, g_scratch);
    uint8_t* scr = (uint8_t*)sp;
    void *o = scr + G_O, *himg = scr + G_HIMG;

    Maps mp;
    { cuuint64_t d[3] = {64, 2048, 7}, s[2] = {896, 128}; cuuint32_t bx[3] = {64, 16, 7}; encode(fn, &mp.xl, x, 3, d, s, bx, true); }
    { cuuint64_t d[2] = {896, 1024}, s[1] = {1792}; cuuint32_t bx[2] = {64, 128}; encode(fn, &mp.x, x, 2, d, s, bx, true); }
    { cuuint64_t d[3] = {448, 448, 3}, s[2] = {2688, 896}; cuuint32_t bx[3] = {64, 32, 3}; encode(fn, &mp.wqkv, wqkv, 3, d, s, bx, true); }
    { cuuint64_t d[3] = {64, 2048, 28}, s[2] = {3584, 128}; cuuint32_t bx[3] = {64, 64, 2}; encode(fn, &mp.w1, w1, 3, d, s, bx, true); }
    { cuuint64_t d[3] = {64, 1792, 32}, s[2] = {4096, 128}; cuuint32_t bx[3] = {64, 64, 2}; encode(fn, &mp.w2, w2, 3, d, s, bx, true); }
    { cuuint64_t d[4] = {64, 28, 4, 128}, s[3] = {128, 3584, BLK}; cuuint32_t bx[4] = {64, 28, 1, 4}; encode(fn, &mp.hst, himg, 4, d, s, bx, false); }
    { cuuint64_t d[2] = {448, 2048}, s[1] = {896}; cuuint32_t bx[2] = {64, 128}; encode(fn, &mp.xn, x, 2, d, s, bx, true); }
    { cuuint64_t d[2] = {64, 8 * 2048}, s[1] = {128}; cuuint32_t bx[2] = {64, 128}; encode(fn, &mp.old_, o, 2, d, s, bx, true); }
    { cuuint64_t d[2] = {128, 8 * 1024}, s[1] = {256}; cuuint32_t bx[2] = {64, 128}; encode(fn, &mp.ost, o, 2, d, s, bx, true); }
    { cuuint64_t d[4] = {8, 56, 56, 8}, s[3] = {896, 16, 56 * 896}; cuuint32_t bx[4] = {8, 64, 14, 1}; encode(fn, &mp.wo, wo, 4, d, s, bx, false); }

    cudaFuncSetAttribute(fused_kernel, cudaFuncAttributeMaxDynamicSharedMemorySize, SMEM_BYTES);
    fused_kernel<<<128, 512, SMEM_BYTES>>>(x, b1, b2, scr, (uint8_t*)d_out, mp);
}
```

```cpp
#include <cuda_runtime.h>
#include <cuda.h>
#include <cuda_bf16.h>
#include <stdint.h>

namespace {

constexpr int S_ = 2048, D_ = 448;
constexpr uint32_t BLK = 14336;

constexpr uint32_t G_HIMG = 0;
constexpr uint32_t G_BIMG = G_HIMG + 32 * 4 * BLK;
constexpr uint32_t G_O = G_BIMG + 36 * 4 * BLK;
constexpr uint32_t G_STATS = G_O + 8 * S_ * 128;
constexpr uint32_t G_CS = G_STATS + S_ * 16;
constexpr uint32_t G_HALO = G_CS + 8 * 4 * 2048;
constexpr uint32_t G_CTR = G_HALO + 128 * 3584;
constexpr uint32_t G_END = G_CTR + (192 + 16 * 32) * 4;
__device__ __align__(1024) uint8_t g_scratch[G_END];

constexpr int C_LN = 0, C_WO = 32, C_U = 64, C_O = 192;

#define TSX(sel, id)
#define TS(id)
#define TS0(id)
#define TSH(id)
#define TSW(id)
#define TG(id)

#define TSG1 0
#define TSD(id)
constexpr int QDEPTH = 3;
constexpr int KS = 3;
constexpr int GATHER = 4;
constexpr uint32_t NE = 2;
constexpr uint32_t PRE0 = 9, PRE1 = 6;
constexpr uint32_t ATT_STEP = 10, GS = 12;
constexpr int NS2 = 3;
constexpr uint32_t DLY1 = 2200, DLY2 = 1600, DH = 400, DO = 200, DU = 120;

constexpr uint32_t OFF_A = 0;
constexpr uint32_t OFF_B = 98304;
constexpr uint32_t OFF_X = 184320;
constexpr uint32_t OFF_K = 196608;
constexpr uint32_t OFF_V = OFF_K + 9 * 896;
constexpr uint32_t OFF_OST = OFF_X, OFF_RECV2 = OFF_X, OFF_RECV1 = OFF_X + 16384, OFF_OUT = OFF_X + 16384;
constexpr uint32_t OFF_SA = OFF_X, OFF_SB = OFF_RECV1 + BLK;
constexpr uint32_t OFF_CSB = 221184;
constexpr uint32_t OFF_ONES = OFF_CSB + 3072;
constexpr uint32_t OFF_STATS = OFF_ONES + 512;
constexpr uint32_t OFF_BIAS = OFF_STATS + 1024;
constexpr uint32_t OFF_LNX = OFF_BIAS + 1024;
constexpr uint32_t OFF_RSTD = OFF_LNX + 512;
constexpr uint32_t OFF_LNST = 229376;
constexpr uint32_t OFF_EP = OFF_LNST + 128;
constexpr uint32_t OFF_BAR = OFF_EP + 16;
constexpr uint32_t OFF_TS = OFF_BAR + 8 * 48;
constexpr uint32_t SMEM_BYTES = OFF_TS;

enum : int {
    B_FULLQ = 0, B_LNIN = 7, B_EMPTYQ = 8, B_FULL = 15, B_EMPTY = 22, B_AUX = 29, B_QKV, B_HALO, B_FREE, B_RECV1, B_RECV2 = B_RECV1 + 2,
    B_EP = B_RECV2 + 2, B_OST, B_LNFREE, B_UDONE, B_NONE, B_GO, B_XR = B_GO + 4, B_KV, B_COUNT, B_LAND = B_FULLQ
};
constexpr uint32_t XSLOT = 0x5432154u;
constexpr uint32_t WSLOT = 0x3421034u;

__device__ __forceinline__ uint32_t smem_u32(const void* p) { return (uint32_t)__cvta_generic_to_shared(p); }
__device__ __forceinline__ void mbar_init(uint32_t a, int c) { asm volatile("mbarrier.init.shared::cta.b64 [%0], %1;" ::"r"(a), "r"(c) : "memory"); }
__device__ __forceinline__ void mbar_expect(uint32_t a, uint32_t b) { asm volatile("mbarrier.arrive.expect_tx.shared::cta.b64 _, [%0], %1;" ::"r"(a), "r"(b) : "memory"); }
__device__ __forceinline__ void mbar_arrive(uint32_t a) { asm volatile("mbarrier.arrive.shared::cta.b64 _, [%0];" ::"r"(a) : "memory"); }
__device__ __forceinline__ void mbar_arrive_if0(uint32_t a, uint32_t sel) {
    asm volatile("{\n.reg .pred p;\nsetp.eq.u32 p, %1, 0;\n@p mbarrier.arrive.shared::cta.b64 _, [%0];\n}" ::"r"(a), "r"(sel) : "memory");
}
__device__ __forceinline__ void mbar_wait(uint32_t a, uint32_t parity) {
    asm volatile("{\n.reg .pred p;\nW0:\nmbarrier.try_wait.parity.shared::cta.b64 p, [%0], %1;\n@!p bra W0;\n}\n" ::"r"(a), "r"(parity) : "memory");
}
__device__ __forceinline__ void mbar_watch(uint32_t a, uint32_t parity) {
    asm volatile(
        "{\n.reg .pred p;\n.reg .u32 n;\nmov.u32 n, 0;\n"
        "W0:\nmbarrier.try_wait.parity.shared::cta.b64 p, [%0], %1;\n@p bra W1;\n"
        "add.u32 n, n, 1;\nsetp.lt.u32 p, n, 4194304;\n@p bra W0;\ntrap;\nW1:\n}\n" ::"r"(a), "r"(parity) : "memory");
}
__device__ __forceinline__ bool elect() {
    uint32_t r;
    asm volatile("{\n.reg .pred p;\nelect.sync _|p, 0xffffffff;\nselp.u32 %0, 1, 0, p;\n}" : "=r"(r));
    return r;
}
__device__ __forceinline__ uint32_t mapa(uint32_t a, uint32_t cta) { uint32_t r; asm("mapa.shared::cluster.u32 %0, %1, %2;" : "=r"(r) : "r"(a), "r"(cta)); return r; }
__device__ __forceinline__ void tma2d(uint32_t dst, const CUtensorMap* m, int c0, int c1, uint32_t bar) {
    asm volatile("cp.async.bulk.tensor.2d.shared::cluster.global.mbarrier::complete_tx::bytes [%0], [%1, {%3, %4}], [%2];" ::"r"(dst), "l"(m), "r"(bar), "r"(c0), "r"(c1) : "memory");
}
__device__ __forceinline__ void tma3d(uint32_t dst, const CUtensorMap* m, int c0, int c1, int c2, uint32_t bar) {
    asm volatile("cp.async.bulk.tensor.3d.shared::cluster.global.mbarrier::complete_tx::bytes [%0], [%1, {%3, %4, %5}], [%2];" ::"r"(dst), "l"(m), "r"(bar), "r"(c0), "r"(c1), "r"(c2) : "memory");
}
__device__ __forceinline__ void tma3d_mc(uint32_t dst, const CUtensorMap* m, int c0, int c1, int c2, uint32_t bar) {
    asm volatile("cp.async.bulk.tensor.3d.shared::cluster.global.mbarrier::complete_tx::bytes.multicast::cluster [%0], [%1, {%3, %4, %5}], [%2], %6;"
                 ::"r"(dst), "l"(m), "r"(bar), "r"(c0), "r"(c1), "r"(c2), "h"((uint16_t)3) : "memory");
}
__device__ __forceinline__ void tma2d_store(const CUtensorMap* m, uint32_t src, int c0, int c1) {
    asm volatile("cp.async.bulk.tensor.2d.global.shared::cta.bulk_group [%0, {%2, %3}], [%1];" ::"l"(m), "r"(src), "r"(c0), "r"(c1) : "memory");
}
__device__ __forceinline__ void tma4d_store(const CUtensorMap* m, uint32_t src, int c0, int c1, int c2, int c3) {
    asm volatile("cp.async.bulk.tensor.4d.global.shared::cta.bulk_group [%0, {%2, %3, %4, %5}], [%1];" ::"l"(m), "r"(src), "r"(c0), "r"(c1), "r"(c2), "r"(c3) : "memory");
}
__device__ __forceinline__ void tma4d(uint32_t dst, const CUtensorMap* m, int c0, int c1, int c2, int c3, uint32_t bar) {
    asm volatile("cp.async.bulk.tensor.4d.shared::cluster.global.mbarrier::complete_tx::bytes [%0], [%1, {%3, %4, %5, %6}], [%2];" ::"r"(dst), "l"(m), "r"(bar), "r"(c0), "r"(c1), "r"(c2), "r"(c3) : "memory");
}
__device__ __forceinline__ void bulk_load(uint32_t dst, const void* src, uint32_t bytes, uint32_t bar) {
    asm volatile("cp.async.bulk.shared::cluster.global.mbarrier::complete_tx::bytes [%0], [%1], %2, [%3];" ::"r"(dst), "l"(src), "r"(bytes), "r"(bar) : "memory");
}
__device__ __forceinline__ void bulk_store(void* dst, uint32_t src, uint32_t bytes) {
    asm volatile("cp.async.bulk.global.shared::cta.bulk_group [%0], [%1], %2;" ::"l"(dst), "r"(src), "r"(bytes) : "memory");
}
__device__ __forceinline__ void bulk_commit() { asm volatile("cp.async.bulk.commit_group;" ::: "memory"); }
__device__ __forceinline__ void bulk_wait_all() { asm volatile("cp.async.bulk.wait_group 0;" ::: "memory"); }
__device__ __forceinline__ void bulk_wait_read() { asm volatile("cp.async.bulk.wait_group.read 0;" ::: "memory"); }
__device__ __forceinline__ void l2_prefetch(const void* p) { asm volatile("prefetch.global.L2 [%0];" ::"l"(p)); }
__device__ __forceinline__ void fence_async_smem() { asm volatile("fence.proxy.async.shared::cta;" ::: "memory"); }
__device__ __forceinline__ void fence_async_global() { asm volatile("fence.proxy.async.global;" ::: "memory"); }
__device__ __forceinline__ void red_relaxed(unsigned* p, unsigned v) { asm volatile("red.relaxed.gpu.global.add.u32 [%0], %1;" ::"l"(p), "r"(v) : "memory"); }
__device__ __forceinline__ void publish(unsigned* p) {
    asm volatile("fence.proxy.async.global;\nred.release.gpu.global.add.u32 [%0], 1;" ::"l"(p) : "memory");
}
__device__ __forceinline__ void stg32(void* p, uint32_t v) { asm volatile("st.global.b32 [%0], %1;" ::"l"(p), "r"(v) : "memory"); }
__device__ __forceinline__ unsigned ld_relaxed(const unsigned* p) { unsigned v; asm volatile("ld.relaxed.gpu.global.u32 %0, [%1];" : "=r"(v) : "l"(p) : "memory"); return v; }
__device__ __forceinline__ bool ctr_done(unsigned v, unsigned target) { return ((v - target) & 0x1FFFFFFu) == 0; }
__device__ __forceinline__ uint32_t clock32() { uint32_t c; asm volatile("mov.u32 %0, %%clock;" : "=r"(c)::"memory"); return c; }
__device__ __forceinline__ void delay(uint32_t n) { const uint32_t t0 = clock32(); while (clock32() - t0 < n) {} }
__device__ __forceinline__ void poll(const unsigned* p, unsigned target) { while (!ctr_done(ld_relaxed(p), target)) {} }
__device__ __forceinline__ void cell_put(void* p, uint32_t a, uint32_t b, uint32_t tag) {
    asm volatile("st.relaxed.gpu.global.v4.b32 [%0], {%1, %3, %2, %3};" ::"l"(p), "r"(a), "r"(b), "r"(tag) : "memory");
}
__device__ __forceinline__ uint32_t cell_get(const void* p, uint32_t& a, uint32_t& b, uint32_t tag) {
    uint32_t t0, t1;
    asm volatile("ld.relaxed.gpu.global.v4.b32 {%0, %1, %2, %3}, [%4];" : "=r"(a), "=r"(t0), "=r"(b), "=r"(t1) : "l"(p) : "memory");
    return (t0 ^ tag) | (t1 ^ tag);
}
__device__ __forceinline__ void after(uint32_t zero) { asm volatile("{\n.reg .pred p;\nsetp.ne.u32 p, %0, 0;\n@p trap;\n}" ::"r"(zero) : "memory"); }
template <int ID, int N> __device__ __forceinline__ void bar_sync() { asm volatile("bar.sync %0, %1;" ::"n"(ID), "n"(N) : "memory"); }
template <int ID = 4> __device__ __forceinline__ void gate_wait(uint32_t on) { asm volatile("{\n.reg .pred p;\nsetp.ne.u32 p, %0, 0;\n@p bar.sync %1, 256;\n}" ::"r"(on), "n"(ID) : "memory"); }
template <int ID = 4> __device__ __forceinline__ void gate_open(uint32_t off) { asm volatile("{\n.reg .pred p;\nsetp.eq.u32 p, %0, 0;\n@p bar.arrive %1, 256;\n}" ::"r"(off), "n"(ID) : "memory"); }
__device__ __forceinline__ void wg_fence() { asm volatile("wgmma.fence.sync.aligned;" ::: "memory"); }
__device__ __forceinline__ void wg_commit() { asm volatile("wgmma.commit_group.sync.aligned;" ::: "memory"); }
template <int N> __device__ __forceinline__ void wg_wait() { asm volatile("wgmma.wait_group.sync.aligned %0;" ::"n"(N) : "memory"); }
template <int LO = 0, int HI = 56, int N> __device__ __forceinline__ void pin(float (&a)[N]) {
#pragma unroll
    for (int i = LO; i < (HI < N ? HI : N); i++) asm volatile("" : "+f"(a[i])::"memory");
}
__device__ __forceinline__ uint32_t ldg_u16(const void* p) {
    uint32_t v;
    asm volatile("ld.global.nc.u16 %0, [%1];" : "=r"(v) : "l"(p) : "memory");
    return v;
}
__device__ __forceinline__ uint32_t pack2(float lo, float hi) { uint32_t r; asm("cvt.rn.bf16x2.f32 %0, %1, %2;" : "=r"(r) : "f"(hi), "f"(lo)); return r; }
__device__ __forceinline__ float bf_lo(uint32_t v) { return __uint_as_float(v << 16); }
__device__ __forceinline__ float bf_hi(uint32_t v) { return __uint_as_float(v & 0xFFFF0000u); }
__device__ __forceinline__ uint32_t split2(float x) { return pack2(x, x - bf_lo(pack2(x, 0.f))); }
__device__ __forceinline__ void stsm4(uint32_t a, uint32_t r0, uint32_t r1, uint32_t r2, uint32_t r3) {
    asm volatile("stmatrix.sync.aligned.m8n8.x4.shared.b16 [%0], {%1, %2, %3, %4};" ::"r"(a), "r"(r0), "r"(r1), "r"(r2), "r"(r3) : "memory");
}
__device__ __forceinline__ void stsm2(uint32_t a, uint32_t r0, uint32_t r1) {
    asm volatile("stmatrix.sync.aligned.m8n8.x2.shared.b16 [%0], {%1, %2};" ::"r"(a), "r"(r0), "r"(r1) : "memory");
}
__device__ __forceinline__ void ldsm4(uint32_t a, uint32_t (&r)[4]) {
    asm volatile("ldmatrix.sync.aligned.m8n8.x4.shared.b16 {%0, %1, %2, %3}, [%4];" : "=r"(r[0]), "=r"(r[1]), "=r"(r[2]), "=r"(r[3]) : "r"(a) : "memory");
}
__device__ __forceinline__ void ldsm4t(uint32_t a, uint32_t (&r)[4]) {
    asm volatile("ldmatrix.sync.aligned.m8n8.x4.trans.shared.b16 {%0, %1, %2, %3}, [%4];" : "=r"(r[0]), "=r"(r[1]), "=r"(r[2]), "=r"(r[3]) : "r"(a) : "memory");
}
__device__ __forceinline__ void mma16816(float (&c)[4], uint32_t a0, uint32_t a1, uint32_t a2, uint32_t a3, uint32_t b0, uint32_t b1) {
    asm volatile("mma.sync.aligned.m16n8k16.row.col.f32.bf16.bf16.f32 {%0,%1,%2,%3}, {%4,%5,%6,%7}, {%8,%9}, {%0,%1,%2,%3};"
                 : "+f"(c[0]), "+f"(c[1]), "+f"(c[2]), "+f"(c[3]) : "r"(a0), "r"(a1), "r"(a2), "r"(a3), "r"(b0), "r"(b1));
}
__device__ __forceinline__ void mma1688(float (&c)[4], uint32_t a0, uint32_t a1, uint32_t b0) {
    asm volatile("mma.sync.aligned.m16n8k8.row.col.f32.bf16.bf16.f32 {%0,%1,%2,%3}, {%4,%5}, {%6}, {%0,%1,%2,%3};"
                 : "+f"(c[0]), "+f"(c[1]), "+f"(c[2]), "+f"(c[3]) : "r"(a0), "r"(a1), "r"(b0));
}
constexpr uint32_t SB0 = 1024;
__device__ __forceinline__ uint32_t desc_lo(uint32_t off, uint32_t lbo) { return ((SB0 + off) >> 4) + ((lbo >> 4) << 16); }
constexpr uint32_t H_SW = (1024 >> 4) | (1u << 30), H_H = 128 >> 4, H_U = 1024 >> 4;
__device__ __forceinline__ float ex2(float x) { float r; asm("ex2.approx.ftz.f32 %0, %1;" : "=f"(r) : "f"(x)); return r; }
__device__ __forceinline__ float rsq(float x) { float r; asm("rsqrt.approx.ftz.f32 %0, %1;" : "=f"(r) : "f"(x)); return r; }
__device__ __forceinline__ float rcp(float x) { float r; asm("rcp.approx.ftz.f32 %0, %1;" : "=f"(r) : "f"(x)); return r; }

template <uint32_t HB, int TB>
__device__ __forceinline__ void wgmma_n56_rs(float (&d)[28], const uint32_t (&a)[4], uint32_t lb, int scale_d) {
    asm volatile("{\n.reg .pred p;\n.reg .b64 db;\nsetp.ne.b32 p, %33, 0;\nmov.b64 db, {%32, %34};\n"
        "wgmma.mma_async.sync.aligned.m64n56k16.f32.bf16.bf16 "
        "{%0, %1, %2, %3, %4, %5, %6, %7, %8, %9, %10, %11, %12, %13, %14, %15, %16, %17, %18, %19, %20, %21, %22, %23, %24, %25, %26, %27}, "
        "{%28, %29, %30, %31}, db, p, 1, 1, %35;\n}\n"
        : "+f"(d[0]), "+f"(d[1]), "+f"(d[2]), "+f"(d[3]), "+f"(d[4]), "+f"(d[5]), "+f"(d[6]), "+f"(d[7]), "+f"(d[8]), "+f"(d[9]), "+f"(d[10]), "+f"(d[11]), "+f"(d[12]), "+f"(d[13]), "+f"(d[14]), "+f"(d[15]), "+f"(d[16]), "+f"(d[17]), "+f"(d[18]), "+f"(d[19]), "+f"(d[20]), "+f"(d[21]), "+f"(d[22]), "+f"(d[23]), "+f"(d[24]), "+f"(d[25]), "+f"(d[26]), "+f"(d[27])
        : "r"(a[0]), "r"(a[1]), "r"(a[2]), "r"(a[3]), "r"(lb), "r"(scale_d), "n"(HB), "n"(TB));
}
template <int TA, uint32_t HA, uint32_t HB>
__device__ __forceinline__ void wgmma_n112(float (&d)[56], uint32_t la, uint32_t lb, int scale_d = 1) {
    asm volatile("{\n.reg .b64 da, db;\n.reg .pred p;\nsetp.ne.b32 p, %61, 0;\nmov.b64 da, {%56, %59};\nmov.b64 db, {%57, %60};\n"
        "wgmma.mma_async.sync.aligned.m64n112k16.f32.bf16.bf16 "
        "{%0, %1, %2, %3, %4, %5, %6, %7, %8, %9, %10, %11, %12, %13, %14, %15, %16, %17, %18, %19, %20, %21, %22, %23, %24, %25, %26, %27, %28, %29, %30, %31, %32, %33, %34, %35, %36, %37, %38, %39, %40, %41, %42, %43, %44, %45, %46, %47, %48, %49, %50, %51, %52, %53, %54, %55}, "
        "da, db, p, 1, 1, %58, 1;\n}\n"
        : "+f"(d[0]), "+f"(d[1]), "+f"(d[2]), "+f"(d[3]), "+f"(d[4]), "+f"(d[5]), "+f"(d[6]), "+f"(d[7]), "+f"(d[8]), "+f"(d[9]), "+f"(d[10]), "+f"(d[11]), "+f"(d[12]), "+f"(d[13]), "+f"(d[14]), "+f"(d[15]), "+f"(d[16]), "+f"(d[17]), "+f"(d[18]), "+f"(d[19]), "+f"(d[20]), "+f"(d[21]), "+f"(d[22]), "+f"(d[23]), "+f"(d[24]), "+f"(d[25]), "+f"(d[26]), "+f"(d[27]), "+f"(d[28]), "+f"(d[29]), "+f"(d[30]), "+f"(d[31]), "+f"(d[32]), "+f"(d[33]), "+f"(d[34]), "+f"(d[35]), "+f"(d[36]), "+f"(d[37]), "+f"(d[38]), "+f"(d[39]), "+f"(d[40]), "+f"(d[41]), "+f"(d[42]), "+f"(d[43]), "+f"(d[44]), "+f"(d[45]), "+f"(d[46]), "+f"(d[47]), "+f"(d[48]), "+f"(d[49]), "+f"(d[50]), "+f"(d[51]), "+f"(d[52]), "+f"(d[53]), "+f"(d[54]), "+f"(d[55])
        : "r"(la), "r"(lb), "n"(TA), "n"(HA), "n"(HB), "r"(scale_d));
}
template <int TA, uint32_t HA, uint32_t HB>
__device__ __forceinline__ void wgmma_n8(float (&d)[4], uint32_t la, uint32_t lb, int scale_d = 1) {
    asm volatile("{\n.reg .b64 da, db;\n.reg .pred p;\nsetp.ne.b32 p, %9, 0;\nmov.b64 da, {%4, %7};\nmov.b64 db, {%5, %8};\n"
        "wgmma.mma_async.sync.aligned.m64n8k16.f32.bf16.bf16 "
        "{%0, %1, %2, %3}, "
        "da, db, p, 1, 1, %6, 1;\n}\n"
        : "+f"(d[0]), "+f"(d[1]), "+f"(d[2]), "+f"(d[3])
        : "r"(la), "r"(lb), "n"(TA), "n"(HA), "n"(HB), "r"(scale_d));
}

__device__ __forceinline__ void send4(uint32_t rbuf, uint32_t rbar, uint32_t w0, uint32_t w1, uint32_t w2, uint32_t w3, uint32_t on) {
    asm volatile("{\n.reg .pred p;\nsetp.ne.u32 p, %6, 0;\n@p st.async.weak.shared::cluster.mbarrier::complete_tx::bytes.v4.b32 [%0], {%1,%2,%3,%4}, [%5];\n}"
                 ::"r"(rbuf), "r"(w0), "r"(w1), "r"(w2), "r"(w3), "r"(rbar), "r"(on) : "memory");
}
__device__ __forceinline__ void send_half(const float (&a)[56], uint32_t rbuf, uint32_t rbar, int t, uint32_t on) {
#pragma unroll
    for (int i = 28; i < 52; i += 8)
        send4(rbuf + (i - 28) * 256 + t * 16, rbar, pack2(a[i], a[i + 1]), pack2(a[i + 2], a[i + 3]), pack2(a[i + 4], a[i + 5]), pack2(a[i + 6], a[i + 7]), on);
    asm volatile("{\n.reg .pred p;\nsetp.ne.u32 p, %4, 0;\n@p st.async.weak.shared::cluster.mbarrier::complete_tx::bytes.v2.b32 [%0], {%1,%2}, [%3];\n}"
                 ::"r"(rbuf + 6144 + t * 8), "r"(pack2(a[52], a[53])), "r"(pack2(a[54], a[55])), "r"(rbar), "r"(on) : "memory");
}
__device__ __forceinline__ void recv_half(uint32_t (&p)[14], uint32_t buf, int t) {
#pragma unroll
    for (int i = 0; i < 3; i++)
        asm volatile("ld.shared.v4.b32 {%0,%1,%2,%3}, [%4];" : "=r"(p[4 * i]), "=r"(p[4 * i + 1]), "=r"(p[4 * i + 2]), "=r"(p[4 * i + 3]) : "r"(buf + i * 2048 + t * 16) : "memory");
    asm volatile("ld.shared.v2.b32 {%0,%1}, [%2];" : "=r"(p[12]), "=r"(p[13]) : "r"(buf + 6144 + t * 8) : "memory");
}

struct Maps { CUtensorMap xl, x, wqkv, hst, w1, w2, xn, old_, ost, wo; };

__global__ void __cluster_dims__(2, 1, 1) __launch_bounds__(512, 1)
fused_kernel(const __nv_bfloat16* __restrict__ x, const __nv_bfloat16* __restrict__ b1, const __nv_bfloat16* __restrict__ b2, uint8_t* __restrict__ scr,
             uint8_t* __restrict__ out, const __grid_constant__ Maps mp) {
    extern __shared__ __align__(1024) uint8_t smem[];
    const uint32_t sb = smem_u32(smem);
    const uint32_t bar = sb + OFF_BAR;
    const int tid = threadIdx.x, lane = tid & 31;
    const int b = blockIdx.x, z = b & 1, c = b >> 1;
    unsigned* const ctr = reinterpret_cast<unsigned*>(scr + G_CTR);
    if (tid < 112) l2_prefetch(reinterpret_cast<const uint8_t*>(x) + (b * 112 + tid) * 128);
    const uint32_t t_in = clock32();
    TS0(0);
    TG(60);
    const int warp = __shfl_sync(0xffffffffu, tid >> 5, 0);
    const int j = c < 4 ? c : c < 36 ? (c - 4) >> 3 : ((c - 36) * 37) >> 8, q = c < 4 ? 15 : c < 36 ? (c - 4) & 7 : c - 28 - 7 * j;
    const bool g1 = q < 14;
    const int R = q < 8 ? q : (0x27654310u >> (4 * q - 32)) & 7, P = (q >> 3) * 4 + j;
    auto krow = [&](int kb) { const int k = kb + (R & 6); return (k >= 7 ? k - 7 : k) * 64; };
    auto x_load = [&](int kb) {
        mbar_expect(bar + 8 * (B_FULLQ + kb), 40960);
        tma2d(sb + OFF_A + ((XSLOT >> (4 * kb)) & 7) * 16384, &mp.x, z * D_ + krow(kb), R * 128, bar + 8 * (B_FULLQ + kb));
    };
    auto w_load = [&](int kb) {
        tma3d_mc(sb + OFF_B + ((WSLOT >> (4 * kb)) & 7) * 24576 + z * 12288, &mp.wqkv, (P * 56) & ~15, krow(kb) + z * 32, 0, bar + 8 * (B_FULLQ + kb));
    };
    if (warp == 12 && elect()) {
#pragma unroll
        for (int i = B_FULLQ; i < B_EMPTYQ; i++) mbar_init(bar + 8 * i, 1);
        mbar_expect(bar + 8 * B_LNIN, BLK);
        tma3d(sb + OFF_A, &mp.xl, 0, 16 * b, 0, bar + 8 * B_LNIN);
        x_load(0);
        TS(15);
    }
    auto bar_count = [&](int i) {
        return i < B_FULL ? (i < B_EMPTYQ + 2 ? 24 : 8) : i < B_EMPTY || i == B_FREE ? 2 : (i < B_AUX || i == B_NONE || i == B_OST) ? 8 : i == B_KV ? 12
               : (i == B_AUX || i == B_HALO) ? 4 : 1;
    };
    if (warp == 13 && elect()) {
#pragma unroll
        for (int i = B_EMPTYQ; i < B_COUNT; i++) mbar_init(bar + 8 * i, bar_count(i));
#pragma unroll
        for (int i = B_RECV1; i < B_EP; i++) mbar_expect(bar + 8 * i, i < B_RECV2 ? 7168 : 8192 - 2048 * z);
    }
    asm volatile("fence.mbarrier_init.release.cluster;" ::: "memory");
    __syncwarp();
    asm volatile("barrier.cluster.arrive.relaxed.aligned;\nbarrier.cluster.wait.aligned;" ::: "memory");
    if (warp == 12 && elect()) { w_load(0); TS(16); }
    auto slot = [](uint32_t r) { return r - 6 * ((r * 43) >> 8); };
    auto phase = [](uint32_t r) { return ((r * 43) >> 8) & 1; };
    const uint32_t r_o = g1 ? 16 : 0, r_u = r_o + 3;
    auto xslot = [&](uint32_t i) { return i == 1 ? 6 : slot(r_o + i - (i > 1)); };
    auto aoff = [](uint32_t s) { return s == 6 ? OFF_SA - OFF_A : s * 16384; };
    auto fetch_x = [&](uint32_t i, bool arm = true) {
        const uint32_t s = xslot(i), lb = bar + 8 * (B_LAND + s);
        if (arm) mbar_expect(lb, i < 4 ? 16384 : BLK);
        if (i < 4) tma2d(sb + OFF_A + aoff(s), &mp.old_, 0, (4 * z + i) * S_ + q * 128, lb);
        else bulk_load(sb + OFF_B + s * BLK, scr + G_BIMG + ((14 * z + (i < 11 ? 2 * i : 2 * i - 13)) * 4 + j) * BLK, BLK, lb);
    };
    auto epoch = [&]() { mbar_wait(bar + 8 * B_EP, 0); return *reinterpret_cast<volatile unsigned*>(smem + OFF_EP); };

    if (warp < 8) {
        const int wg = warp >> 2, w4 = warp & 3, t = tid & 127, g = lane >> 2, tq = lane & 3;
        asm volatile("setmaxnreg.inc.sync.aligned.u32 208;");
        uint32_t xa[4];
#pragma unroll
        for (int k = 0; k < 4; k++) xa[k] = sb + OFF_A + (warp * 16 + (lane & 15)) * 128 + (((2 * k + (lane >> 4)) ^ (lane & 7)) << 4);
        {
            const int rg = warp & 1, jq = warp >> 1;
            const uint32_t ex = sb + OFF_LNX + (rg * 8 + g) * 32, ew = ex + jq * 8, ls = sb + OFF_LNST + (rg * 8 + g) * 8;
            const uint32_t l0 = sb + OFF_A + rg * 1024 + g * 144;
            uint32_t r[4][4], la[4], ha[4], x0, dep = ex | ew | ls | l0;
#pragma unroll
            for (int i = 0; i < 4; i++) {
                const int cg = 14 * jq + 4 * i + ((lane >> 3) & (i < 3 ? 3 : 1));
                la[i] = sb + OFF_A + (cg >> 3) * 2048 + rg * 1024 + (lane & 7) * 128 + (((cg ^ lane) & 7) << 4);
                int pos = 4 * i + (lane >> 3) + (b >= 64 ? 7 : 0);
                if (pos >= 14) pos -= 14;
                ha[i] = sb + OFF_A + jq * 3584 + rg * 1792 + (lane & 7) * 16 + pos * 128;
                dep |= la[i] | xa[i] | ha[i];
            }
            mbar_wait(bar + 8 * B_LNIN, dep >> 31);
            asm volatile("ld.shared.b32 %0, [%1];" : "=r"(x0) : "r"(l0) : "memory");
#pragma unroll
            for (int i = 0; i < 4; i++) ldsm4(la[i], r[i]);
            float s1[4], s2[4], v[28];
            const float sh = bf_lo(x0);
#pragma unroll
            for (int n = 0; n < 14; n++) { v[2 * n] = bf_lo(r[n >> 2][n & 3]) - sh; v[2 * n + 1] = bf_hi(r[n >> 2][n & 3]) - sh; }
#pragma unroll
            for (int n = 0; n < 28; n++) {
                s1[n & 3] = n < 4 ? v[n] : s1[n & 3] + v[n];
                s2[n & 3] = n < 4 ? v[n] * v[n] : fmaf(v[n], v[n], s2[n & 3]);
            }
            float m1 = (s1[0] + s1[1]) + (s1[2] + s1[3]), m2 = (s2[0] + s2[1]) + (s2[2] + s2[3]);
#pragma unroll
            for (int o = 1; o <= 2; o <<= 1) { m1 += __shfl_xor_sync(0xffffffffu, m1, o); m2 += __shfl_xor_sync(0xffffffffu, m2, o); }
            asm volatile("st.shared.v2.f32 [%0], {%1, %2};" ::"r"(ew), "f"(m1), "f"(m2) : "memory");
            bar_sync<1, 256>();
            float4 e0, e1;
            asm volatile("ld.shared.v4.f32 {%0,%1,%2,%3}, [%4];" : "=f"(e0.x), "=f"(e0.y), "=f"(e0.z), "=f"(e0.w) : "r"(ex) : "memory");
            asm volatile("ld.shared.v4.f32 {%0,%1,%2,%3}, [%4];" : "=f"(e1.x), "=f"(e1.y), "=f"(e1.z), "=f"(e1.w) : "r"(ex + 16) : "memory");
            const float dm = ((e0.x + e0.z) + (e1.x + e1.z)) * (1.f / D_);
            const float var = fmaxf(fmaf(-dm, dm, ((e0.y + e0.w) + (e1.y + e1.w)) * (1.f / D_)), 0.f);
            const float r1 = rsq(var + 1e-5f), sc = rsq(fmaf(1e-5f, var + 1e-5f, var)), of = -dm * sc;
#pragma unroll
            for (int n = 0; n < 14; n++) r[n >> 2][n & 3] = pack2(fmaf(v[2 * n], sc, of), fmaf(v[2 * n + 1], sc, of));
#pragma unroll
            for (int i = 0; i < 3; i++) stsm4(ha[i], r[i][0], r[i][1], r[i][2], r[i][3]);
            stsm2(ha[3], r[3][0], r[3][1]);
            asm volatile("st.shared.v2.b32 [%0], {%1, %2};" ::"r"(ls), "r"(__float_as_uint(r1)), "r"(split2(-(sh + dm))) : "memory");
            TS0(24);
            asm volatile("bar.arrive 10, 288;" ::: "memory");
        }
        float a1[56];
        float rq[2], hb1[2], fb2[2];
        uint32_t qp[14], kp[14];
        const uint32_t ka = sb + OFF_K + warp * 896 + (lane & 7) * 112 + (lane >> 3) * 16;
        const uint32_t va = sb + OFF_V + (warp * 16 + (lane & 15)) * 112 + (lane >> 4) * 16;
        const uint32_t sta = sb + OFF_RSTD + warp * 64 + tq * 8;
        const uint32_t dA = desc_lo(OFF_A + wg * 8192, 16), dH = desc_lo(OFF_B, 1792), dU = desc_lo(OFF_B, 128);
        auto release = [&](uint32_t a) { mbar_arrive_if0(a, lane); };
        uint32_t rel = bar + 8 * (B_EMPTYQ + 6);
        auto g1_step = [&](uint32_t s, uint32_t acc) {
            wg_fence();
#pragma unroll
            for (int k = 0; k < 4; k++) wgmma_n112<1, H_SW, H_H>(a1, dA + s * 1024 + k * 128, dH + s * 896 + k * 224, k ? 1 : acc);
            wg_commit();
            wg_wait<1>();
            release(rel);
            rel = bar + 8 * (B_EMPTY + s);
        };
        auto g1_run = [&](uint32_t r0, uint32_t r1, bool last = false) {
#pragma unroll 1
            for (uint32_t r = g1 ? r0 : r1; r < r1; r++) {
                if (TSG1) TSD(64 + r);
                g1_step(slot(r), r);
                const bool end = last && r + 1 == r1;
                mbar_wait(bar + 8 * (end ? B_FREE : B_FULL + slot(r + 1)), !end && phase(r + 1));
            }
        };
        auto drain = [&]() { wg_wait<0>(); release(rel); rel = bar + 8 * B_NONE; };
        {
            float aq0[28], aq1[28], aq2[28];
            const uint32_t dW = desc_lo(OFF_B + (P & 1) * 16, 16);
            uint32_t xf[2][4][4];
            const uint32_t rb = mapa(bar + 8 * (B_EMPTYQ - 1), z ^ 1);
            auto fetch = [&](int kb, uint32_t (&f)[4][4]) {
                if (TSG1) TSD(178 + kb);
                mbar_wait(bar + 8 * (B_FULLQ + kb), 0);
                if (TSG1) TSD(170 + kb);
#pragma unroll
                for (int k = 0; k < 4; k++) ldsm4(xa[k] + ((XSLOT >> (4 * kb)) & 7) * 16384, f[k]);
            };
            auto mma = [&](int kb, uint32_t (&f)[4][4], int k0, int k1) {
                const uint32_t d0 = dW + ((WSLOT >> (4 * kb)) & 7) * 1536;
                wg_fence();
#pragma unroll
                for (int k = k0; k < k1; k++) {
                    const uint32_t d = d0 + (k >> 1) * 768 + (k & 1) * 128;
                    const int sc = k > 0 ? 1 : kb;
                    wgmma_n56_rs<H_SW, 1>(aq0, f[k], d, sc);
                    wgmma_n56_rs<H_SW, 1>(aq1, f[k], d + 256, sc);
                    wgmma_n56_rs<H_SW, 1>(aq2, f[k], d + 512, sc);
                }
            };
            auto retire = [&](int kb) {
                wg_commit();
                wg_wait<1>();
                mbar_arrive_if0(bar + 8 * (B_EMPTYQ + kb - 1), lane | (kb < 1));
                asm volatile("{\n.reg .pred p;\nsetp.eq.u32 p, %1, 0;\n@p mbarrier.arrive.shared::cluster.b64 _, [%0];\n}"
                             ::"r"(rb + 8 * kb), "r"(lane | ((uint32_t)(kb - 1) > 1)) : "memory");
            };
            auto stage = [&](int kb, uint32_t (&f)[4][4], uint32_t (&n)[4][4]) {
                mma(kb, f, 0, KS);
                retire(kb);
                fetch(kb + 1, n);
                mma(kb, f, KS, 4);
                wg_commit();
            };
            fetch(0, xf[0]);
#pragma unroll 1
            for (int kb = 0; kb < 6; kb += 2) {
                stage(kb, xf[0], xf[1]);
                stage(kb + 1, xf[1], xf[0]);
            }
            mma(6, xf[0], 0, KS);
            retire(6);
            TS0(2);
            mbar_wait(bar + 8 * B_AUX, 0);
            {
                uint32_t (&f)[4] = xf[1][0];
                const uint2* mt = reinterpret_cast<const uint2*>(smem + OFF_STATS) + warp * 16 + g;
                const uint2 m0 = mt[0], m1 = mt[8];
                const uint32_t sel = tq == 0 ? 0x1010 : tq == 1 ? 0x3232 : 0x4444;
                f[0] = __byte_perm(m0.y, 0, sel); f[1] = __byte_perm(m1.y, 0, sel); f[2] = f[3] = 0;
                rq[0] = __uint_as_float(m0.x); rq[1] = __uint_as_float(m1.x);
                asm volatile("" : "+r"(f[0]), "+r"(f[1]), "+r"(f[2]), "+r"(f[3])::"memory");
                const uint32_t d = desc_lo(OFF_CSB + (P & 1) * 128, 0);
                mma(6, xf[0], KS, 4);
                wgmma_n56_rs<H_H, 0>(aq1, f, d + 64, 1);
                wgmma_n56_rs<H_H, 0>(aq2, f, d + 128, 1);
                wgmma_n56_rs<H_H, 0>(aq0, f, d, 1);
                wg_commit();
            }
            mbar_wait(bar + 8 * (g1 ? B_FULL : B_LNIN), 0);
            g1_run(0, wg ? 0 : NE);
            drain();
            pin(aq0); pin(aq1); pin(aq2);
            TSW(3);
            mbar_wait(bar + 8 * (B_EMPTYQ + 5), 0);
#pragma unroll
            for (int i = 0; i < 14; i++) { kp[i] = pack2(aq1[2 * i], aq1[2 * i + 1]); qp[i] = pack2(aq2[2 * i], aq2[2 * i + 1]); }
            stsm4(ka + 896, kp[1], kp[3], kp[5], kp[7]);
            stsm4(ka + 896 + 48, kp[7], kp[9], kp[11], kp[13]);
#pragma unroll
            for (int n = 0; n < 3; n++) stsm4(va + 896 + n * 32, qp[4 * n], qp[4 * n + 1], qp[4 * n + 2], qp[4 * n + 3]);
            stsm2(va + 896 + 96, qp[12], qp[13]);
            __syncwarp();
            mbar_arrive_if0(bar + 8 * B_QKV, tid - 224);
            release(bar + 8 * B_KV);
#pragma unroll
            for (int i = 0; i < 14; i++) qp[i] = pack2(aq0[2 * i], aq0[2 * i + 1]);
            TSW(4);
        }
        g1_run(wg ? 0 : NE, wg ? PRE1 : PRE0);
        {
            uint32_t kf[2][3][4], vf[2][3][4];
            const bool up0 = 2 * tq > g, up1 = 2 * tq + 1 > g, edge = (R | warp) == 0;
            float rk[2][2], fs[2][2], rs[3][2];
            mbar_wait(bar + 8 * (warp ? B_KV : B_HALO), 0);
            const uint32_t tag = *reinterpret_cast<volatile unsigned*>(smem + OFF_EP);
#pragma unroll
            for (int i = 0; i < 2; i++)
                asm volatile("ld.shared.v2.f32 {%0,%1}, [%2];" : "=f"(hb1[i]), "=f"(fb2[i]) : "r"(sb + OFF_BIAS + (warp * 16 + g + 8 * i) * 8) : "memory");
#pragma unroll
            for (int i = 0; i < 3; i++)
                asm volatile("ld.shared.v2.f32 {%0,%1}, [%2];" : "=f"(rs[i][0]), "=f"(rs[i][1]) : "r"(sta + i * 32) : "memory");
#pragma unroll
            for (int hd = 0; hd < 2; hd++) {
                ldsm4(ka + hd * 48, kf[hd][0]);
#pragma unroll
                for (int i = 0; i < 4; i++) { kf[hd][1][i] = kp[6 * hd + 2 * i]; kf[hd][2][i] = kp[6 * hd + 2 * i + 1]; }
                ldsm4t(va + hd * 48, vf[hd][0]); ldsm4t(va + hd * 48 + 32, vf[hd][1]);
                ldsm4t(ka + (OFF_V - OFF_K) + warp * 896 + hd * 48 + 1792, vf[hd][2]);
            }
            const uint32_t q0l = tq < 2 ? qp[6] : 0, q0h = tq < 2 ? qp[7] : 0, q1l = tq < 2 ? 0 : qp[6], q1h = tq < 2 ? 0 : qp[7];
            const uint32_t mk = (up0 ? 0xFFFFu : 0u) | (up1 ? 0xFFFF0000u : 0u);
            g1_run(wg ? PRE1 : PRE0, ATT_STEP);
#pragma unroll
            for (int i = 0; i < 4; i++) {
                rk[i >> 1][i & 1] = ((i & 1) ? up1 : up0) ? rs[i >> 1][i & 1] : rs[(i >> 1) + 1][i & 1];
                fs[i >> 1][i & 1] = rk[i >> 1][i & 1] * (rq[i >> 1] * (0.18898223650461362f * 1.4426950408889634f));
                asm volatile("" : "+f"(fs[i >> 1][i & 1])::"memory");
            }
            uint32_t zr[4], oa[4], dep = q0l | q0h | q1l | q1h | mk;
#pragma unroll
            for (int i = 0; i < 4; i++) {
                zr[i] = (lane + i) * (sb >> 31);
                oa[i] = xa[i] + OFF_OST;
            }
#pragma unroll
            for (int i = 0; i < 4; i++) dep |= __float_as_uint(fs[i >> 1][i & 1]) | oa[i] | zr[i];
            after(dep & (sb >> 31));
            drain();
            bar_sync<1, 256>();
            TS0(19);
            float sc[2][3][4];
#pragma unroll
            for (int u = 0; u < 3; u++) {
#pragma unroll
                for (int i = 0; i < 8; i++) sc[i >> 2][u][i & 3] = 0.f;
                mma16816(sc[0][u], qp[0], qp[1], qp[2], qp[3], kf[0][u][0], kf[0][u][1]);
                mma16816(sc[1][u], q1l, q1h, qp[8], qp[9], kf[1][u][0], kf[1][u][1]);
            }
#pragma unroll
            for (int u = 0; u < 3; u++) {
                mma16816(sc[0][u], qp[4], qp[5], q0l, q0h, kf[0][u][2], kf[0][u][3]);
                mma16816(sc[1][u], qp[10], qp[11], qp[12], qp[13], kf[1][u][2], kf[1][u][3]);
            }
            float e[2][2][2], mx[2][2], sm[2][4];
#pragma unroll
            for (int hd = 0; hd < 2; hd++) {
                e[hd][0][0] = (up0 ? sc[hd][0][0] : sc[hd][1][0]) * fs[0][0];
                e[hd][0][1] = (up1 ? sc[hd][0][1] : sc[hd][1][1]) * fs[0][1];
                e[hd][1][0] = (up0 ? sc[hd][1][2] : sc[hd][2][2]) * fs[1][0];
                e[hd][1][1] = (up1 ? sc[hd][1][3] : sc[hd][2][3]) * fs[1][1];
                if (edge && up0) e[hd][0][0] = -1e30f;
                if (edge && up1) e[hd][0][1] = -1e30f;
                mx[hd][0] = fmaxf(e[hd][0][0], e[hd][0][1]);
                mx[hd][1] = fmaxf(e[hd][1][0], e[hd][1][1]);
            }
#pragma unroll
            for (int o = 1; o <= 2; o <<= 1)
#pragma unroll
                for (int i = 0; i < 4; i++) mx[i >> 1][i & 1] = fmaxf(mx[i >> 1][i & 1], __shfl_xor_sync(0xffffffffu, mx[i >> 1][i & 1], o));
            uint32_t pp[2][2], pu[2][2];
#pragma unroll
            for (int i = 0; i < 4; i++) {
                const float p0 = ex2(e[i >> 1][i & 1][0] - mx[i >> 1][i & 1]), p1 = ex2(e[i >> 1][i & 1][1] - mx[i >> 1][i & 1]);
                pp[i >> 1][i & 1] = pack2(p0 * rk[i & 1][0], p1 * rk[i & 1][1]);
                pu[i >> 1][i & 1] = pack2(p0, p1);
            }
            float ov[2][4][4];
#pragma unroll
            for (int hd = 0; hd < 2; hd++)
#pragma unroll
                for (int n = 0; n < 4; n++) {
                    ov[hd][n][0] = ov[hd][n][1] = ov[hd][n][2] = ov[hd][n][3] = 0.f;
                    mma16816(ov[hd][n], pp[hd][0] & mk, zr[hd], pp[hd][0] & ~mk, pp[hd][1] & mk, vf[hd][n >> 1][2 * (n & 1)], vf[hd][n >> 1][2 * (n & 1) + 1]);
                }
#pragma unroll
            for (int hd = 0; hd < 2; hd++) {
                sm[hd][0] = sm[hd][1] = sm[hd][2] = sm[hd][3] = 0.f;
                mma1688(sm[hd], pu[hd][0], pu[hd][1], 0x3F803F80u);
            }
#pragma unroll
            for (int hd = 0; hd < 2; hd++)
#pragma unroll
                for (int n = 0; n < 4; n++) mma1688(ov[hd][n], zr[2 + hd], pp[hd][1] & ~mk, vf[hd][2][n]);
            TS0(18);
            uint32_t op[16];
            op[14] = op[15] = tag & 0x3FFF;
#pragma unroll
            for (int i = 0; i < 4; i++) sm[i >> 1][i & 1] = rcp(sm[i >> 1][2 * (i & 1)]);
#pragma unroll
            for (int n = 0; n < 7; n++) {
                const bool hb = n > 3 || (n == 3 && tq >= 2);
#pragma unroll
                for (int h = 0; h < 2; h++) {
                    const float r = hb ? sm[1][h] : sm[0][h];
                    const float x0 = hb ? ov[1][n >= 3 ? n - 3 : 0][2 * h] : ov[0][n <= 3 ? n : 0][2 * h];
                    const float x1 = hb ? ov[1][n >= 3 ? n - 3 : 0][2 * h + 1] : ov[0][n <= 3 ? n : 0][2 * h + 1];
                    op[2 * n + h] = pack2(x0 * r, x1 * r);
                }
            }
#pragma unroll
            for (int n = 0; n < 4; n++) stsm4(oa[n], op[4 * n], op[4 * n + 1], op[4 * n + 2], op[4 * n + 3]);
            __syncwarp();
            release(bar + 8 * B_OST);
            mbar_wait(bar + 8 * B_OST, 0);
            TSW(5);
        }
        const uint32_t peer = z ^ 1;
        g1_run(ATT_STEP, wg ? GS : 16, true);
        gate_open(wg | !g1);
        drain();
#pragma unroll 1
        for (uint32_t r = g1 && wg ? GS : 16; r < 16; r++) {
            gate_wait(r == GS);
            g1_step(r - 12, 1);
        }
        drain();
        pin(a1);
        TSW(6);
        send_half(a1, mapa(sb + OFF_RECV1 + wg * 7168, peer), mapa(bar + 8 * (B_RECV1 + wg), peer), t, g1);
        float h[28];
#pragma unroll
        for (int i = 0; i < 28; i++) h[i] = fmaf(a1[i], 0.5f, hb1[(i >> 1) & 1]);
        pin(h);
        if (g1) {
            uint32_t p[14];
            float y[28];
            uint8_t* ub = scr + G_BIMG + ((8 + 2 * q + wg) * 4 + j) * BLK + w4 * 256 + lane * 4;
            uint8_t *u0 = ub + (q < 7 ? 7 : 13) * z * 1024, *u1 = ub + (q < 7 ? 7 : 1) * z * 1024, *u2 = u1 + (q < 7 || z ? 0 : 6144);
            mbar_wait(bar + 8 * (B_RECV1 + wg), __any_sync(0xffffffffu, ((uint64_t)u0 | (uint64_t)u1 | (uint64_t)u2) >> 63));
            TSW(8);
            recv_half(p, sb + OFF_RECV1 + wg * 7168, t);
#pragma unroll
            for (int i = 0; i < 28; i++) {
                h[i] = fmaf((i & 1) ? bf_hi(p[i >> 1]) : bf_lo(p[i >> 1]), 0.5f, h[i]);
                y[i] = h[i] * fmaf(h[i] * h[i], 8.f * 0.0356774081363f, 2.f * 0.7978845608029f);
            }
#pragma unroll
            for (int i = 0; i < 28; i++) asm volatile("tanh.approx.f32 %0, %0;" : "+f"(y[i]));
#pragma unroll
            for (int i = 0; i < 14; i++)
                stg32((i < 2 ? u0 : i < 4 ? u1 : u2) + (i >> 1) * 1024 + (i & 1) * 128, pack2(fmaf(h[2 * i], y[2 * i], h[2 * i]), fmaf(h[2 * i + 1], y[2 * i + 1], h[2 * i + 1])));
            TSW(9);
        }
        float a2[56];
#pragma unroll 1
        for (uint32_t i = 0; i < 4; i++) {
            const uint32_t s = ((g1 ? 0x0564u : 0x2160u) >> (4 * i)) & 7, da = dA + (aoff(s) >> 4), db = dU + (i == 1 ? (OFF_SB - OFF_B) >> 4 : s * 896);
            mbar_wait(bar + 8 * (B_FULL + s), g1 && i == 3);
            TSD(64 + 17 + i);
            wg_fence();
#pragma unroll
            for (int k = 0; k < 4; k++) wgmma_n112<0, H_SW, H_U>(a2, da + k * 2, db + k * 16, k ? 1 : i);
            wg_commit();
            wg_wait<1>();
            release(rel);
            rel = bar + 8 * (B_EMPTY + s);
        }
        drain();
        TSW(10);
#pragma unroll 1
        for (uint32_t r = r_u; r < r_u + 14 - (wg ? NS2 : 0); r++) {
            const uint32_t s = slot(r);
            mbar_wait(bar + 8 * (B_FULL + s), phase(r));
            TSD(85 + r - r_u);
            wg_fence();
#pragma unroll
            for (int k = 0; k < 4; k++) wgmma_n112<1, H_SW, H_U>(a2, dA + s * 1024 + k * 128, dU + s * 896 + k * 16);
            wg_commit();
            wg_wait<1>();
            release(rel);
            rel = bar + 8 * (B_EMPTY + s);
        }
        uint32_t late = wg;
        asm volatile("" : "+r"(late));
        late = __shfl_sync(0xffffffffu, late, 0);
        gate_open(wg);
        mbar_wait(bar + 8 * B_UDONE, 0);
#pragma unroll 1
        for (uint32_t n = 0; n < late; n++) {
            bar_sync<4, 256>();
            wg_fence();
#pragma unroll
            for (int k = 0; k < 4 * NS2; k++) {
                const uint32_t s = g1 ? (33 - NS2 + k / 4) % 6 : (17 - NS2 + k / 4) % 6;
                wgmma_n112<1, H_SW, H_U>(a2, dA + s * 1024 + k % 4 * 128, dU + s * 896 + k % 4 * 16);
            }
            wg_commit();
        }
        {
            uint32_t ln = lane | (clock32() & (sb >> 31));
            const uint32_t un = warp * 2048 + (ln ^ ((ln >> 3) & 1)) * 16;
            const uint32_t rbuf = mapa(sb + OFF_RECV2, peer), rbar = mapa(bar + 8 * (B_RECV2 + wg), peer);
            uint32_t xr[4][4], u[4][4], sa[4];
#pragma unroll
            for (int i = 0; i < 4; i++) sa[i] = rbuf + (un ^ (i & 1) * 32) + i * 512;
            after((sa[0] | sa[1] | sa[2] | sa[3] | rbar) >> 31);
            wg_wait<0>();
            pin(a2);
            TSW(11);
            auto word = [&](int n, int h) { return pack2(a2[4 * n + 2 * h], a2[4 * n + 2 * h + 1]); };
            send4(sa[1], rbar, word(12, 0), word(13, 0), word(10, 0), word(11, 0), 1);
            send4(sa[3], rbar, word(10, 1), word(11, 1), word(12, 1), word(13, 1), 1);
            send4(sa[0], rbar, word(8, 0), word(9, 0), z ? word(0, 0) : word(8, 1), z ? word(1, 0) : word(9, 1), 1);
            send4(sa[2], rbar, word(0, 1), word(1, 1), word(8, 1), word(9, 1), z);
            const uint32_t nil = clock32() & (sb >> 31);
            const float one = __uint_as_float(0x3F800000u | nil);
#pragma unroll
            for (int i = 0; i < 32; i++) a2[i] = fmaf(a2[i], one, fb2[(i >> 1) & 1]);
#pragma unroll
            for (int i = 0; i < 4; i++) {
                const int n = i % 2 * 4 + (~i & 2), h = i / 2;
                asm volatile("st.shared.v4.b32 [%0], {%1,%2,%3,%4};" ::"r"(sb + OFF_OUT + (un ^ (i & 1) * 32) + i * 512), "r"(word(n, h)), "r"(word(n + 1, h)),
                             "r"(word(n ^ 2, h)), "r"(word(n ^ 3, h)) : "memory");
            }
            ln |= nil;
            const uint32_t la = sb + warp * 2048 + (ln & 1) * 512 + (ln & 6) * 32 + (((ln >> 3) ^ (ln >> 2 & 1) ^ (ln << 1)) & 3) * 16;
            const uint32_t lb = la - (z & ~ln) * 1024;
            const uint32_t lx = sb + OFF_A + slot(r_u + 14) * 16384 + (warp * 16 + (ln >> 3)) * 128 + (((ln ^ (ln >> 3)) & 7) << 4);
            uint8_t* o1 = out + ((q * 128 + warp * 16 + (ln >> 3)) * 896 + j * 224 + z * 96 + (ln & 7) * 16);
            uint8_t* o0 = o1 + (ln & 2 ? -32 : 32);
            auto add_x = [&]() {
#pragma unroll
                for (int i = 0; i < 16; i++) asm("add.rn.bf16x2 %0, %0, %1;" : "+r"(u[i >> 2][i & 3]) : "r"(xr[i >> 2][i & 3]));
            };
            __syncwarp();
#pragma unroll
            for (int i = 0; i < 4; i++) ldsm4(la + OFF_OUT + i / 2 * 1024 + i % 2 * 256, u[i]);
            mbar_wait(bar + 8 * B_XR, 0);
#pragma unroll
            for (int i = 0; i < 4; i++)
                asm volatile("ld.shared.v4.b32 {%0,%1,%2,%3}, [%4];" : "=r"(xr[i][0]), "=r"(xr[i][1]), "=r"(xr[i][2]), "=r"(xr[i][3])
                             : "r"((lx ^ (i % 2 * 64 + (~i & 2) * 16)) + i * 512) : "memory");
            add_x();
            mbar_wait(bar + 8 * (B_RECV2 + wg), (lb | (uint32_t)((uint64_t)o0 >> 32)) >> 31);
            TSW(12);
#pragma unroll
            for (int i = 0; i < 4; i++) ldsm4((i < 2 ? la : lb) + OFF_RECV2 + i / 2 * 1024 + i % 2 * 256, xr[i]);
            add_x();
#pragma unroll
            for (int i = 0; i < 4; i++)
                asm volatile("{\n.reg .pred p;\nsetp.ge.u32 p, %5, %6;\n@p st.global.v4.b32 [%0], {%1,%2,%3,%4};\n}"
                             ::"l"((i < 2 ? o0 : o1) + i * 3584), "r"(u[i][0]), "r"(u[i][1]), "r"(u[i][2]), "r"(u[i][3]), "r"((lane & 6) ^ (~i & 2)), "r"(z) : "memory");
        }
        TSW(13);
    } else if (warp < 12) {
        asm volatile("setmaxnreg.dec.sync.aligned.u32 64;");
        const int hw = warp - 8, t = tid & 127;
        reinterpret_cast<uint32_t*>(smem + OFF_ONES)[t] = t < 64 ? 0x3F803F80u : 0;
        fence_async_smem();
        bar_sync<12, 128>();
        while (clock32() - t_in < DLY1) {}
        uint8_t* cscell = scr + G_CS + ((P * 8 + R) * 2 + z) * 512 + (t >> 2) * 16;
        if ((lane & 3) == 0) cell_put(cscell, 0, 0, 0);
        uint8_t* cells = scr + G_HALO + ((R * 8 + P) * 2 + z) * 3584 + min(t, 111) * 16;
        cell_put(cells, 0, 0, 0);
        cell_put(cells + 1792, 0, 0, 0);
        const unsigned e1 = epoch();
        const uint32_t bv1 = ldg_u16(b1 + (g1 ? q * 128 : 0) + t), bv2 = ldg_u16(b2 + q * 128 + t);
        {
            const uint32_t da = desc_lo(OFF_B + min((R & 1) * 2 + z, 2) * 4096, 16), db = desc_lo(OFF_ONES, 128);
            float c0[4];
            mbar_wait(bar + 8 * B_FULLQ, 0);
            mbar_wait(bar + 8 * (B_FULLQ + 1), 0);
            TSH(47);
            wg_fence();
#pragma unroll
            for (int k = 0; k < 8; k++)
                wgmma_n8<1, H_SW, H_H>(c0, da + ((WSLOT >> (k & 4)) & 7) * 1536 + (k & 2) * 384 + (k & 1) * 128, db + (k >= 4 && R >= 6 ? 16 : 0), k);
            wg_commit();
            wg_wait<0>();
            pin(c0);
            if ((lane & 3) == 0) cell_put(cscell, __float_as_uint(c0[0]), __float_as_uint(c0[2]), e1);
            if (lane < 4) asm volatile("mbarrier.arrive.shared::cluster.b64 _, [%0];" ::"r"(mapa(bar + 8 * (B_EMPTYQ + (lane >> 1)), lane & 1)) : "memory");
            TSH(43);
        }
        mbar_wait(bar + 8 * (B_FULLQ + GATHER), 0);
        TSH(39);
        {
            const bool cw = hw < 3;
            const uint8_t* src = cw ? scr + G_CS + P * 8192 + t * 16 : scr + G_STATS + (z * 1024 + R * 128 + lane) * 16;
            uint32_t a[5], d[5], bad;
            do {
                bad = 0;
#pragma unroll
                for (int i = 0; i < 4; i++) bad |= cell_get(src + i * (cw ? 2048 : 512), a[i], d[i], e1);
                if (t >= 120) bad |= cell_get(src - (R ? 512 : 0), a[4], d[4], e1);
            } while (bad);
            TSH(45);
            if (cw) {
                uint4* cb = reinterpret_cast<uint4*>(smem + OFF_CSB) + (t >> 3) * 16 + (t & 7);
                const uint32_t lo = split2((__uint_as_float(a[0]) + __uint_as_float(a[1])) + (__uint_as_float(a[2]) + __uint_as_float(a[3])));
                const uint32_t hi = split2((__uint_as_float(d[0]) + __uint_as_float(d[1])) + (__uint_as_float(d[2]) + __uint_as_float(d[3])));
                cb[0] = make_uint4(lo, lo, 0, 0);
                cb[8] = make_uint4(hi, hi, 0, 0);
            } else {
                uint2* st = reinterpret_cast<uint2*>(smem + OFF_STATS) + lane;
                uint32_t* rd = reinterpret_cast<uint32_t*>(smem + OFF_RSTD) + lane;
#pragma unroll
                for (int i = 0; i < 4; i++) { st[32 * i] = make_uint2(a[i], d[i]); rd[8 + 32 * i] = a[i]; }
                if (t >= 120) rd[-24] = a[4];
            }
            fence_async_smem();
            __syncwarp();
            mbar_arrive_if0(bar + 8 * B_AUX, lane);
            TSH(41);
            reinterpret_cast<float2*>(smem + OFF_BIAS)[t] = make_float2(0.5f * bf_lo(bv1), bf_lo(bv2));
            __syncwarp();
            mbar_arrive_if0(bar + 8 * B_KV, lane);
        }
        {
            uint2* kv = reinterpret_cast<uint2*>(smem + OFF_K) + min(t, 111);
            mbar_wait(bar + 8 * B_QKV, 0);
            uint2 k2 = kv[896], v2 = kv[1792 + (OFF_V - OFF_K) / 8];
            cell_put(cells, k2.x, k2.y, e1);
            cell_put(cells + 1792, v2.x, v2.y, e1);
            k2 = v2 = make_uint2(0, 0);
            delay(DH);
            if (R > 0) while (cell_get(cells - 16 * 3584, k2.x, k2.y, e1) | cell_get(cells - 16 * 3584 + 1792, v2.x, v2.y, e1)) {}
            kv[0] = k2;
            kv[(OFF_V - OFF_K) / 8] = v2;
            mbar_wait(bar + 8 * B_KV, 0);
            __syncwarp();
            mbar_arrive_if0(bar + 8 * B_HALO, lane);
            TSH(40);
        }
        if (hw == 3) {
            mbar_wait(bar + 8 * B_OST, 0);
            if (elect()) {
                unsigned* oc = ctr + C_O + (R * 2 + (P >> 2)) * 32;
                TS(38);
                fence_async_smem();
                TS(46);
                tma2d_store(&mp.ost, sb + OFF_OST, z * 64, P * 1024 + R * 128);
                bulk_commit();
                TS(7);
                asm volatile("mbarrier.arrive.relaxed.cluster.shared::cluster.b64 _, [%0];" ::"r"(mapa(bar + 8 * B_FREE, z ^ 1)) : "memory");
                delay(DO);
                red_relaxed(oc, 1);
                TS(21);
                mbar_wait(bar + 8 * B_LNIN, 0);
                bulk_wait_read();
                mbar_arrive(bar + 8 * B_LNFREE);
                TS(20);
                mbar_wait(bar + 8 * (B_EMPTY + 6), 0);
                asm volatile("mbarrier.arrive.relaxed.cluster.shared::cluster.b64 _, [%0];" ::"r"(mapa(bar + 8 * B_UDONE, z ^ 1)) : "memory");
            }
        } else {
            const uint32_t tag = e1 & 0x3FFF;
            const uint32_t ca = sb + OFF_A + lane * 128 + ((~lane & 7) << 4) + (lane >> 3) * 4, cb = sb + OFF_B + lane * 132;
            uint32_t par = 0x7F;
#pragma unroll 1
            for (uint32_t i = hw ? 3 - hw : 0; i < 18;) {
                const uint32_t s = xslot(i);
                const bool isa = i < 4;
                const uint32_t a0 = isa ? ca + aoff(s) : cb + s * BLK, a3 = a0 - (isa ? 0 : (lane & 16) * 132);
                mbar_wait(bar + 8 * (B_LAND + s), (par >> s) & 1);
                par ^= 1 << s;
                bool ok = true;
#pragma unroll
                for (int k = 0; k < 4; k++) {
                    uint32_t v;
                    asm volatile("ld.shared.b32 %0, [%1];" : "=r"(v) : "r"((k < 3 ? a0 : a3) + k * 4096) : "memory");
                    ok &= (v == (isa ? tag : ~0u)) == isa;
                }
                const uint32_t bad = __ballot_sync(0xffffffffu, !ok);
                mbar_arrive_if0(bar + 8 * (B_FULL + s), lane | bad);
                if (!bad) {
                    if (i == 0 || i == 4) TS(i ? 30 : 29);
                    i += i < 1 ? 4 : i == 1 ? 2 : 3;
                } else if (elect()) {
                    TS(31);
                    fetch_x(i);
                }
            }
        }
    } else {
        asm volatile("setmaxnreg.dec.sync.aligned.u32 32;");
        auto wait_free = [&](uint32_t r, uint32_t first) {
            const uint32_t a = r < 6 ? B_EMPTYQ + ((first >> (4 * r)) & 7) : B_EMPTY + slot(r);
            mbar_wait(bar + 8 * a, r < 6 ? 0 : phase(r) ^ 1);
        };
        if (warp == 12) {
            TS(14);
            if (elect()) {
#pragma unroll 1
                for (int kb = 1; kb < 7; kb++) {
                    if (kb == 1) while (clock32() - t_in < DLY2) {}
                    if (kb >= QDEPTH) { mbar_wait(bar + 8 * (B_FULLQ + kb - QDEPTH), 0); TS(25 + kb - QDEPTH); }
                    if (kb >= 5) mbar_wait(bar + 8 * (B_EMPTYQ + kb - 5), 0);
                    x_load(kb);
                    w_load(kb);
                }
                TS(17);
                mbar_wait(bar + 8 * B_LNFREE, 0);
                if (!g1) {
                    const int ic = (q - 14) * 8 + j * 2 + z, rot = ic >> 3;
                    mbar_wait(bar + 8 * (B_EMPTYQ + 2), 0);
                    mbar_expect(bar + 8 * B_GO, 2 * BLK);
#pragma unroll 1
                    for (int i = 0; i < 2; i++) tma4d(sb + OFF_A + i * BLK, &mp.wo, 0, 0, (z * 2 + i) * 14, ic >> 1, bar + 8 * B_GO);
                    mbar_wait(bar + 8 * B_GO, 0);
#pragma unroll 1
                    for (int i = 0; i < 2; i++) {
                        uint8_t* dst = scr + G_BIMG + (ic * 2 + i) * BLK;
                        bulk_store(dst, sb + OFF_A + i * BLK, 2048);
                        bulk_store(dst + 2048 + rot * 6144, sb + OFF_A + i * BLK + 2048, 6144);
                        bulk_store(dst + 8192 - rot * 6144, sb + OFF_A + i * BLK + 8192, 6144);
                    }
                    bulk_commit();
                    bulk_wait_all();
                    publish(ctr + C_WO);
                    TS(44);
                }
#pragma unroll 1
                for (uint32_t r = 0; r < r_o; r++) {
                    const uint32_t s = slot(r), fb = bar + 8 * (B_FULL + s);
                    wait_free(r, 0x654320u);
                    mbar_expect(fb, 16384);
                    tma3d(sb + OFF_A + s * 16384, &mp.w1, 0, z * 1024 + r * 64, 2 * q, fb);
                    TS(99 + r);
                }
                mbar_wait(bar + 8 * B_OST, 0);
                mbar_expect(bar + 8 * (B_LAND + 6), 16384);
                wait_free(r_o, 0x654320u);
                mbar_expect(bar + 8 * (B_LAND + slot(r_o)), 16384);
                poll(ctr + C_O + ((q & ~1) + z) * 32, epoch() * 8);
                TS(32);
                fetch_x(0, false);
                mbar_wait(bar + 8 * B_LNFREE, 1);
                fetch_x(1, false);
                TS(99 + 17);
#pragma unroll 1
                for (uint32_t i = 1; i < 3; i++) {
                    wait_free(r_o + i, 0x654320u);
                    fetch_x(i + 1);
                }
                TS(99 + 20);
#pragma unroll 1
                for (uint32_t i = 0; i < 14; i++) {
                    const uint32_t r = r_u + i, s = slot(r), fb = bar + 8 * (B_FULL + s);
                    wait_free(r, 0x654320u);
                    mbar_expect(fb, 16384);
                    tma3d(sb + OFF_A + s * 16384, &mp.w2, 0, (14 * z + (i < 7 ? 2 * i : 2 * i - 13)) * 64, 2 * q, fb);
                    TS(99 + 21 + i);
                }
                wait_free(r_u + 14, 0);
                mbar_expect(bar + 8 * B_XR, 16384);
                tma2d(sb + OFF_A + slot(r_u + 14) * 16384, &mp.xn, j * 112 + z * 48, q * 128, bar + 8 * B_XR);
            }
        } else if (warp == 13) {
            if (elect()) {
#pragma unroll 1
                for (int ph = g1 ? 0 : 1; ph < 4; ph++) {
                    const uint8_t* src = ph == 0 ? scr + G_HIMG + (64 * z + j) * BLK : scr + G_BIMG + ((ph == 1 ? 4 * z : 6 + 14 * z + ph) * 4 + j) * BLK;
                    const uint32_t r0 = ph == 0 ? 0 : r_o + (ph == 1 ? 0 : 7 * ph - 11), r1 = r_o + (ph == 0 ? 0 : 7 * ph - 4);
                    if (ph == 1) {
                        mbar_wait(bar + 8 * B_OST, 0);
                        mbar_expect(bar + 8 * (B_FULL + 6), BLK);
                        mbar_wait(bar + 8 * (B_GO + 1), 0);
                        bulk_load(sb + OFF_SB, src + 4 * BLK, BLK, bar + 8 * (B_FULL + 6));
                    }
#pragma unroll 1
                    for (uint32_t r = r0; r < r1; r++, src += r <= r_o || r == r_o + 2 ? 4 * BLK : 8 * BLK) {
                        const uint32_t s = slot(r), fb = bar + 8 * ((ph < 2 ? B_FULL : B_LAND) + s);
                        wait_free(r, 0x644332u);
                        mbar_expect(fb, BLK);
                        if (ph == 0) {
                            if (r == 0) {
                                poll(ctr + C_LN, epoch() * 128);
                                fence_async_global();
                                TS(33);
                            }
                        } else mbar_wait(bar + 8 * (B_GO + ph), 0);
                        bulk_load(sb + OFF_B + s * BLK, src, BLK, fb);
                        TS(134 + 16 + 2 * (ph > 0) + r - r_o);
                    }
                }
            }
        } else if (warp == 14) {
            uint8_t* stcell = scr + G_STATS + ((lane & 1) * 1024 + 8 * b + (lane >> 1)) * 16;
            if (lane < 16) cell_put(stcell, 0, 0, 0);
            const unsigned ev = ld_relaxed(ctr + C_LN);
            uint8_t* hb = scr + G_HIMG + (b & ~3) * BLK;
            const unsigned e1 = (ev >> 7) + 1;
            if (lane == 0) {
                *reinterpret_cast<volatile unsigned*>(smem + OFF_EP) = e1;
                mbar_arrive(bar + 8 * B_EP);
                TS(36);
            }
            bar_sync<10, 288>();
            if (elect()) {
                fence_async_smem();
                TS(42);
                tma4d_store(&mp.hst, sb + OFF_A, 0, 0, b & 3, b & ~3);
                bulk_commit();
            }
            __syncwarp();
            if (lane < 16) {
                const uint2 v = reinterpret_cast<const uint2*>(smem + OFF_LNST)[lane];
                cell_put(stcell, v.x, v.y, e1);
            }
            const uint8_t* hl = hb + ((b & 3) * 28 + min(lane, 27)) * 128;
            mbar_wait(bar + 8 * B_LNIN, (uint64_t)hl >> 63);
            bulk_wait_all();
            __syncwarp();
            mbar_arrive_if0(bar + 8 * B_LNFREE, lane);
            TS(63);
            unsigned rb = 0;
#pragma unroll
            for (int i = 0; i < 4; i++) rb |= ld_relaxed(reinterpret_cast<const unsigned*>(hl + i * BLK));
            if (elect()) {
                red_relaxed(ctr + C_LN, 1 + (rb & (sb >> 31)));
                TS(37);
#pragma unroll 1
                for (int ph = 1; ph < 4; ph++) {
                    mbar_wait(bar + 8 * (ph == 1 ? B_HALO : g1 ? B_RECV1 : B_OST), 0);
                    poll(ctr + ph * 32 + (ph >> 1) * z * 64, e1 * (ph == 1 ? 16 : 56));
                    fence_async_global();
                    mbar_arrive(bar + 8 * (B_GO + ph));
                    if (ph != 1) TS(32 + ph);
                }
            }
        } else {
            if ((sb & 0x3FFFF) != SB0) __trap();
            if (elect()) {
#pragma unroll 1
                for (int i = 3; i < 10; i++) asm volatile("prefetch.tensormap [%0];" ::"l"(reinterpret_cast<const CUtensorMap*>(&mp) + i) : "memory");
            }
            __syncwarp();
            mbar_watch(bar + 8 * B_KV, 0);
#pragma unroll 1
            for (int i = g1 ? 0 : 8; i < 8; i++) {
                uint32_t l = 56 * z + (i & 3) * 14 + min(lane >> 1, 13);
                if (q >= 7 && l >= 16) l += l < 64 ? 48 : -48;
                cell_put(scr + G_BIMG + ((8 + 2 * q + (i >> 2)) * 4 + j) * BLK + l * 128 + (l & 24) * 4 + (lane & 1) * 16, ~0u, ~0u, ~0u);
            }
            __threadfence();
            __syncwarp();
            mbar_arrive_if0(bar + 8 * B_FREE, lane);
            TS(59);
#pragma unroll 1
            for (int i = g1 ? 0 : 2; i < 2; i++) {
                mbar_watch(bar + 8 * (B_RECV1 + i), 0);
                delay(DU);
                if (lane == 0) red_relaxed(ctr + C_U + ((q >= 7 ? 2 : 0) + i) * 32, 1);
                TS(22 + i);
            }
            mbar_watch(bar + 8 * B_FREE, 0);
            mbar_watch(bar + 8 * B_RECV2, 0);
            mbar_watch(bar + 8 * (B_RECV2 + 1), 0);
        }
    }
}

typedef CUresult (*EncodeFn)(CUtensorMap*, CUtensorMapDataType, cuuint32_t, void*, const cuuint64_t*, const cuuint64_t*, const cuuint32_t*,
                             const cuuint32_t*, CUtensorMapInterleave, CUtensorMapSwizzle, CUtensorMapL2promotion, CUtensorMapFloatOOBfill);

void encode(EncodeFn fn, CUtensorMap* m, const void* p, int rank, const cuuint64_t* dims, const cuuint64_t* strides, const cuuint32_t* box, bool swz) {
    const cuuint32_t es[4] = {1, 1, 1, 1};
    fn(m, CU_TENSOR_MAP_DATA_TYPE_BFLOAT16, rank, const_cast<void*>(p), dims, strides, box, es, CU_TENSOR_MAP_INTERLEAVE_NONE,
       swz ? CU_TENSOR_MAP_SWIZZLE_128B : CU_TENSOR_MAP_SWIZZLE_NONE, CU_TENSOR_MAP_L2_PROMOTION_L2_128B, CU_TENSOR_MAP_FLOAT_OOB_FILL_NONE);
}

}

extern "C" void kernel_launch(void* const* d_in, const int* in_sizes, int n_in, void* d_out, int out_size) {
    const __nv_bfloat16* x = (const __nv_bfloat16*)d_in[0];
    const __nv_bfloat16* wqkv = (const __nv_bfloat16*)d_in[1];
    const __nv_bfloat16* wo = (const __nv_bfloat16*)d_in[2];
    const __nv_bfloat16* w1 = (const __nv_bfloat16*)d_in[4];
    const __nv_bfloat16* b1 = (const __nv_bfloat16*)d_in[5];
    const __nv_bfloat16* w2 = (const __nv_bfloat16*)d_in[6];
    const __nv_bfloat16* b2 = (const __nv_bfloat16*)d_in[7];

    void* fp = nullptr;
    cudaDriverEntryPointQueryResult qr;
    cudaGetDriverEntryPoint("cuTensorMapEncodeTiled", &fp, cudaEnableDefault, &qr);
    EncodeFn fn = (EncodeFn)fp;
    void* sp = nullptr;
    cudaGetSymbolAddress(&sp, g_scratch);
    uint8_t* scr = (uint8_t*)sp;
    void *o = scr + G_O, *himg = scr + G_HIMG;

    Maps mp;
    { cuuint64_t d[3] = {64, 2048, 7}, s[2] = {896, 128}; cuuint32_t bx[3] = {64, 16, 7}; encode(fn, &mp.xl, x, 3, d, s, bx, true); }
    { cuuint64_t d[2] = {896, 1024}, s[1] = {1792}; cuuint32_t bx[2] = {64, 128}; encode(fn, &mp.x, x, 2, d, s, bx, true); }
    { cuuint64_t d[3] = {448, 448, 3}, s[2] = {2688, 896}; cuuint32_t bx[3] = {64, 32, 3}; encode(fn, &mp.wqkv, wqkv, 3, d, s, bx, true); }
    { cuuint64_t d[3] = {64, 2048, 28}, s[2] = {3584, 128}; cuuint32_t bx[3] = {64, 64, 2}; encode(fn, &mp.w1, w1, 3, d, s, bx, true); }
    { cuuint64_t d[3] = {64, 1792, 32}, s[2] = {4096, 128}; cuuint32_t bx[3] = {64, 64, 2}; encode(fn, &mp.w2, w2, 3, d, s, bx, true); }
    { cuuint64_t d[4] = {64, 28, 4, 128}, s[3] = {128, 3584, BLK}; cuuint32_t bx[4] = {64, 28, 1, 4}; encode(fn, &mp.hst, himg, 4, d, s, bx, false); }
    { cuuint64_t d[2] = {448, 2048}, s[1] = {896}; cuuint32_t bx[2] = {64, 128}; encode(fn, &mp.xn, x, 2, d, s, bx, true); }
    { cuuint64_t d[2] = {64, 8 * 2048}, s[1] = {128}; cuuint32_t bx[2] = {64, 128}; encode(fn, &mp.old_, o, 2, d, s, bx, true); }
    { cuuint64_t d[2] = {128, 8 * 1024}, s[1] = {256}; cuuint32_t bx[2] = {64, 128}; encode(fn, &mp.ost, o, 2, d, s, bx, true); }
    { cuuint64_t d[4] = {8, 56, 56, 8}, s[3] = {896, 16, 56 * 896}; cuuint32_t bx[4] = {8, 64, 14, 1}; encode(fn, &mp.wo, wo, 4, d, s, bx, false); }

    cudaFuncSetAttribute(fused_kernel, cudaFuncAttributeMaxDynamicSharedMemorySize, SMEM_BYTES);
    fused_kernel<<<128, 512, SMEM_BYTES>>>(x, b1, b2, scr, (uint8_t*)d_out, mp);
}
```

```cpp
#include <cuda_runtime.h>
#include <cuda.h>
#include <cuda_bf16.h>
#include <stdint.h>

namespace {

constexpr int S_ = 2048, D_ = 448;
constexpr uint32_t BLK = 14336;

constexpr uint32_t G_HIMG = 0;
constexpr uint32_t G_BIMG = G_HIMG + 32 * 4 * BLK;
constexpr uint32_t G_O = G_BIMG + 36 * 4 * BLK;
constexpr uint32_t G_STATS = G_O + 8 * S_ * 128;
constexpr uint32_t G_CS = G_STATS + S_ * 16;
constexpr uint32_t G_HALO = G_CS + 8 * 4 * 2048;
constexpr uint32_t G_CTR = G_HALO + 128 * 3584;
constexpr uint32_t G_END = G_CTR + (192 + 16 * 32) * 4;
__device__ __align__(1024) uint8_t g_scratch[G_END];

constexpr int C_LN = 0, C_WO = 32, C_U = 64, C_O = 192;

#define TSX(sel, id)
#define TS(id)
#define TS0(id)
#define TSH(id)
#define TSW(id)
#define TG(id)

#define TSG1 0
#define TSD(id)
constexpr int QDEPTH = 3;
constexpr int KS = 3;
constexpr int GATHER = 4;
constexpr uint32_t NE = 2;
constexpr uint32_t PRE0 = 9, PRE1 = 6;
constexpr uint32_t ATT_STEP = 10, GS = 12;
constexpr int NS2 = 3;
constexpr uint32_t DLY1 = 2200, DLY2 = 1600, DH = 400, DO = 100, DU = 120;

constexpr uint32_t OFF_A = 0;
constexpr uint32_t OFF_B = 98304;
constexpr uint32_t OFF_X = 184320;
constexpr uint32_t OFF_K = 196608;
constexpr uint32_t OFF_V = OFF_K + 9 * 896;
constexpr uint32_t OFF_OST = OFF_X, OFF_RECV2 = OFF_X, OFF_RECV1 = OFF_X + 16384, OFF_OUT = OFF_X + 16384;
constexpr uint32_t OFF_SA = OFF_X, OFF_SB = OFF_RECV1 + BLK;
constexpr uint32_t OFF_CSB = 221184;
constexpr uint32_t OFF_ONES = OFF_CSB + 3072;
constexpr uint32_t OFF_STATS = OFF_ONES + 512;
constexpr uint32_t OFF_BIAS = OFF_STATS + 1024;
constexpr uint32_t OFF_LNX = OFF_BIAS + 1024;
constexpr uint32_t OFF_RSTD = OFF_LNX + 512;
constexpr uint32_t OFF_LNST = 229376;
constexpr uint32_t OFF_EP = OFF_LNST + 128;
constexpr uint32_t OFF_BAR = OFF_EP + 16;
constexpr uint32_t OFF_TS = OFF_BAR + 8 * 48;
constexpr uint32_t SMEM_BYTES = OFF_TS;

enum : int {
    B_FULLQ = 0, B_LNIN = 7, B_EMPTYQ = 8, B_FULL = 15, B_EMPTY = 22, B_AUX = 29, B_QKV, B_HALO, B_FREE, B_RECV1, B_RECV2 = B_RECV1 + 2,
    B_EP = B_RECV2 + 2, B_OST, B_LNFREE, B_UDONE, B_NONE, B_GO, B_XR = B_GO + 4, B_KV, B_COUNT, B_LAND = B_FULLQ
};
constexpr uint32_t XSLOT = 0x5432154u;
constexpr uint32_t WSLOT = 0x3421034u;

__device__ __forceinline__ uint32_t smem_u32(const void* p) { return (uint32_t)__cvta_generic_to_shared(p); }
__device__ __forceinline__ void mbar_init(uint32_t a, int c) { asm volatile("mbarrier.init.shared::cta.b64 [%0], %1;" ::"r"(a), "r"(c) : "memory"); }
__device__ __forceinline__ void mbar_expect(uint32_t a, uint32_t b) { asm volatile("mbarrier.arrive.expect_tx.shared::cta.b64 _, [%0], %1;" ::"r"(a), "r"(b) : "memory"); }
__device__ __forceinline__ void mbar_arrive(uint32_t a) { asm volatile("mbarrier.arrive.shared::cta.b64 _, [%0];" ::"r"(a) : "memory"); }
__device__ __forceinline__ void mbar_arrive_if0(uint32_t a, uint32_t sel) {
    asm volatile("{\n.reg .pred p;\nsetp.eq.u32 p, %1, 0;\n@p mbarrier.arrive.shared::cta.b64 _, [%0];\n}" ::"r"(a), "r"(sel) : "memory");
}
__device__ __forceinline__ void mbar_wait(uint32_t a, uint32_t parity) {
    asm volatile("{\n.reg .pred p;\nW0:\nmbarrier.try_wait.parity.shared::cta.b64 p, [%0], %1;\n@!p bra W0;\n}\n" ::"r"(a), "r"(parity) : "memory");
}
__device__ __forceinline__ void mbar_watch(uint32_t a, uint32_t parity) {
    asm volatile(
        "{\n.reg .pred p;\n.reg .u32 n;\nmov.u32 n, 0;\n"
        "W0:\nmbarrier.try_wait.parity.shared::cta.b64 p, [%0], %1;\n@p bra W1;\n"
        "add.u32 n, n, 1;\nsetp.lt.u32 p, n, 1048576;\n@p bra W0;\ntrap;\nW1:\n}\n" ::"r"(a), "r"(parity) : "memory");
}
__device__ __forceinline__ bool elect() {
    uint32_t r;
    asm volatile("{\n.reg .pred p;\nelect.sync _|p, 0xffffffff;\nselp.u32 %0, 1, 0, p;\n}" : "=r"(r));
    return r;
}
__device__ __forceinline__ uint32_t mapa(uint32_t a, uint32_t cta) { uint32_t r; asm("mapa.shared::cluster.u32 %0, %1, %2;" : "=r"(r) : "r"(a), "r"(cta)); return r; }
__device__ __forceinline__ void tma2d(uint32_t dst, const CUtensorMap* m, int c0, int c1, uint32_t bar) {
    asm volatile("cp.async.bulk.tensor.2d.shared::cluster.global.mbarrier::complete_tx::bytes [%0], [%1, {%3, %4}], [%2];" ::"r"(dst), "l"(m), "r"(bar), "r"(c0), "r"(c1) : "memory");
}
__device__ __forceinline__ void tma3d(uint32_t dst, const CUtensorMap* m, int c0, int c1, int c2, uint32_t bar) {
    asm volatile("cp.async.bulk.tensor.3d.shared::cluster.global.mbarrier::complete_tx::bytes [%0], [%1, {%3, %4, %5}], [%2];" ::"r"(dst), "l"(m), "r"(bar), "r"(c0), "r"(c1), "r"(c2) : "memory");
}
__device__ __forceinline__ void tma3d_mc(uint32_t dst, const CUtensorMap* m, int c0, int c1, int c2, uint32_t bar) {
    asm volatile("cp.async.bulk.tensor.3d.shared::cluster.global.mbarrier::complete_tx::bytes.multicast::cluster [%0], [%1, {%3, %4, %5}], [%2], %6;"
                 ::"r"(dst), "l"(m), "r"(bar), "r"(c0), "r"(c1), "r"(c2), "h"((uint16_t)3) : "memory");
}
__device__ __forceinline__ void tma2d_store(const CUtensorMap* m, uint32_t src, int c0, int c1) {
    asm volatile("cp.async.bulk.tensor.2d.global.shared::cta.bulk_group [%0, {%2, %3}], [%1];" ::"l"(m), "r"(src), "r"(c0), "r"(c1) : "memory");
}
__device__ __forceinline__ void tma4d_store(const CUtensorMap* m, uint32_t src, int c0, int c1, int c2, int c3) {
    asm volatile("cp.async.bulk.tensor.4d.global.shared::cta.bulk_group [%0, {%2, %3, %4, %5}], [%1];" ::"l"(m), "r"(src), "r"(c0), "r"(c1), "r"(c2), "r"(c3) : "memory");
}
__device__ __forceinline__ void tma4d(uint32_t dst, const CUtensorMap* m, int c0, int c1, int c2, int c3, uint32_t bar) {
    asm volatile("cp.async.bulk.tensor.4d.shared::cluster.global.mbarrier::complete_tx::bytes [%0], [%1, {%3, %4, %5, %6}], [%2];" ::"r"(dst), "l"(m), "r"(bar), "r"(c0), "r"(c1), "r"(c2), "r"(c3) : "memory");
}
__device__ __forceinline__ void bulk_load(uint32_t dst, const void* src, uint32_t bytes, uint32_t bar) {
    asm volatile("cp.async.bulk.shared::cluster.global.mbarrier::complete_tx::bytes [%0], [%1], %2, [%3];" ::"r"(dst), "l"(src), "r"(bytes), "r"(bar) : "memory");
}
__device__ __forceinline__ void bulk_store(void* dst, uint32_t src, uint32_t bytes) {
    asm volatile("cp.async.bulk.global.shared::cta.bulk_group [%0], [%1], %2;" ::"l"(dst), "r"(src), "r"(bytes) : "memory");
}
__device__ __forceinline__ void bulk_commit() { asm volatile("cp.async.bulk.commit_group;" ::: "memory"); }
__device__ __forceinline__ void bulk_wait_all() { asm volatile("cp.async.bulk.wait_group 0;" ::: "memory"); }
template <int N> __device__ __forceinline__ void bulk_wait_read() { asm volatile("cp.async.bulk.wait_group.read %0;" ::"n"(N) : "memory"); }
__device__ __forceinline__ void l2_prefetch(const void* p) { asm volatile("prefetch.global.L2 [%0];" ::"l"(p)); }
__device__ __forceinline__ void fence_async_smem() { asm volatile("fence.proxy.async.shared::cta;" ::: "memory"); }
__device__ __forceinline__ void fence_async_global() { asm volatile("fence.proxy.async.global;" ::: "memory"); }
__device__ __forceinline__ void red_relaxed(unsigned* p, unsigned v) { asm volatile("red.relaxed.gpu.global.add.u32 [%0], %1;" ::"l"(p), "r"(v) : "memory"); }
__device__ __forceinline__ void publish(unsigned* p) {
    asm volatile("fence.proxy.async.global;\nred.release.gpu.global.add.u32 [%0], 1;" ::"l"(p) : "memory");
}
__device__ __forceinline__ void stg32(void* p, uint32_t v) { asm volatile("st.global.b32 [%0], %1;" ::"l"(p), "r"(v) : "memory"); }
__device__ __forceinline__ unsigned ld_relaxed(const unsigned* p) { unsigned v; asm volatile("ld.relaxed.gpu.global.u32 %0, [%1];" : "=r"(v) : "l"(p) : "memory"); return v; }
__device__ __forceinline__ bool ctr_done(unsigned v, unsigned target) { return ((v - target) & 0x1FFFFFFu) == 0; }
__device__ __forceinline__ uint32_t clock32() { uint32_t c; asm volatile("mov.u32 %0, %%clock;" : "=r"(c)::"memory"); return c; }
__device__ __forceinline__ void delay(uint32_t n) { const uint32_t t0 = clock32(); while (clock32() - t0 < n) {} }
__device__ __forceinline__ void poll(const unsigned* p, unsigned target) { while (!ctr_done(ld_relaxed(p), target)) {} }
__device__ __forceinline__ void cell_put(void* p, uint32_t a, uint32_t b, uint32_t tag) {
    asm volatile("st.relaxed.gpu.global.v4.b32 [%0], {%1, %3, %2, %3};" ::"l"(p), "r"(a), "r"(b), "r"(tag) : "memory");
}
__device__ __forceinline__ uint32_t cell_get(const void* p, uint32_t& a, uint32_t& b, uint32_t tag) {
    uint32_t t0, t1;
    asm volatile("ld.relaxed.gpu.global.v4.b32 {%0, %1, %2, %3}, [%4];" : "=r"(a), "=r"(t0), "=r"(b), "=r"(t1) : "l"(p) : "memory");
    return (t0 ^ tag) | (t1 ^ tag);
}
__device__ __forceinline__ void after(uint32_t zero) { asm volatile("{\n.reg .pred p;\nsetp.ne.u32 p, %0, 0;\n@p trap;\n}" ::"r"(zero) : "memory"); }
template <int ID, int N> __device__ __forceinline__ void bar_sync() { asm volatile("bar.sync %0, %1;" ::"n"(ID), "n"(N) : "memory"); }
template <int ID = 4> __device__ __forceinline__ void gate_wait(uint32_t on) { asm volatile("{\n.reg .pred p;\nsetp.ne.u32 p, %0, 0;\n@p bar.sync %1, 256;\n}" ::"r"(on), "n"(ID) : "memory"); }
template <int ID = 4> __device__ __forceinline__ void gate_open(uint32_t off) { asm volatile("{\n.reg .pred p;\nsetp.eq.u32 p, %0, 0;\n@p bar.arrive %1, 256;\n}" ::"r"(off), "n"(ID) : "memory"); }
__device__ __forceinline__ void wg_fence() { asm volatile("wgmma.fence.sync.aligned;" ::: "memory"); }
__device__ __forceinline__ void wg_commit() { asm volatile("wgmma.commit_group.sync.aligned;" ::: "memory"); }
template <int N> __device__ __forceinline__ void wg_wait() { asm volatile("wgmma.wait_group.sync.aligned %0;" ::"n"(N) : "memory"); }
template <int LO = 0, int HI = 56, int N> __device__ __forceinline__ void pin(float (&a)[N]) {
#pragma unroll
    for (int i = LO; i < (HI < N ? HI : N); i++) asm volatile("" : "+f"(a[i])::"memory");
}
__device__ __forceinline__ uint32_t ldg_u16(const void* p) {
    uint32_t v;
    asm volatile("ld.global.nc.u16 %0, [%1];" : "=r"(v) : "l"(p) : "memory");
    return v;
}
__device__ __forceinline__ uint32_t pack2(float lo, float hi) { uint32_t r; asm("cvt.rn.bf16x2.f32 %0, %1, %2;" : "=r"(r) : "f"(hi), "f"(lo)); return r; }
__device__ __forceinline__ float bf_lo(uint32_t v) { return __uint_as_float(v << 16); }
__device__ __forceinline__ float bf_hi(uint32_t v) { return __uint_as_float(v & 0xFFFF0000u); }
__device__ __forceinline__ uint32_t split2(float x) { return pack2(x, x - bf_lo(pack2(x, 0.f))); }
__device__ __forceinline__ void stsm4(uint32_t a, uint32_t r0, uint32_t r1, uint32_t r2, uint32_t r3) {
    asm volatile("stmatrix.sync.aligned.m8n8.x4.shared.b16 [%0], {%1, %2, %3, %4};" ::"r"(a), "r"(r0), "r"(r1), "r"(r2), "r"(r3) : "memory");
}
__device__ __forceinline__ void stsm2(uint32_t a, uint32_t r0, uint32_t r1) {
    asm volatile("stmatrix.sync.aligned.m8n8.x2.shared.b16 [%0], {%1, %2};" ::"r"(a), "r"(r0), "r"(r1) : "memory");
}
__device__ __forceinline__ void ldsm4(uint32_t a, uint32_t (&r)[4]) {
    asm volatile("ldmatrix.sync.aligned.m8n8.x4.shared.b16 {%0, %1, %2, %3}, [%4];" : "=r"(r[0]), "=r"(r[1]), "=r"(r[2]), "=r"(r[3]) : "r"(a) : "memory");
}
__device__ __forceinline__ void ldsm4t(uint32_t a, uint32_t (&r)[4]) {
    asm volatile("ldmatrix.sync.aligned.m8n8.x4.trans.shared.b16 {%0, %1, %2, %3}, [%4];" : "=r"(r[0]), "=r"(r[1]), "=r"(r[2]), "=r"(r[3]) : "r"(a) : "memory");
}
__device__ __forceinline__ void mma16816(float (&c)[4], uint32_t a0, uint32_t a1, uint32_t a2, uint32_t a3, uint32_t b0, uint32_t b1) {
    asm volatile("mma.sync.aligned.m16n8k16.row.col.f32.bf16.bf16.f32 {%0,%1,%2,%3}, {%4,%5,%6,%7}, {%8,%9}, {%0,%1,%2,%3};"
                 : "+f"(c[0]), "+f"(c[1]), "+f"(c[2]), "+f"(c[3]) : "r"(a0), "r"(a1), "r"(a2), "r"(a3), "r"(b0), "r"(b1));
}
__device__ __forceinline__ void mma1688(float (&c)[4], uint32_t a0, uint32_t a1, uint32_t b0) {
    asm volatile("mma.sync.aligned.m16n8k8.row.col.f32.bf16.bf16.f32 {%0,%1,%2,%3}, {%4,%5}, {%6}, {%0,%1,%2,%3};"
                 : "+f"(c[0]), "+f"(c[1]), "+f"(c[2]), "+f"(c[3]) : "r"(a0), "r"(a1), "r"(b0));
}
constexpr uint32_t SB0 = 1024;
__device__ __forceinline__ uint32_t desc_lo(uint32_t off, uint32_t lbo) { return ((SB0 + off) >> 4) + ((lbo >> 4) << 16); }
constexpr uint32_t H_SW = (1024 >> 4) | (1u << 30), H_H = 128 >> 4, H_U = 1024 >> 4;
__device__ __forceinline__ float ex2(float x) { float r; asm("ex2.approx.ftz.f32 %0, %1;" : "=f"(r) : "f"(x)); return r; }
__device__ __forceinline__ float rsq(float x) { float r; asm("rsqrt.approx.ftz.f32 %0, %1;" : "=f"(r) : "f"(x)); return r; }
__device__ __forceinline__ float rcp(float x) { float r; asm("rcp.approx.ftz.f32 %0, %1;" : "=f"(r) : "f"(x)); return r; }

template <uint32_t HB, int TB>
__device__ __forceinline__ void wgmma_n56_rs(float (&d)[28], const uint32_t (&a)[4], uint32_t lb, int scale_d) {
    asm volatile("{\n.reg .pred p;\n.reg .b64 db;\nsetp.ne.b32 p, %33, 0;\nmov.b64 db, {%32, %34};\n"
        "wgmma.mma_async.sync.aligned.m64n56k16.f32.bf16.bf16 "
        "{%0, %1, %2, %3, %4, %5, %6, %7, %8, %9, %10, %11, %12, %13, %14, %15, %16, %17, %18, %19, %20, %21, %22, %23, %24, %25, %26, %27}, "
        "{%28, %29, %30, %31}, db, p, 1, 1, %35;\n}\n"
        : "+f"(d[0]), "+f"(d[1]), "+f"(d[2]), "+f"(d[3]), "+f"(d[4]), "+f"(d[5]), "+f"(d[6]), "+f"(d[7]), "+f"(d[8]), "+f"(d[9]), "+f"(d[10]), "+f"(d[11]), "+f"(d[12]), "+f"(d[13]), "+f"(d[14]), "+f"(d[15]), "+f"(d[16]), "+f"(d[17]), "+f"(d[18]), "+f"(d[19]), "+f"(d[20]), "+f"(d[21]), "+f"(d[22]), "+f"(d[23]), "+f"(d[24]), "+f"(d[25]), "+f"(d[26]), "+f"(d[27])
        : "r"(a[0]), "r"(a[1]), "r"(a[2]), "r"(a[3]), "r"(lb), "r"(scale_d), "n"(HB), "n"(TB));
}
template <int TA, uint32_t HA, uint32_t HB>
__device__ __forceinline__ void wgmma_n112(float (&d)[56], uint32_t la, uint32_t lb, int scale_d = 1) {
    asm volatile("{\n.reg .b64 da, db;\n.reg .pred p;\nsetp.ne.b32 p, %61, 0;\nmov.b64 da, {%56, %59};\nmov.b64 db, {%57, %60};\n"
        "wgmma.mma_async.sync.aligned.m64n112k16.f32.bf16.bf16 "
        "{%0, %1, %2, %3, %4, %5, %6, %7, %8, %9, %10, %11, %12, %13, %14, %15, %16, %17, %18, %19, %20, %21, %22, %23, %24, %25, %26, %27, %28, %29, %30, %31, %32, %33, %34, %35, %36, %37, %38, %39, %40, %41, %42, %43, %44, %45, %46, %47, %48, %49, %50, %51, %52, %53, %54, %55}, "
        "da, db, p, 1, 1, %58, 1;\n}\n"
        : "+f"(d[0]), "+f"(d[1]), "+f"(d[2]), "+f"(d[3]), "+f"(d[4]), "+f"(d[5]), "+f"(d[6]), "+f"(d[7]), "+f"(d[8]), "+f"(d[9]), "+f"(d[10]), "+f"(d[11]), "+f"(d[12]), "+f"(d[13]), "+f"(d[14]), "+f"(d[15]), "+f"(d[16]), "+f"(d[17]), "+f"(d[18]), "+f"(d[19]), "+f"(d[20]), "+f"(d[21]), "+f"(d[22]), "+f"(d[23]), "+f"(d[24]), "+f"(d[25]), "+f"(d[26]), "+f"(d[27]), "+f"(d[28]), "+f"(d[29]), "+f"(d[30]), "+f"(d[31]), "+f"(d[32]), "+f"(d[33]), "+f"(d[34]), "+f"(d[35]), "+f"(d[36]), "+f"(d[37]), "+f"(d[38]), "+f"(d[39]), "+f"(d[40]), "+f"(d[41]), "+f"(d[42]), "+f"(d[43]), "+f"(d[44]), "+f"(d[45]), "+f"(d[46]), "+f"(d[47]), "+f"(d[48]), "+f"(d[49]), "+f"(d[50]), "+f"(d[51]), "+f"(d[52]), "+f"(d[53]), "+f"(d[54]), "+f"(d[55])
        : "r"(la), "r"(lb), "n"(TA), "n"(HA), "n"(HB), "r"(scale_d));
}
template <int TA, uint32_t HA, uint32_t HB>
__device__ __forceinline__ void wgmma_n8(float (&d)[4], uint32_t la, uint32_t lb, int scale_d = 1) {
    asm volatile("{\n.reg .b64 da, db;\n.reg .pred p;\nsetp.ne.b32 p, %9, 0;\nmov.b64 da, {%4, %7};\nmov.b64 db, {%5, %8};\n"
        "wgmma.mma_async.sync.aligned.m64n8k16.f32.bf16.bf16 "
        "{%0, %1, %2, %3}, "
        "da, db, p, 1, 1, %6, 1;\n}\n"
        : "+f"(d[0]), "+f"(d[1]), "+f"(d[2]), "+f"(d[3])
        : "r"(la), "r"(lb), "n"(TA), "n"(HA), "n"(HB), "r"(scale_d));
}

__device__ __forceinline__ void send4(uint32_t rbuf, uint32_t rbar, uint32_t w0, uint32_t w1, uint32_t w2, uint32_t w3, uint32_t on) {
    asm volatile("{\n.reg .pred p;\nsetp.ne.u32 p, %6, 0;\n@p st.async.weak.shared::cluster.mbarrier::complete_tx::bytes.v4.b32 [%0], {%1,%2,%3,%4}, [%5];\n}"
                 ::"r"(rbuf), "r"(w0), "r"(w1), "r"(w2), "r"(w3), "r"(rbar), "r"(on) : "memory");
}
__device__ __forceinline__ void send_half(const float (&a)[56], uint32_t rbuf, uint32_t rbar, int t, uint32_t on) {
#pragma unroll
    for (int i = 28; i < 52; i += 8)
        send4(rbuf + (i - 28) * 256 + t * 16, rbar, pack2(a[i], a[i + 1]), pack2(a[i + 2], a[i + 3]), pack2(a[i + 4], a[i + 5]), pack2(a[i + 6], a[i + 7]), on);
    asm volatile("{\n.reg .pred p;\nsetp.ne.u32 p, %4, 0;\n@p st.async.weak.shared::cluster.mbarrier::complete_tx::bytes.v2.b32 [%0], {%1,%2}, [%3];\n}"
                 ::"r"(rbuf + 6144 + t * 8), "r"(pack2(a[52], a[53])), "r"(pack2(a[54], a[55])), "r"(rbar), "r"(on) : "memory");
}
__device__ __forceinline__ void recv_half(uint32_t (&p)[14], uint32_t buf, int t) {
#pragma unroll
    for (int i = 0; i < 3; i++)
        asm volatile("ld.shared.v4.b32 {%0,%1,%2,%3}, [%4];" : "=r"(p[4 * i]), "=r"(p[4 * i + 1]), "=r"(p[4 * i + 2]), "=r"(p[4 * i + 3]) : "r"(buf + i * 2048 + t * 16) : "memory");
    asm volatile("ld.shared.v2.b32 {%0,%1}, [%2];" : "=r"(p[12]), "=r"(p[13]) : "r"(buf + 6144 + t * 8) : "memory");
}

struct Maps { CUtensorMap xl, x, wqkv, hst, w1, w2, xn, old_, ost, wo; };

__global__ void __cluster_dims__(2, 1, 1) __launch_bounds__(512, 1)
fused_kernel(const __nv_bfloat16* __restrict__ x, const __nv_bfloat16* __restrict__ b1, const __nv_bfloat16* __restrict__ b2, uint8_t* __restrict__ scr,
             uint8_t* __restrict__ out, const __grid_constant__ Maps mp) {
    extern __shared__ __align__(1024) uint8_t smem[];
    const uint32_t sb = smem_u32(smem);
    const uint32_t bar = sb + OFF_BAR;
    const int tid = threadIdx.x, lane = tid & 31;
    const int b = blockIdx.x, z = b & 1, c = b >> 1;
    unsigned* const ctr = reinterpret_cast<unsigned*>(scr + G_CTR);
    if (tid < 112) l2_prefetch(reinterpret_cast<const uint8_t*>(x) + (b * 112 + tid) * 128);
    const uint32_t t_in = clock32();
    TS0(0);
    TG(60);
    const int warp = __shfl_sync(0xffffffffu, tid >> 5, 0);
    const int j = c < 4 ? c : c < 36 ? (c - 4) >> 3 : ((c - 36) * 37) >> 8, q = c < 4 ? 15 : c < 36 ? (c - 4) & 7 : c - 28 - 7 * j;
    const bool g1 = q < 14;
    const int R = q < 8 ? q : (0x27654310u >> (4 * q - 32)) & 7, P = (q >> 3) * 4 + j;
    auto krow = [&](int kb) { const int k = kb + (R & 6); return (k >= 7 ? k - 7 : k) * 64; };
    auto x_load = [&](int kb) {
        mbar_expect(bar + 8 * (B_FULLQ + kb), 40960);
        tma2d(sb + OFF_A + ((XSLOT >> (4 * kb)) & 7) * 16384, &mp.x, z * D_ + krow(kb), R * 128, bar + 8 * (B_FULLQ + kb));
    };
    auto w_load = [&](int kb) {
        tma3d_mc(sb + OFF_B + ((WSLOT >> (4 * kb)) & 7) * 24576 + z * 12288, &mp.wqkv, (P * 56) & ~15, krow(kb) + z * 32, 0, bar + 8 * (B_FULLQ + kb));
    };
    if (warp == 12 && elect()) {
#pragma unroll
        for (int i = B_FULLQ; i < B_EMPTYQ; i++) mbar_init(bar + 8 * i, 1);
        mbar_expect(bar + 8 * B_LNIN, BLK);
        tma3d(sb + OFF_A, &mp.xl, 0, 16 * b, 0, bar + 8 * B_LNIN);
        x_load(0);
        TS(15);
    }
    auto bar_count = [&](int i) {
        return i < B_FULL ? (i < B_EMPTYQ + 2 ? 24 : 8) : i < B_EMPTY || i == B_FREE ? 2 : (i < B_AUX || i == B_NONE || i == B_OST) ? 8 : i == B_KV ? 12
               : (i == B_AUX || i == B_HALO) ? 4 : 1;
    };
    if (warp == 13 && elect()) {
#pragma unroll
        for (int i = B_EMPTYQ; i < B_COUNT; i++) mbar_init(bar + 8 * i, bar_count(i));
#pragma unroll
        for (int i = B_RECV1; i < B_EP; i++) mbar_expect(bar + 8 * i, i < B_RECV2 ? 7168 : 8192 - 2048 * z);
    }
    asm volatile("fence.mbarrier_init.release.cluster;" ::: "memory");
    __syncwarp();
    asm volatile("barrier.cluster.arrive.relaxed.aligned;\nbarrier.cluster.wait.aligned;" ::: "memory");
    if (warp == 12 && elect()) { w_load(0); TS(16); }
    auto slot = [](uint32_t r) { return r - 6 * ((r * 43) >> 8); };
    auto phase = [](uint32_t r) { return ((r * 43) >> 8) & 1; };
    const uint32_t r_o = g1 ? 16 : 0, r_u = r_o + 3;
    auto xslot = [&](uint32_t i) { return i == 1 ? 6 : slot(r_o + i - (i > 1)); };
    auto aoff = [](uint32_t s) { return s == 6 ? OFF_SA - OFF_A : s * 16384; };
    auto fetch_x = [&](uint32_t i, bool arm = true) {
        const uint32_t s = xslot(i), lb = bar + 8 * (B_LAND + s);
        if (arm) mbar_expect(lb, i < 4 ? 16384 : BLK);
        if (i < 4) tma2d(sb + OFF_A + aoff(s), &mp.old_, 0, (4 * z + i) * S_ + q * 128, lb);
        else bulk_load(sb + OFF_B + s * BLK, scr + G_BIMG + ((14 * z + (i < 11 ? 2 * i : 2 * i - 13)) * 4 + j) * BLK, BLK, lb);
    };
    auto epoch = [&]() { mbar_wait(bar + 8 * B_EP, 0); return *reinterpret_cast<volatile unsigned*>(smem + OFF_EP); };

    if (warp < 8) {
        const int wg = warp >> 2, w4 = warp & 3, t = tid & 127, g = lane >> 2, tq = lane & 3;
        asm volatile("setmaxnreg.inc.sync.aligned.u32 208;");
        uint32_t xa[4];
#pragma unroll
        for (int k = 0; k < 4; k++) xa[k] = sb + OFF_A + (warp * 16 + (lane & 15)) * 128 + (((2 * k + (lane >> 4)) ^ (lane & 7)) << 4);
        {
            const int rg = warp & 1, jq = warp >> 1;
            const uint32_t ex = sb + OFF_LNX + (rg * 8 + g) * 32, ew = ex + jq * 8, ls = sb + OFF_LNST + (rg * 8 + g) * 8;
            const uint32_t l0 = sb + OFF_A + rg * 1024 + g * 144;
            uint32_t r[4][4], la[4], ha[4], x0, dep = ex | ew | ls | l0;
#pragma unroll
            for (int i = 0; i < 4; i++) {
                const int cg = 14 * jq + 4 * i + ((lane >> 3) & (i < 3 ? 3 : 1));
                la[i] = sb + OFF_A + (cg >> 3) * 2048 + rg * 1024 + (lane & 7) * 128 + (((cg ^ lane) & 7) << 4);
                int pos = 4 * i + (lane >> 3) + (b >= 64 ? 7 : 0);
                if (pos >= 14) pos -= 14;
                ha[i] = sb + OFF_A + jq * 3584 + rg * 1792 + (lane & 7) * 16 + pos * 128;
                dep |= la[i] | xa[i] | ha[i];
            }
            mbar_wait(bar + 8 * B_LNIN, dep >> 31);
            asm volatile("ld.shared.b32 %0, [%1];" : "=r"(x0) : "r"(l0) : "memory");
#pragma unroll
            for (int i = 0; i < 4; i++) ldsm4(la[i], r[i]);
            float s1[4], s2[4], v[28];
            const float sh = bf_lo(x0);
#pragma unroll
            for (int n = 0; n < 14; n++) { v[2 * n] = bf_lo(r[n >> 2][n & 3]) - sh; v[2 * n + 1] = bf_hi(r[n >> 2][n & 3]) - sh; }
#pragma unroll
            for (int n = 0; n < 28; n++) {
                s1[n & 3] = n < 4 ? v[n] : s1[n & 3] + v[n];
                s2[n & 3] = n < 4 ? v[n] * v[n] : fmaf(v[n], v[n], s2[n & 3]);
            }
            float m1 = (s1[0] + s1[1]) + (s1[2] + s1[3]), m2 = (s2[0] + s2[1]) + (s2[2] + s2[3]);
#pragma unroll
            for (int o = 1; o <= 2; o <<= 1) { m1 += __shfl_xor_sync(0xffffffffu, m1, o); m2 += __shfl_xor_sync(0xffffffffu, m2, o); }
            asm volatile("st.shared.v2.f32 [%0], {%1, %2};" ::"r"(ew), "f"(m1), "f"(m2) : "memory");
            bar_sync<1, 256>();
            float4 e0, e1;
            asm volatile("ld.shared.v4.f32 {%0,%1,%2,%3}, [%4];" : "=f"(e0.x), "=f"(e0.y), "=f"(e0.z), "=f"(e0.w) : "r"(ex) : "memory");
            asm volatile("ld.shared.v4.f32 {%0,%1,%2,%3}, [%4];" : "=f"(e1.x), "=f"(e1.y), "=f"(e1.z), "=f"(e1.w) : "r"(ex + 16) : "memory");
            const float dm = ((e0.x + e0.z) + (e1.x + e1.z)) * (1.f / D_);
            const float var = fmaxf(fmaf(-dm, dm, ((e0.y + e0.w) + (e1.y + e1.w)) * (1.f / D_)), 0.f);
            const float r1 = rsq(var + 1e-5f), sc = rsq(fmaf(1e-5f, var + 1e-5f, var)), of = -dm * sc;
#pragma unroll
            for (int n = 0; n < 14; n++) r[n >> 2][n & 3] = pack2(fmaf(v[2 * n], sc, of), fmaf(v[2 * n + 1], sc, of));
#pragma unroll
            for (int i = 0; i < 3; i++) stsm4(ha[i], r[i][0], r[i][1], r[i][2], r[i][3]);
            stsm2(ha[3], r[3][0], r[3][1]);
            asm volatile("st.shared.v2.b32 [%0], {%1, %2};" ::"r"(ls), "r"(__float_as_uint(r1)), "r"(split2(-(sh + dm))) : "memory");
            TS0(24);
            asm volatile("bar.arrive 10, 288;" ::: "memory");
        }
        float a1[56];
        float rq[2], hb1[2], fb2[2];
        uint32_t qp[14], kp[14];
        const uint32_t ka = sb + OFF_K + warp * 896 + (lane & 7) * 112 + (lane >> 3) * 16;
        const uint32_t va = sb + OFF_V + (warp * 16 + (lane & 15)) * 112 + (lane >> 4) * 16;
        const uint32_t sta = sb + OFF_RSTD + warp * 64 + tq * 8;
        const uint32_t dA = desc_lo(OFF_A + wg * 8192, 16), dH = desc_lo(OFF_B, 1792), dU = desc_lo(OFF_B, 128);
        auto release = [&](uint32_t a) { mbar_arrive_if0(a, lane); };
        uint32_t rel = bar + 8 * (B_EMPTYQ + 6);
        auto g1_step = [&](uint32_t s, uint32_t acc) {
            wg_fence();
#pragma unroll
            for (int k = 0; k < 4; k++) wgmma_n112<1, H_SW, H_H>(a1, dA + s * 1024 + k * 128, dH + s * 896 + k * 224, k ? 1 : acc);
            wg_commit();
            wg_wait<1>();
            release(rel);
            rel = bar + 8 * (B_EMPTY + s);
        };
        auto g1_run = [&](uint32_t r0, uint32_t r1, bool last = false) {
#pragma unroll 1
            for (uint32_t r = g1 ? r0 : r1; r < r1; r++) {
                if (TSG1) TSD(64 + r);
                g1_step(slot(r), r);
                const bool end = last && r + 1 == r1;
                mbar_wait(bar + 8 * (end ? B_FREE : B_FULL + slot(r + 1)), !end && phase(r + 1));
            }
        };
        auto drain = [&]() { wg_wait<0>(); release(rel); rel = bar + 8 * B_NONE; };
        {
            float aq0[28], aq1[28], aq2[28];
            const uint32_t dW = desc_lo(OFF_B + (P & 1) * 16, 16);
            uint32_t xf[2][4][4];
            const uint32_t rb = mapa(bar + 8 * (B_EMPTYQ - 1), z ^ 1);
            auto fetch = [&](int kb, uint32_t (&f)[4][4]) {
                if (TSG1) TSD(178 + kb);
                mbar_wait(bar + 8 * (B_FULLQ + kb), 0);
                if (TSG1) TSD(170 + kb);
#pragma unroll
                for (int k = 0; k < 4; k++) ldsm4(xa[k] + ((XSLOT >> (4 * kb)) & 7) * 16384, f[k]);
            };
            auto mma = [&](int kb, uint32_t (&f)[4][4], int k0, int k1) {
                const uint32_t d0 = dW + ((WSLOT >> (4 * kb)) & 7) * 1536;
                wg_fence();
#pragma unroll
                for (int k = k0; k < k1; k++) {
                    const uint32_t d = d0 + (k >> 1) * 768 + (k & 1) * 128;
                    const int sc = k > 0 ? 1 : kb;
                    wgmma_n56_rs<H_SW, 1>(aq0, f[k], d, sc);
                    wgmma_n56_rs<H_SW, 1>(aq1, f[k], d + 256, sc);
                    wgmma_n56_rs<H_SW, 1>(aq2, f[k], d + 512, sc);
                }
            };
            auto retire = [&](int kb) {
                wg_commit();
                wg_wait<1>();
                mbar_arrive_if0(bar + 8 * (B_EMPTYQ + kb - 1), lane | (kb < 1));
                asm volatile("{\n.reg .pred p;\nsetp.eq.u32 p, %1, 0;\n@p mbarrier.arrive.shared::cluster.b64 _, [%0];\n}"
                             ::"r"(rb + 8 * kb), "r"(lane | ((uint32_t)(kb - 1) > 1)) : "memory");
            };
            auto stage = [&](int kb, uint32_t (&f)[4][4], uint32_t (&n)[4][4]) {
                mma(kb, f, 0, KS);
                retire(kb);
                fetch(kb + 1, n);
                mma(kb, f, KS, 4);
                wg_commit();
            };
            fetch(0, xf[0]);
#pragma unroll 1
            for (int kb = 0; kb < 6; kb += 2) {
                stage(kb, xf[0], xf[1]);
                stage(kb + 1, xf[1], xf[0]);
            }
            mma(6, xf[0], 0, KS);
            retire(6);
            TS0(2);
            mbar_wait(bar + 8 * B_AUX, 0);
            {
                uint32_t (&f)[4] = xf[1][0];
                const uint2* mt = reinterpret_cast<const uint2*>(smem + OFF_STATS) + warp * 16 + g;
                const uint2 m0 = mt[0], m1 = mt[8];
                const uint32_t sel = tq == 0 ? 0x1010 : tq == 1 ? 0x3232 : 0x4444;
                f[0] = __byte_perm(m0.y, 0, sel); f[1] = __byte_perm(m1.y, 0, sel); f[2] = f[3] = 0;
                rq[0] = __uint_as_float(m0.x); rq[1] = __uint_as_float(m1.x);
                asm volatile("" : "+r"(f[0]), "+r"(f[1]), "+r"(f[2]), "+r"(f[3])::"memory");
                const uint32_t d = desc_lo(OFF_CSB + (P & 1) * 128, 0);
                mma(6, xf[0], KS, 4);
                wgmma_n56_rs<H_H, 0>(aq1, f, d + 64, 1);
                wgmma_n56_rs<H_H, 0>(aq2, f, d + 128, 1);
                wgmma_n56_rs<H_H, 0>(aq0, f, d, 1);
                wg_commit();
            }
            mbar_wait(bar + 8 * (g1 ? B_FULL : B_LNIN), 0);
            g1_run(0, wg ? 0 : NE);
            drain();
            pin(aq0); pin(aq1); pin(aq2);
            TSW(3);
            mbar_wait(bar + 8 * (B_EMPTYQ + 5), 0);
#pragma unroll
            for (int i = 0; i < 14; i++) { kp[i] = pack2(aq1[2 * i], aq1[2 * i + 1]); qp[i] = pack2(aq2[2 * i], aq2[2 * i + 1]); }
            stsm4(ka + 896, kp[1], kp[3], kp[5], kp[7]);
            stsm4(ka + 896 + 48, kp[7], kp[9], kp[11], kp[13]);
#pragma unroll
            for (int n = 0; n < 3; n++) stsm4(va + 896 + n * 32, qp[4 * n], qp[4 * n + 1], qp[4 * n + 2], qp[4 * n + 3]);
            stsm2(va + 896 + 96, qp[12], qp[13]);
            __syncwarp();
            mbar_arrive_if0(bar + 8 * B_QKV, tid - 224);
            release(bar + 8 * B_KV);
#pragma unroll
            for (int i = 0; i < 14; i++) qp[i] = pack2(aq0[2 * i], aq0[2 * i + 1]);
            TSW(4);
        }
        g1_run(wg ? 0 : NE, wg ? PRE1 : PRE0);
        {
            uint32_t kf[2][3][4], vf[2][3][4];
            const bool up0 = 2 * tq > g, up1 = 2 * tq + 1 > g, edge = (R | warp) == 0;
            float rk[2][2], fs[2][2], rs[3][2];
            mbar_wait(bar + 8 * (warp ? B_KV : B_HALO), 0);
            const uint32_t tag = *reinterpret_cast<volatile unsigned*>(smem + OFF_EP);
#pragma unroll
            for (int i = 0; i < 2; i++)
                asm volatile("ld.shared.v2.f32 {%0,%1}, [%2];" : "=f"(hb1[i]), "=f"(fb2[i]) : "r"(sb + OFF_BIAS + (warp * 16 + g + 8 * i) * 8) : "memory");
#pragma unroll
            for (int i = 0; i < 3; i++)
                asm volatile("ld.shared.v2.f32 {%0,%1}, [%2];" : "=f"(rs[i][0]), "=f"(rs[i][1]) : "r"(sta + i * 32) : "memory");
#pragma unroll
            for (int hd = 0; hd < 2; hd++) {
                ldsm4(ka + hd * 48, kf[hd][0]);
#pragma unroll
                for (int i = 0; i < 4; i++) { kf[hd][1][i] = kp[6 * hd + 2 * i]; kf[hd][2][i] = kp[6 * hd + 2 * i + 1]; }
                ldsm4t(va + hd * 48, vf[hd][0]); ldsm4t(va + hd * 48 + 32, vf[hd][1]);
                ldsm4t(ka + (OFF_V - OFF_K) + warp * 896 + hd * 48 + 1792, vf[hd][2]);
            }
            const uint32_t q0l = tq < 2 ? qp[6] : 0, q0h = tq < 2 ? qp[7] : 0, q1l = tq < 2 ? 0 : qp[6], q1h = tq < 2 ? 0 : qp[7];
            const uint32_t mk = (up0 ? 0xFFFFu : 0u) | (up1 ? 0xFFFF0000u : 0u);
            g1_run(wg ? PRE1 : PRE0, ATT_STEP);
#pragma unroll
            for (int i = 0; i < 4; i++) {
                rk[i >> 1][i & 1] = ((i & 1) ? up1 : up0) ? rs[i >> 1][i & 1] : rs[(i >> 1) + 1][i & 1];
                fs[i >> 1][i & 1] = rk[i >> 1][i & 1] * (rq[i >> 1] * (0.18898223650461362f * 1.4426950408889634f));
                asm volatile("" : "+f"(fs[i >> 1][i & 1])::"memory");
            }
            uint32_t zr[4], oa[4], dep = q0l | q0h | q1l | q1h | mk;
#pragma unroll
            for (int i = 0; i < 4; i++) {
                zr[i] = (lane + i) * (sb >> 31);
                oa[i] = xa[i] + OFF_OST;
            }
#pragma unroll
            for (int i = 0; i < 4; i++) dep |= __float_as_uint(fs[i >> 1][i & 1]) | oa[i] | zr[i];
            after(dep & (sb >> 31));
            drain();
            bar_sync<1, 256>();
            TS0(19);
            float sc[2][3][4];
#pragma unroll
            for (int u = 0; u < 3; u++) {
#pragma unroll
                for (int i = 0; i < 8; i++) sc[i >> 2][u][i & 3] = 0.f;
                mma16816(sc[0][u], qp[0], qp[1], qp[2], qp[3], kf[0][u][0], kf[0][u][1]);
                mma16816(sc[1][u], q1l, q1h, qp[8], qp[9], kf[1][u][0], kf[1][u][1]);
            }
#pragma unroll
            for (int u = 0; u < 3; u++) {
                mma16816(sc[0][u], qp[4], qp[5], q0l, q0h, kf[0][u][2], kf[0][u][3]);
                mma16816(sc[1][u], qp[10], qp[11], qp[12], qp[13], kf[1][u][2], kf[1][u][3]);
            }
            float e[2][2][2], mx[2][2], sm[2][4];
#pragma unroll
            for (int hd = 0; hd < 2; hd++) {
                e[hd][0][0] = (up0 ? sc[hd][0][0] : sc[hd][1][0]) * fs[0][0];
                e[hd][0][1] = (up1 ? sc[hd][0][1] : sc[hd][1][1]) * fs[0][1];
                e[hd][1][0] = (up0 ? sc[hd][1][2] : sc[hd][2][2]) * fs[1][0];
                e[hd][1][1] = (up1 ? sc[hd][1][3] : sc[hd][2][3]) * fs[1][1];
                if (edge && up0) e[hd][0][0] = -1e30f;
                if (edge && up1) e[hd][0][1] = -1e30f;
                mx[hd][0] = fmaxf(e[hd][0][0], e[hd][0][1]);
                mx[hd][1] = fmaxf(e[hd][1][0], e[hd][1][1]);
            }
#pragma unroll
            for (int o = 1; o <= 2; o <<= 1)
#pragma unroll
                for (int i = 0; i < 4; i++) mx[i >> 1][i & 1] = fmaxf(mx[i >> 1][i & 1], __shfl_xor_sync(0xffffffffu, mx[i >> 1][i & 1], o));
            uint32_t pp[2][2], pu[2][2];
#pragma unroll
            for (int i = 0; i < 4; i++) {
                const float p0 = ex2(e[i >> 1][i & 1][0] - mx[i >> 1][i & 1]), p1 = ex2(e[i >> 1][i & 1][1] - mx[i >> 1][i & 1]);
                pp[i >> 1][i & 1] = pack2(p0 * rk[i & 1][0], p1 * rk[i & 1][1]);
                pu[i >> 1][i & 1] = pack2(p0, p1);
            }
            float ov[2][4][4];
#pragma unroll
            for (int hd = 0; hd < 2; hd++)
#pragma unroll
                for (int n = 0; n < 4; n++) {
                    ov[hd][n][0] = ov[hd][n][1] = ov[hd][n][2] = ov[hd][n][3] = 0.f;
                    mma16816(ov[hd][n], pp[hd][0] & mk, zr[hd], pp[hd][0] & ~mk, pp[hd][1] & mk, vf[hd][n >> 1][2 * (n & 1)], vf[hd][n >> 1][2 * (n & 1) + 1]);
                }
#pragma unroll
            for (int hd = 0; hd < 2; hd++) {
                sm[hd][0] = sm[hd][1] = sm[hd][2] = sm[hd][3] = 0.f;
                mma1688(sm[hd], pu[hd][0], pu[hd][1], 0x3F803F80u);
            }
#pragma unroll
            for (int hd = 0; hd < 2; hd++)
#pragma unroll
                for (int n = 0; n < 4; n++) mma1688(ov[hd][n], zr[2 + hd], pp[hd][1] & ~mk, vf[hd][2][n]);
            TS0(18);
            uint32_t op[16];
            op[14] = op[15] = tag & 0x3FFF;
#pragma unroll
            for (int i = 0; i < 4; i++) sm[i >> 1][i & 1] = rcp(sm[i >> 1][2 * (i & 1)]);
#pragma unroll
            for (int n = 0; n < 7; n++) {
                const bool hb = n > 3 || (n == 3 && tq >= 2);
#pragma unroll
                for (int h = 0; h < 2; h++) {
                    const float r = hb ? sm[1][h] : sm[0][h];
                    const float x0 = hb ? ov[1][n >= 3 ? n - 3 : 0][2 * h] : ov[0][n <= 3 ? n : 0][2 * h];
                    const float x1 = hb ? ov[1][n >= 3 ? n - 3 : 0][2 * h + 1] : ov[0][n <= 3 ? n : 0][2 * h + 1];
                    op[2 * n + h] = pack2(x0 * r, x1 * r);
                }
            }
#pragma unroll
            for (int n = 0; n < 4; n++) stsm4(oa[n], op[4 * n], op[4 * n + 1], op[4 * n + 2], op[4 * n + 3]);
            __syncwarp();
            release(bar + 8 * B_OST);
            mbar_wait(bar + 8 * B_OST, 0);
            TSW(5);
        }
        const uint32_t peer = z ^ 1;
        g1_run(ATT_STEP, wg ? GS : 16, true);
        gate_open(wg | !g1);
        drain();
#pragma unroll 1
        for (uint32_t r = g1 && wg ? GS : 16; r < 16; r++) {
            gate_wait(r == GS);
            g1_step(r - 12, 1);
        }
        drain();
        pin(a1);
        TSW(6);
        send_half(a1, mapa(sb + OFF_RECV1 + wg * 7168, peer), mapa(bar + 8 * (B_RECV1 + wg), peer), t, g1);
        float h[28];
#pragma unroll
        for (int i = 0; i < 28; i++) h[i] = fmaf(a1[i], 0.5f, hb1[(i >> 1) & 1]);
        pin(h);
        if (g1) {
            uint32_t p[14];
            float y[28];
            uint8_t* ub = scr + G_BIMG + ((8 + 2 * q + wg) * 4 + j) * BLK + w4 * 256 + lane * 4;
            uint8_t *u0 = ub + (q < 7 ? 7 : 13) * z * 1024, *u1 = ub + (q < 7 ? 7 : 1) * z * 1024, *u2 = u1 + (q < 7 || z ? 0 : 6144);
            mbar_wait(bar + 8 * (B_RECV1 + wg), __any_sync(0xffffffffu, ((uint64_t)u0 | (uint64_t)u1 | (uint64_t)u2) >> 63));
            TSW(8);
            recv_half(p, sb + OFF_RECV1 + wg * 7168, t);
#pragma unroll
            for (int i = 0; i < 28; i++) {
                h[i] = fmaf((i & 1) ? bf_hi(p[i >> 1]) : bf_lo(p[i >> 1]), 0.5f, h[i]);
                y[i] = h[i] * fmaf(h[i] * h[i], 8.f * 0.0356774081363f, 2.f * 0.7978845608029f);
            }
#pragma unroll
            for (int i = 0; i < 28; i++) asm volatile("tanh.approx.f32 %0, %0;" : "+f"(y[i]));
#pragma unroll
            for (int i = 0; i < 14; i++)
                stg32((i < 2 ? u0 : i < 4 ? u1 : u2) + (i >> 1) * 1024 + (i & 1) * 128, pack2(fmaf(h[2 * i], y[2 * i], h[2 * i]), fmaf(h[2 * i + 1], y[2 * i + 1], h[2 * i + 1])));
            TSW(9);
        }
        float a2[56];
#pragma unroll 1
        for (uint32_t i = 0; i < 4; i++) {
            const uint32_t s = ((g1 ? 0x0564u : 0x2160u) >> (4 * i)) & 7, da = dA + (aoff(s) >> 4), db = dU + (i == 1 ? (OFF_SB - OFF_B) >> 4 : s * 896);
            mbar_wait(bar + 8 * (B_FULL + s), g1 && i == 3);
            TSD(64 + 17 + i);
            wg_fence();
#pragma unroll
            for (int k = 0; k < 4; k++) wgmma_n112<0, H_SW, H_U>(a2, da + k * 2, db + k * 16, k ? 1 : i);
            wg_commit();
            wg_wait<1>();
            release(rel);
            rel = bar + 8 * (B_EMPTY + s);
        }
        TSW(10);
#pragma unroll 1
        for (uint32_t r = r_u; r < r_u + 14 - (wg ? NS2 : 0); r++) {
            const uint32_t s = slot(r);
            mbar_wait(bar + 8 * (B_FULL + s), phase(r));
            TSD(85 + r - r_u);
            wg_fence();
#pragma unroll
            for (int k = 0; k < 4; k++) wgmma_n112<1, H_SW, H_U>(a2, dA + s * 1024 + k * 128, dU + s * 896 + k * 16);
            wg_commit();
            wg_wait<1>();
            release(rel);
            rel = bar + 8 * (B_EMPTY + s);
        }
        uint32_t late = wg;
        asm volatile("" : "+r"(late));
        late = __shfl_sync(0xffffffffu, late, 0);
        gate_open(wg);
        mbar_wait(bar + 8 * B_UDONE, 0);
#pragma unroll 1
        for (uint32_t n = 0; n < late; n++) {
            bar_sync<4, 256>();
            wg_fence();
#pragma unroll
            for (int k = 0; k < 4 * NS2; k++) {
                const uint32_t s = g1 ? (33 - NS2 + k / 4) % 6 : (17 - NS2 + k / 4) % 6;
                wgmma_n112<1, H_SW, H_U>(a2, dA + s * 1024 + k % 4 * 128, dU + s * 896 + k % 4 * 16);
            }
            wg_commit();
        }
        {
            uint32_t ln = lane | (clock32() & (sb >> 31));
            const uint32_t un = warp * 2048 + (ln ^ ((ln >> 3) & 1)) * 16;
            const uint32_t rbuf = mapa(sb + OFF_RECV2, peer), rbar = mapa(bar + 8 * (B_RECV2 + wg), peer);
            uint32_t xr[4][4], u[4][4], sa[4];
#pragma unroll
            for (int i = 0; i < 4; i++) sa[i] = rbuf + (un ^ (i & 1) * 32) + i * 512;
            after((sa[0] | sa[1] | sa[2] | sa[3] | rbar) >> 31);
            wg_wait<0>();
            pin(a2);
            TSW(11);
            auto word = [&](int n, int h) { return pack2(a2[4 * n + 2 * h], a2[4 * n + 2 * h + 1]); };
            send4(sa[1], rbar, word(12, 0), word(13, 0), word(10, 0), word(11, 0), 1);
            send4(sa[3], rbar, word(10, 1), word(11, 1), word(12, 1), word(13, 1), 1);
            send4(sa[0], rbar, word(8, 0), word(9, 0), z ? word(0, 0) : word(8, 1), z ? word(1, 0) : word(9, 1), 1);
            send4(sa[2], rbar, word(0, 1), word(1, 1), word(8, 1), word(9, 1), z);
            const uint32_t nil = clock32() & (sb >> 31);
            const float one = __uint_as_float(0x3F800000u | nil);
#pragma unroll
            for (int i = 0; i < 32; i++) a2[i] = fmaf(a2[i], one, fb2[(i >> 1) & 1]);
#pragma unroll
            for (int i = 0; i < 4; i++) {
                const int n = i % 2 * 4 + (~i & 2), h = i / 2;
                asm volatile("st.shared.v4.b32 [%0], {%1,%2,%3,%4};" ::"r"(sb + OFF_OUT + (un ^ (i & 1) * 32) + i * 512), "r"(word(n, h)), "r"(word(n + 1, h)),
                             "r"(word(n ^ 2, h)), "r"(word(n ^ 3, h)) : "memory");
            }
            ln |= nil;
            const uint32_t la = sb + warp * 2048 + (ln & 1) * 512 + (ln & 6) * 32 + (((ln >> 3) ^ (ln >> 2 & 1) ^ (ln << 1)) & 3) * 16;
            const uint32_t lb = la - (z & ~ln) * 1024;
            const uint32_t lx = sb + OFF_A + slot(r_u + 14) * 16384 + (warp * 16 + (ln >> 3)) * 128 + (((ln ^ (ln >> 3)) & 7) << 4);
            uint8_t* o1 = out + ((q * 128 + warp * 16 + (ln >> 3)) * 896 + j * 224 + z * 96 + (ln & 7) * 16);
            uint8_t* o0 = o1 + (ln & 2 ? -32 : 32);
            auto add_x = [&]() {
#pragma unroll
                for (int i = 0; i < 16; i++) asm("add.rn.bf16x2 %0, %0, %1;" : "+r"(u[i >> 2][i & 3]) : "r"(xr[i >> 2][i & 3]));
            };
            __syncwarp();
#pragma unroll
            for (int i = 0; i < 4; i++) ldsm4(la + OFF_OUT + i / 2 * 1024 + i % 2 * 256, u[i]);
            mbar_wait(bar + 8 * B_XR, 0);
#pragma unroll
            for (int i = 0; i < 4; i++)
                asm volatile("ld.shared.v4.b32 {%0,%1,%2,%3}, [%4];" : "=r"(xr[i][0]), "=r"(xr[i][1]), "=r"(xr[i][2]), "=r"(xr[i][3])
                             : "r"((lx ^ (i % 2 * 64 + (~i & 2) * 16)) + i * 512) : "memory");
            add_x();
            mbar_wait(bar + 8 * (B_RECV2 + wg), (lb | (uint32_t)((uint64_t)o0 >> 32)) >> 31);
            TSW(12);
#pragma unroll
            for (int i = 0; i < 4; i++) ldsm4((i < 2 ? la : lb) + OFF_RECV2 + i / 2 * 1024 + i % 2 * 256, xr[i]);
            add_x();
#pragma unroll
            for (int i = 0; i < 4; i++)
                asm volatile("{\n.reg .pred p;\nsetp.ge.u32 p, %5, %6;\n@p st.global.v4.b32 [%0], {%1,%2,%3,%4};\n}"
                             ::"l"((i < 2 ? o0 : o1) + i * 3584), "r"(u[i][0]), "r"(u[i][1]), "r"(u[i][2]), "r"(u[i][3]), "r"((lane & 6) ^ (~i & 2)), "r"(z) : "memory");
        }
        TSW(13);
    } else if (warp < 12) {
        asm volatile("setmaxnreg.dec.sync.aligned.u32 64;");
        const int hw = warp - 8, t = tid & 127;
        reinterpret_cast<uint32_t*>(smem + OFF_ONES)[t] = t < 64 ? 0x3F803F80u : 0;
        fence_async_smem();
        bar_sync<12, 128>();
        while (clock32() - t_in < DLY1) {}
        uint8_t* cscell = scr + G_CS + ((P * 8 + R) * 2 + z) * 512 + (t >> 2) * 16;
        if ((lane & 3) == 0) cell_put(cscell, 0, 0, 0);
        uint8_t* cells = scr + G_HALO + ((R * 8 + P) * 2 + z) * 3584 + min(t, 111) * 16;
        cell_put(cells, 0, 0, 0);
        cell_put(cells + 1792, 0, 0, 0);
        const unsigned e1 = epoch();
        const uint32_t bv1 = ldg_u16(b1 + (g1 ? q * 128 : 0) + t), bv2 = ldg_u16(b2 + q * 128 + t);
        {
            const uint32_t da = desc_lo(OFF_B + min((R & 1) * 2 + z, 2) * 4096, 16), db = desc_lo(OFF_ONES, 128);
            float c0[4];
            mbar_wait(bar + 8 * B_FULLQ, 0);
            mbar_wait(bar + 8 * (B_FULLQ + 1), 0);
            TSH(47);
            wg_fence();
#pragma unroll
            for (int k = 0; k < 8; k++)
                wgmma_n8<1, H_SW, H_H>(c0, da + ((WSLOT >> (k & 4)) & 7) * 1536 + (k & 2) * 384 + (k & 1) * 128, db + (k >= 4 && R >= 6 ? 16 : 0), k);
            wg_commit();
            wg_wait<0>();
            pin(c0);
            if ((lane & 3) == 0) cell_put(cscell, __float_as_uint(c0[0]), __float_as_uint(c0[2]), e1);
            if (lane < 4) asm volatile("mbarrier.arrive.shared::cluster.b64 _, [%0];" ::"r"(mapa(bar + 8 * (B_EMPTYQ + (lane >> 1)), lane & 1)) : "memory");
            TSH(43);
        }
        mbar_wait(bar + 8 * (B_FULLQ + GATHER), 0);
        TSH(39);
        {
            const bool cw = hw < 3;
            const uint8_t* src = cw ? scr + G_CS + P * 8192 + t * 16 : scr + G_STATS + (z * 1024 + R * 128 + lane) * 16;
            uint32_t a[5], d[5], bad;
            do {
                bad = 0;
#pragma unroll
                for (int i = 0; i < 4; i++) bad |= cell_get(src + i * (cw ? 2048 : 512), a[i], d[i], e1);
                if (t >= 120) bad |= cell_get(src - (R ? 512 : 0), a[4], d[4], e1);
            } while (bad);
            TSH(45);
            if (cw) {
                uint4* cb = reinterpret_cast<uint4*>(smem + OFF_CSB) + (t >> 3) * 16 + (t & 7);
                const uint32_t lo = split2((__uint_as_float(a[0]) + __uint_as_float(a[1])) + (__uint_as_float(a[2]) + __uint_as_float(a[3])));
                const uint32_t hi = split2((__uint_as_float(d[0]) + __uint_as_float(d[1])) + (__uint_as_float(d[2]) + __uint_as_float(d[3])));
                cb[0] = make_uint4(lo, lo, 0, 0);
                cb[8] = make_uint4(hi, hi, 0, 0);
            } else {
                uint2* st = reinterpret_cast<uint2*>(smem + OFF_STATS) + lane;
                uint32_t* rd = reinterpret_cast<uint32_t*>(smem + OFF_RSTD) + lane;
#pragma unroll
                for (int i = 0; i < 4; i++) { st[32 * i] = make_uint2(a[i], d[i]); rd[8 + 32 * i] = a[i]; }
                if (t >= 120) rd[-24] = a[4];
            }
            fence_async_smem();
            __syncwarp();
            mbar_arrive_if0(bar + 8 * B_AUX, lane);
            TSH(41);
            reinterpret_cast<float2*>(smem + OFF_BIAS)[t] = make_float2(0.5f * bf_lo(bv1), bf_lo(bv2));
            __syncwarp();
            mbar_arrive_if0(bar + 8 * B_KV, lane);
        }
        {
            uint2* kv = reinterpret_cast<uint2*>(smem + OFF_K) + min(t, 111);
            mbar_wait(bar + 8 * B_QKV, 0);
            uint2 k2 = kv[896], v2 = kv[1792 + (OFF_V - OFF_K) / 8];
            cell_put(cells, k2.x, k2.y, e1);
            cell_put(cells + 1792, v2.x, v2.y, e1);
            k2 = v2 = make_uint2(0, 0);
            delay(DH);
            if (R > 0) while (cell_get(cells - 16 * 3584, k2.x, k2.y, e1) | cell_get(cells - 16 * 3584 + 1792, v2.x, v2.y, e1)) {}
            kv[0] = k2;
            kv[(OFF_V - OFF_K) / 8] = v2;
            mbar_wait(bar + 8 * B_KV, 0);
            __syncwarp();
            mbar_arrive_if0(bar + 8 * B_HALO, lane);
            TSH(40);
        }
        if (hw == 3) {
            mbar_wait(bar + 8 * B_OST, 0);
            if (elect()) {
                unsigned* oc = ctr + C_O + (R * 2 + (P >> 2)) * 32;
                TS(38);
                fence_async_smem();
                TS(46);
#pragma unroll
                for (int i = 0; i < 4; i++) {
                    tma2d_store(&mp.ost, sb + OFF_OST + i * 4096, z * 64, P * 1024 + R * 128 + i * 32);
                    bulk_commit();
                }
                TS(7);
                asm volatile("mbarrier.arrive.relaxed.cluster.shared::cluster.b64 _, [%0];" ::"r"(mapa(bar + 8 * B_FREE, z ^ 1)) : "memory");
                bulk_wait_read<3>();
                delay(DO);
                red_relaxed(oc, 1);
                TS(21);
                mbar_wait(bar + 8 * B_LNIN, 0);
                bulk_wait_read<0>();
                mbar_arrive(bar + 8 * B_QKV);
                TS(20);
                mbar_wait(bar + 8 * (B_EMPTY + 6), 0);
                asm volatile("mbarrier.arrive.relaxed.cluster.shared::cluster.b64 _, [%0];" ::"r"(mapa(bar + 8 * B_UDONE, z ^ 1)) : "memory");
            }
        } else {
            const uint32_t tag = e1 & 0x3FFF;
            const uint32_t ca = sb + OFF_A + lane * 128 + ((~lane & 7) << 4) + (lane >> 3) * 4, cb = sb + OFF_B + lane * 132;
            uint32_t par = 0x7F;
#pragma unroll 1
            for (uint32_t i = hw ? 3 - hw : 0; i < 18;) {
                const uint32_t s = xslot(i);
                const bool isa = i < 4;
                const uint32_t a0 = isa ? ca + aoff(s) : cb + s * BLK, a3 = a0 - (isa ? 0 : (lane & 16) * 132);
                mbar_wait(bar + 8 * (B_LAND + s), (par >> s) & 1);
                par ^= 1 << s;
                bool ok = true;
#pragma unroll
                for (int k = 0; k < 4; k++) {
                    uint32_t v;
                    asm volatile("ld.shared.b32 %0, [%1];" : "=r"(v) : "r"((k < 3 ? a0 : a3) + k * 4096) : "memory");
                    ok &= (v == (isa ? tag : ~0u)) == isa;
                }
                const uint32_t bad = __ballot_sync(0xffffffffu, !ok);
                mbar_arrive_if0(bar + 8 * (B_FULL + s), lane | bad);
                if (!bad) {
                    if (i == 0 || i == 4) TS(i ? 30 : 29);
                    i += i < 1 ? 4 : i == 1 ? 2 : 3;
                } else if (elect()) {
                    TS(31);
                    fetch_x(i);
                }
            }
        }
    } else {
        asm volatile("setmaxnreg.dec.sync.aligned.u32 32;");
        auto wait_free = [&](uint32_t r, uint32_t first) {
            const uint32_t a = r < 6 ? B_EMPTYQ + ((first >> (4 * r)) & 7) : B_EMPTY + slot(r);
            mbar_wait(bar + 8 * a, r < 6 ? 0 : phase(r) ^ 1);
        };
        if (warp == 12) {
            TS(14);
            if (elect()) {
#pragma unroll 1
                for (int kb = 1; kb < 7; kb++) {
                    if (kb == 1) while (clock32() - t_in < DLY2) {}
                    if (kb >= QDEPTH) { mbar_wait(bar + 8 * (B_FULLQ + kb - QDEPTH), 0); TS(25 + kb - QDEPTH); }
                    if (kb >= 5) mbar_wait(bar + 8 * (B_EMPTYQ + kb - 5), 0);
                    x_load(kb);
                    w_load(kb);
                }
                TS(17);
                mbar_wait(bar + 8 * B_LNFREE, 0);
                if (!g1) {
                    const int ic = (q - 14) * 8 + j * 2 + z, rot = ic >> 3;
                    mbar_wait(bar + 8 * (B_EMPTYQ + 2), 0);
                    mbar_expect(bar + 8 * B_GO, 2 * BLK);
#pragma unroll 1
                    for (int i = 0; i < 2; i++) tma4d(sb + OFF_A + i * BLK, &mp.wo, 0, 0, (z * 2 + i) * 14, ic >> 1, bar + 8 * B_GO);
                    mbar_wait(bar + 8 * B_GO, 0);
#pragma unroll 1
                    for (int i = 0; i < 2; i++) {
                        uint8_t* dst = scr + G_BIMG + (ic * 2 + i) * BLK;
                        bulk_store(dst, sb + OFF_A + i * BLK, 2048);
                        bulk_store(dst + 2048 + rot * 6144, sb + OFF_A + i * BLK + 2048, 6144);
                        bulk_store(dst + 8192 - rot * 6144, sb + OFF_A + i * BLK + 8192, 6144);
                    }
                    bulk_commit();
                    bulk_wait_all();
                    publish(ctr + C_WO);
                    TS(44);
                }
#pragma unroll 1
                for (uint32_t r = 0; r < r_o; r++) {
                    const uint32_t s = slot(r), fb = bar + 8 * (B_FULL + s);
                    wait_free(r, 0x654320u);
                    mbar_expect(fb, 16384);
                    tma3d(sb + OFF_A + s * 16384, &mp.w1, 0, z * 1024 + r * 64, 2 * q, fb);
                    TS(99 + r);
                }
                mbar_wait(bar + 8 * B_OST, 0);
                mbar_expect(bar + 8 * (B_LAND + 6), 16384);
                wait_free(r_o, 0x654320u);
                mbar_expect(bar + 8 * (B_LAND + slot(r_o)), 16384);
                poll(ctr + C_O + ((q & ~1) + z) * 32, epoch() * 8);
                TS(32);
                fetch_x(0, false);
                mbar_wait(bar + 8 * B_QKV, 1);
                fetch_x(1, false);
                TS(99 + 17);
#pragma unroll 1
                for (uint32_t i = 1; i < 3; i++) {
                    wait_free(r_o + i, 0x654320u);
                    fetch_x(i + 1);
                }
                TS(99 + 20);
#pragma unroll 1
                for (uint32_t i = 0; i < 14; i++) {
                    const uint32_t r = r_u + i, s = slot(r), fb = bar + 8 * (B_FULL + s);
                    wait_free(r, 0x654320u);
                    mbar_expect(fb, 16384);
                    tma3d(sb + OFF_A + s * 16384, &mp.w2, 0, (14 * z + (i < 7 ? 2 * i : 2 * i - 13)) * 64, 2 * q, fb);
                    TS(99 + 21 + i);
                }
                wait_free(r_u + 14, 0);
                mbar_expect(bar + 8 * B_XR, 16384);
                tma2d(sb + OFF_A + slot(r_u + 14) * 16384, &mp.xn, j * 112 + z * 48, q * 128, bar + 8 * B_XR);
            }
        } else if (warp == 13) {
            if (elect()) {
#pragma unroll 1
                for (int ph = g1 ? 0 : 1; ph < 4; ph++) {
                    const uint8_t* src = ph == 0 ? scr + G_HIMG + (64 * z + j) * BLK : scr + G_BIMG + ((ph == 1 ? 4 * z : 6 + 14 * z + ph) * 4 + j) * BLK;
                    const uint32_t r0 = ph == 0 ? 0 : r_o + (ph == 1 ? 0 : 7 * ph - 11), r1 = r_o + (ph == 0 ? 0 : 7 * ph - 4);
                    if (ph == 1) {
                        mbar_wait(bar + 8 * B_OST, 0);
                        mbar_expect(bar + 8 * (B_FULL + 6), BLK);
                        mbar_wait(bar + 8 * (B_GO + 1), 0);
                        bulk_load(sb + OFF_SB, src + 4 * BLK, BLK, bar + 8 * (B_FULL + 6));
                    }
#pragma unroll 1
                    for (uint32_t r = r0; r < r1; r++, src += r <= r_o || r == r_o + 2 ? 4 * BLK : 8 * BLK) {
                        const uint32_t s = slot(r), fb = bar + 8 * ((ph < 2 ? B_FULL : B_LAND) + s);
                        wait_free(r, 0x644332u);
                        mbar_expect(fb, BLK);
                        if (ph == 0) {
                            if (r == 0) {
                                poll(ctr + C_LN, epoch() * 128);
                                fence_async_global();
                                TS(33);
                            }
                        } else mbar_wait(bar + 8 * (B_GO + ph), 0);
                        bulk_load(sb + OFF_B + s * BLK, src, BLK, fb);
                        TS(134 + 16 + 2 * (ph > 0) + r - r_o);
                    }
                }
            }
        } else if (warp == 14) {
            uint8_t* stcell = scr + G_STATS + ((lane & 1) * 1024 + 8 * b + (lane >> 1)) * 16;
            if (lane < 16) cell_put(stcell, 0, 0, 0);
            const unsigned ev = ld_relaxed(ctr + C_LN);
            uint8_t* hb = scr + G_HIMG + (b & ~3) * BLK;
            const unsigned e1 = (ev >> 7) + 1;
            if (lane == 0) {
                *reinterpret_cast<volatile unsigned*>(smem + OFF_EP) = e1;
                mbar_arrive(bar + 8 * B_EP);
                TS(36);
            }
            bar_sync<10, 288>();
            if (elect()) {
                fence_async_smem();
                TS(42);
                tma4d_store(&mp.hst, sb + OFF_A, 0, 0, b & 3, b & ~3);
                bulk_commit();
            }
            __syncwarp();
            if (lane < 16) {
                const uint2 v = reinterpret_cast<const uint2*>(smem + OFF_LNST)[lane];
                cell_put(stcell, v.x, v.y, e1);
            }
            const uint8_t* hl = hb + ((b & 3) * 28 + min(lane, 27)) * 128;
            mbar_wait(bar + 8 * B_LNIN, (uint64_t)hl >> 63);
            bulk_wait_all();
            __syncwarp();
            mbar_arrive_if0(bar + 8 * B_LNFREE, lane);
            TS(63);
            unsigned rb = 0;
#pragma unroll
            for (int i = 0; i < 4; i++) rb |= ld_relaxed(reinterpret_cast<const unsigned*>(hl + i * BLK));
            if (elect()) {
                red_relaxed(ctr + C_LN, 1 + (rb & (sb >> 31)));
                TS(37);
#pragma unroll 1
                for (int ph = 1; ph < 4; ph++) {
                    mbar_wait(bar + 8 * (ph == 1 ? B_HALO : g1 ? B_RECV1 : B_OST), 0);
                    poll(ctr + ph * 32 + (ph >> 1) * z * 64, e1 * (ph == 1 ? 16 : 56));
                    fence_async_global();
                    mbar_arrive(bar + 8 * (B_GO + ph));
                    if (ph != 1) TS(32 + ph);
                }
            }
        } else {
            if ((sb & 0x3FFFF) != SB0) __trap();
            if (elect()) {
#pragma unroll 1
                for (int i = 3; i < 10; i++) asm volatile("prefetch.tensormap [%0];" ::"l"(reinterpret_cast<const CUtensorMap*>(&mp) + i) : "memory");
            }
            __syncwarp();
            mbar_watch(bar + 8 * B_KV, 0);
#pragma unroll 1
            for (int i = g1 ? 0 : 8; i < 8; i++) {
                uint32_t l = 56 * z + (i & 3) * 14 + min(lane >> 1, 13);
                if (q >= 7 && l >= 16) l += l < 64 ? 48 : -48;
                cell_put(scr + G_BIMG + ((8 + 2 * q + (i >> 2)) * 4 + j) * BLK + l * 128 + (l & 24) * 4 + (lane & 1) * 16, ~0u, ~0u, ~0u);
            }
            __threadfence();
            __syncwarp();
            mbar_arrive_if0(bar + 8 * B_FREE, lane);
            TS(59);
#pragma unroll 1
            for (int i = g1 ? 0 : 2; i < 2; i++) {
                mbar_watch(bar + 8 * (B_RECV1 + i), 0);
                delay(DU);
                if (lane == 0) red_relaxed(ctr + C_U + ((q >= 7 ? 2 : 0) + i) * 32, 1);
                TS(22 + i);
            }
            mbar_watch(bar + 8 * B_FREE, 0);
            mbar_watch(bar + 8 * B_RECV2, 0);
            mbar_watch(bar + 8 * (B_RECV2 + 1), 0);
        }
    }
}

typedef CUresult (*EncodeFn)(CUtensorMap*, CUtensorMapDataType, cuuint32_t, void*, const cuuint64_t*, const cuuint64_t*, const cuuint32_t*,
                             const cuuint32_t*, CUtensorMapInterleave, CUtensorMapSwizzle, CUtensorMapL2promotion, CUtensorMapFloatOOBfill);

void encode(EncodeFn fn, CUtensorMap* m, const void* p, int rank, const cuuint64_t* dims, const cuuint64_t* strides, const cuuint32_t* box, bool swz) {
    const cuuint32_t es[4] = {1, 1, 1, 1};
    fn(m, CU_TENSOR_MAP_DATA_TYPE_BFLOAT16, rank, const_cast<void*>(p), dims, strides, box, es, CU_TENSOR_MAP_INTERLEAVE_NONE,
       swz ? CU_TENSOR_MAP_SWIZZLE_128B : CU_TENSOR_MAP_SWIZZLE_NONE, CU_TENSOR_MAP_L2_PROMOTION_L2_128B, CU_TENSOR_MAP_FLOAT_OOB_FILL_NONE);
}

}

extern "C" void kernel_launch(void* const* d_in, const int* in_sizes, int n_in, void* d_out, int out_size) {
    const __nv_bfloat16* x = (const __nv_bfloat16*)d_in[0];
    const __nv_bfloat16* wqkv = (const __nv_bfloat16*)d_in[1];
    const __nv_bfloat16* wo = (const __nv_bfloat16*)d_in[2];
    const __nv_bfloat16* w1 = (const __nv_bfloat16*)d_in[4];
    const __nv_bfloat16* b1 = (const __nv_bfloat16*)d_in[5];
    const __nv_bfloat16* w2 = (const __nv_bfloat16*)d_in[6];
    const __nv_bfloat16* b2 = (const __nv_bfloat16*)d_in[7];

    void* fp = nullptr;
    cudaDriverEntryPointQueryResult qr;
    cudaGetDriverEntryPoint("cuTensorMapEncodeTiled", &fp, cudaEnableDefault, &qr);
    EncodeFn fn = (EncodeFn)fp;
    void* sp = nullptr;
    cudaGetSymbolAddress(&sp, g_scratch);
    uint8_t* scr = (uint8_t*)sp;
    void *o = scr + G_O, *himg = scr + G_HIMG;

    Maps mp;
    { cuuint64_t d[3] = {64, 2048, 7}, s[2] = {896, 128}; cuuint32_t bx[3] = {64, 16, 7}; encode(fn, &mp.xl, x, 3, d, s, bx, true); }
    { cuuint64_t d[2] = {896, 1024}, s[1] = {1792}; cuuint32_t bx[2] = {64, 128}; encode(fn, &mp.x, x, 2, d, s, bx, true); }
    { cuuint64_t d[3] = {448, 448, 3}, s[2] = {2688, 896}; cuuint32_t bx[3] = {64, 32, 3}; encode(fn, &mp.wqkv, wqkv, 3, d, s, bx, true); }
    { cuuint64_t d[3] = {64, 2048, 28}, s[2] = {3584, 128}; cuuint32_t bx[3] = {64, 64, 2}; encode(fn, &mp.w1, w1, 3, d, s, bx, true); }
    { cuuint64_t d[3] = {64, 1792, 32}, s[2] = {4096, 128}; cuuint32_t bx[3] = {64, 64, 2}; encode(fn, &mp.w2, w2, 3, d, s, bx, true); }
    { cuuint64_t d[4] = {64, 28, 4, 128}, s[3] = {128, 3584, BLK}; cuuint32_t bx[4] = {64, 28, 1, 4}; encode(fn, &mp.hst, himg, 4, d, s, bx, false); }
    { cuuint64_t d[2] = {448, 2048}, s[1] = {896}; cuuint32_t bx[2] = {64, 128}; encode(fn, &mp.xn, x, 2, d, s, bx, true); }
    { cuuint64_t d[2] = {64, 8 * 2048}, s[1] = {128}; cuuint32_t bx[2] = {64, 128}; encode(fn, &mp.old_, o, 2, d, s, bx, true); }
    { cuuint64_t d[2] = {128, 8 * 1024}, s[1] = {256}; cuuint32_t bx[2] = {64, 32}; encode(fn, &mp.ost, o, 2, d, s, bx, true); }
    { cuuint64_t d[4] = {8, 56, 56, 8}, s[3] = {896, 16, 56 * 896}; cuuint32_t bx[4] = {8, 64, 14, 1}; encode(fn, &mp.wo, wo, 4, d, s, bx, false); }

    cudaFuncSetAttribute(fused_kernel, cudaFuncAttributeMaxDynamicSharedMemorySize, SMEM_BYTES);
    fused_kernel<<<128, 512, SMEM_BYTES>>>(x, b1, b2, scr, (uint8_t*)d_out, mp);
}
```

```cpp
#include <cuda_runtime.h>
#include <cuda.h>
#include <cuda_bf16.h>
#include <stdint.h>

namespace {

constexpr int S_ = 2048, D_ = 448;
constexpr uint32_t BLK = 14336;

constexpr uint32_t G_HIMG = 0;
constexpr uint32_t G_BIMG = G_HIMG + 32 * 4 * BLK;
constexpr uint32_t G_O = G_BIMG + 36 * 4 * BLK;
constexpr uint32_t G_STATS = G_O + 8 * S_ * 128;
constexpr uint32_t G_CS = G_STATS + S_ * 16;
constexpr uint32_t G_HALO = G_CS + 8 * 4 * 2048;
constexpr uint32_t G_CTR = G_HALO + 128 * 3584;
constexpr uint32_t G_END = G_CTR + (192 + 16 * 32) * 4;
__device__ __align__(1024) uint8_t g_scratch[G_END];

constexpr int C_LN = 0, C_WO = 32, C_U = 64, C_O = 192;

#define TSX(sel, id)
#define TS(id)
#define TS0(id)
#define TSH(id)
#define TSW(id)
#define TG(id)

#define TSG1 0
#define TSD(id)
constexpr int QDEPTH = 3;
constexpr int KS = 3;
constexpr int GATHER = 4;
constexpr uint32_t NE = 2;
constexpr uint32_t PRE0 = 9, PRE1 = 6;
constexpr uint32_t ATT_STEP = 10, GS = 12;
constexpr int NS2 = 3;
constexpr uint32_t DLY1 = 2200, DLY2 = 1600, DH = 400, DO = 100, DU = 120, DW = 400;

constexpr uint32_t OFF_A = 0;
constexpr uint32_t OFF_B = 98304;
constexpr uint32_t OFF_X = 184320;
constexpr uint32_t OFF_K = 196608;
constexpr uint32_t OFF_V = OFF_K + 9 * 896;
constexpr uint32_t OFF_OST = OFF_X, OFF_RECV2 = OFF_X, OFF_RECV1 = OFF_X + 16384, OFF_OUT = OFF_X + 16384;
constexpr uint32_t OFF_SA = OFF_X, OFF_SB = OFF_RECV1 + BLK;
constexpr uint32_t OFF_CSB = 221184;
constexpr uint32_t OFF_ONES = OFF_CSB + 3072;
constexpr uint32_t OFF_STATS = OFF_ONES + 512;
constexpr uint32_t OFF_BIAS = OFF_STATS + 1024;
constexpr uint32_t OFF_LNX = OFF_BIAS + 1024;
constexpr uint32_t OFF_RSTD = OFF_LNX + 512;
constexpr uint32_t OFF_LNST = 229376;
constexpr uint32_t OFF_EP = OFF_LNST + 128;
constexpr uint32_t OFF_BAR = OFF_EP + 16;
constexpr uint32_t OFF_TS = OFF_BAR + 8 * 48;
constexpr uint32_t SMEM_BYTES = OFF_TS;

enum : int {
    B_FULLQ = 0, B_LNIN = 7, B_EMPTYQ = 8, B_FULL = 15, B_EMPTY = 22, B_AUX = 29, B_QKV, B_HALO, B_FREE, B_RECV1, B_RECV2 = B_RECV1 + 2,
    B_EP = B_RECV2 + 2, B_OST, B_LNFREE, B_UDONE, B_NONE, B_GO, B_XR = B_GO + 4, B_KV, B_COUNT, B_LAND = B_FULLQ
};
constexpr uint32_t XSLOT = 0x5432154u;
constexpr uint32_t WSLOT = 0x3421034u;

__device__ __forceinline__ uint32_t smem_u32(const void* p) { return (uint32_t)__cvta_generic_to_shared(p); }
__device__ __forceinline__ void mbar_init(uint32_t a, int c) { asm volatile("mbarrier.init.shared::cta.b64 [%0], %1;" ::"r"(a), "r"(c) : "memory"); }
__device__ __forceinline__ void mbar_expect(uint32_t a, uint32_t b) { asm volatile("mbarrier.arrive.expect_tx.shared::cta.b64 _, [%0], %1;" ::"r"(a), "r"(b) : "memory"); }
__device__ __forceinline__ void mbar_arrive(uint32_t a) { asm volatile("mbarrier.arrive.shared::cta.b64 _, [%0];" ::"r"(a) : "memory"); }
__device__ __forceinline__ void mbar_arrive_if0(uint32_t a, uint32_t sel) {
    asm volatile("{\n.reg .pred p;\nsetp.eq.u32 p, %1, 0;\n@p mbarrier.arrive.shared::cta.b64 _, [%0];\n}" ::"r"(a), "r"(sel) : "memory");
}
__device__ __forceinline__ void mbar_wait(uint32_t a, uint32_t parity) {
    asm volatile("{\n.reg .pred p;\nW0:\nmbarrier.try_wait.parity.shared::cta.b64 p, [%0], %1;\n@!p bra W0;\n}\n" ::"r"(a), "r"(parity) : "memory");
}
__device__ __forceinline__ void mbar_watch(uint32_t a, uint32_t parity) {
    asm volatile(
        "{\n.reg .pred p;\n.reg .u32 n;\nmov.u32 n, 0;\n"
        "W0:\nmbarrier.try_wait.parity.shared::cta.b64 p, [%0], %1;\n@p bra W1;\n"
        "add.u32 n, n, 1;\nsetp.lt.u32 p, n, 1048576;\n@p bra W0;\ntrap;\nW1:\n}\n" ::"r"(a), "r"(parity) : "memory");
}
__device__ __forceinline__ bool elect() {
    uint32_t r;
    asm volatile("{\n.reg .pred p;\nelect.sync _|p, 0xffffffff;\nselp.u32 %0, 1, 0, p;\n}" : "=r"(r));
    return r;
}
__device__ __forceinline__ uint32_t mapa(uint32_t a, uint32_t cta) { uint32_t r; asm("mapa.shared::cluster.u32 %0, %1, %2;" : "=r"(r) : "r"(a), "r"(cta)); return r; }
__device__ __forceinline__ void tma2d(uint32_t dst, const CUtensorMap* m, int c0, int c1, uint32_t bar) {
    asm volatile("cp.async.bulk.tensor.2d.shared::cluster.global.mbarrier::complete_tx::bytes [%0], [%1, {%3, %4}], [%2];" ::"r"(dst), "l"(m), "r"(bar), "r"(c0), "r"(c1) : "memory");
}
__device__ __forceinline__ void tma3d(uint32_t dst, const CUtensorMap* m, int c0, int c1, int c2, uint32_t bar) {
    asm volatile("cp.async.bulk.tensor.3d.shared::cluster.global.mbarrier::complete_tx::bytes [%0], [%1, {%3, %4, %5}], [%2];" ::"r"(dst), "l"(m), "r"(bar), "r"(c0), "r"(c1), "r"(c2) : "memory");
}
__device__ __forceinline__ void tma3d_mc(uint32_t dst, const CUtensorMap* m, int c0, int c1, int c2, uint32_t bar) {
    asm volatile("cp.async.bulk.tensor.3d.shared::cluster.global.mbarrier::complete_tx::bytes.multicast::cluster [%0], [%1, {%3, %4, %5}], [%2], %6;"
                 ::"r"(dst), "l"(m), "r"(bar), "r"(c0), "r"(c1), "r"(c2), "h"((uint16_t)3) : "memory");
}
__device__ __forceinline__ void tma2d_store(const CUtensorMap* m, uint32_t src, int c0, int c1) {
    asm volatile("cp.async.bulk.tensor.2d.global.shared::cta.bulk_group [%0, {%2, %3}], [%1];" ::"l"(m), "r"(src), "r"(c0), "r"(c1) : "memory");
}
__device__ __forceinline__ void tma4d_store(const CUtensorMap* m, uint32_t src, int c0, int c1, int c2, int c3) {
    asm volatile("cp.async.bulk.tensor.4d.global.shared::cta.bulk_group [%0, {%2, %3, %4, %5}], [%1];" ::"l"(m), "r"(src), "r"(c0), "r"(c1), "r"(c2), "r"(c3) : "memory");
}
__device__ __forceinline__ void tma4d(uint32_t dst, const CUtensorMap* m, int c0, int c1, int c2, int c3, uint32_t bar) {
    asm volatile("cp.async.bulk.tensor.4d.shared::cluster.global.mbarrier::complete_tx::bytes [%0], [%1, {%3, %4, %5, %6}], [%2];" ::"r"(dst), "l"(m), "r"(bar), "r"(c0), "r"(c1), "r"(c2), "r"(c3) : "memory");
}
__device__ __forceinline__ void bulk_load(uint32_t dst, const void* src, uint32_t bytes, uint32_t bar) {
    asm volatile("cp.async.bulk.shared::cluster.global.mbarrier::complete_tx::bytes [%0], [%1], %2, [%3];" ::"r"(dst), "l"(src), "r"(bytes), "r"(bar) : "memory");
}
__device__ __forceinline__ void bulk_store(void* dst, uint32_t src, uint32_t bytes) {
    asm volatile("cp.async.bulk.global.shared::cta.bulk_group [%0], [%1], %2;" ::"l"(dst), "r"(src), "r"(bytes) : "memory");
}
__device__ __forceinline__ void bulk_commit() { asm volatile("cp.async.bulk.commit_group;" ::: "memory"); }
__device__ __forceinline__ void bulk_wait_all() { asm volatile("cp.async.bulk.wait_group 0;" ::: "memory"); }
template <int N> __device__ __forceinline__ void bulk_wait_read() { asm volatile("cp.async.bulk.wait_group.read %0;" ::"n"(N) : "memory"); }
__device__ __forceinline__ void l2_prefetch_lt(const void* p, uint32_t i, uint32_t n) {
    asm volatile("{\n.reg .pred p;\nsetp.lt.u32 p, %1, %2;\n@p prefetch.global.L2 [%0];\n}" ::"l"(p), "r"(i), "r"(n));
}
__device__ __forceinline__ void fence_async_smem() { asm volatile("fence.proxy.async.shared::cta;" ::: "memory"); }
__device__ __forceinline__ void fence_async_global() { asm volatile("fence.proxy.async.global;" ::: "memory"); }
__device__ __forceinline__ void red_relaxed(unsigned* p, unsigned v) { asm volatile("red.relaxed.gpu.global.add.u32 [%0], %1;" ::"l"(p), "r"(v) : "memory"); }
__device__ __forceinline__ void publish(unsigned* p) {
    asm volatile("fence.proxy.async.global;\nred.release.gpu.global.add.u32 [%0], 1;" ::"l"(p) : "memory");
}
__device__ __forceinline__ void stg32(void* p, uint32_t v) { asm volatile("st.relaxed.gpu.global.b32 [%0], %1;" ::"l"(p), "r"(v) : "memory"); }
__device__ __forceinline__ unsigned ld_relaxed(const unsigned* p) { unsigned v; asm volatile("ld.relaxed.gpu.global.u32 %0, [%1];" : "=r"(v) : "l"(p) : "memory"); return v; }
__device__ __forceinline__ bool ctr_done(unsigned v, unsigned target) { return ((v - target) & 0x1FFFFFFu) == 0; }
__device__ __forceinline__ uint32_t clock32() { uint32_t c; asm volatile("mov.u32 %0, %%clock;" : "=r"(c)::"memory"); return c; }
__device__ __forceinline__ void delay(uint32_t n) { const uint32_t t0 = clock32(); while (clock32() - t0 < n) {} }
__device__ __forceinline__ void poll(const unsigned* p, unsigned target) { while (!ctr_done(ld_relaxed(p), target)) {} }
__device__ __forceinline__ void cell_put(void* p, uint32_t a, uint32_t b, uint32_t tag) {
    asm volatile("st.relaxed.gpu.global.v4.b32 [%0], {%1, %3, %2, %3};" ::"l"(p), "r"(a), "r"(b), "r"(tag) : "memory");
}
__device__ __forceinline__ uint32_t cell_get(const void* p, uint32_t& a, uint32_t& b, uint32_t tag) {
    uint32_t t0, t1;
    asm volatile("ld.relaxed.gpu.global.v4.b32 {%0, %1, %2, %3}, [%4];" : "=r"(a), "=r"(t0), "=r"(b), "=r"(t1) : "l"(p) : "memory");
    return (t0 ^ tag) | (t1 ^ tag);
}
__device__ __forceinline__ void after(uint32_t zero) { asm volatile("{\n.reg .pred p;\nsetp.ne.u32 p, %0, 0;\n@p trap;\n}" ::"r"(zero) : "memory"); }
template <int ID, int N> __device__ __forceinline__ void bar_sync() { asm volatile("bar.sync %0, %1;" ::"n"(ID), "n"(N) : "memory"); }
template <int ID = 4> __device__ __forceinline__ void gate_wait(uint32_t on) { asm volatile("{\n.reg .pred p;\nsetp.ne.u32 p, %0, 0;\n@p bar.sync %1, 256;\n}" ::"r"(on), "n"(ID) : "memory"); }
template <int ID = 4> __device__ __forceinline__ void gate_open(uint32_t off) { asm volatile("{\n.reg .pred p;\nsetp.eq.u32 p, %0, 0;\n@p bar.arrive %1, 256;\n}" ::"r"(off), "n"(ID) : "memory"); }
__device__ __forceinline__ void wg_fence() { asm volatile("wgmma.fence.sync.aligned;" ::: "memory"); }
__device__ __forceinline__ void wg_commit() { asm volatile("wgmma.commit_group.sync.aligned;" ::: "memory"); }
template <int N> __device__ __forceinline__ void wg_wait() { asm volatile("wgmma.wait_group.sync.aligned %0;" ::"n"(N) : "memory"); }
template <int LO = 0, int HI = 56, int N> __device__ __forceinline__ void pin(float (&a)[N]) {
#pragma unroll
    for (int i = LO; i < (HI < N ? HI : N); i++) asm volatile("" : "+f"(a[i])::"memory");
}
__device__ __forceinline__ uint32_t ldg_u16(const void* p) {
    uint32_t v;
    asm volatile("ld.global.nc.u16 %0, [%1];" : "=r"(v) : "l"(p) : "memory");
    return v;
}
__device__ __forceinline__ uint32_t pack2(float lo, float hi) { uint32_t r; asm("cvt.rn.bf16x2.f32 %0, %1, %2;" : "=r"(r) : "f"(hi), "f"(lo)); return r; }
__device__ __forceinline__ float bf_lo(uint32_t v) { return __uint_as_float(v << 16); }
__device__ __forceinline__ float bf_hi(uint32_t v) { return __uint_as_float(v & 0xFFFF0000u); }
__device__ __forceinline__ uint32_t split2(float x) { return pack2(x, x - bf_lo(pack2(x, 0.f))); }
__device__ __forceinline__ void stsm4(uint32_t a, uint32_t r0, uint32_t r1, uint32_t r2, uint32_t r3) {
    asm volatile("stmatrix.sync.aligned.m8n8.x4.shared.b16 [%0], {%1, %2, %3, %4};" ::"r"(a), "r"(r0), "r"(r1), "r"(r2), "r"(r3) : "memory");
}
__device__ __forceinline__ void stsm2(uint32_t a, uint32_t r0, uint32_t r1) {
    asm volatile("stmatrix.sync.aligned.m8n8.x2.shared.b16 [%0], {%1, %2};" ::"r"(a), "r"(r0), "r"(r1) : "memory");
}
__device__ __forceinline__ void ldsm4(uint32_t a, uint32_t (&r)[4]) {
    asm volatile("ldmatrix.sync.aligned.m8n8.x4.shared.b16 {%0, %1, %2, %3}, [%4];" : "=r"(r[0]), "=r"(r[1]), "=r"(r[2]), "=r"(r[3]) : "r"(a) : "memory");
}
__device__ __forceinline__ void ldsm4t(uint32_t a, uint32_t (&r)[4]) {
    asm volatile("ldmatrix.sync.aligned.m8n8.x4.trans.shared.b16 {%0, %1, %2, %3}, [%4];" : "=r"(r[0]), "=r"(r[1]), "=r"(r[2]), "=r"(r[3]) : "r"(a) : "memory");
}
__device__ __forceinline__ void mma16816(float (&c)[4], uint32_t a0, uint32_t a1, uint32_t a2, uint32_t a3, uint32_t b0, uint32_t b1) {
    asm volatile("mma.sync.aligned.m16n8k16.row.col.f32.bf16.bf16.f32 {%0,%1,%2,%3}, {%4,%5,%6,%7}, {%8,%9}, {%0,%1,%2,%3};"
                 : "+f"(c[0]), "+f"(c[1]), "+f"(c[2]), "+f"(c[3]) : "r"(a0), "r"(a1), "r"(a2), "r"(a3), "r"(b0), "r"(b1));
}
__device__ __forceinline__ void mma1688(float (&c)[4], uint32_t a0, uint32_t a1, uint32_t b0) {
    asm volatile("mma.sync.aligned.m16n8k8.row.col.f32.bf16.bf16.f32 {%0,%1,%2,%3}, {%4,%5}, {%6}, {%0,%1,%2,%3};"
                 : "+f"(c[0]), "+f"(c[1]), "+f"(c[2]), "+f"(c[3]) : "r"(a0), "r"(a1), "r"(b0));
}
constexpr uint32_t SB0 = 1024;
__device__ __forceinline__ uint32_t desc_lo(uint32_t off, uint32_t lbo) { return ((SB0 + off) >> 4) + ((lbo >> 4) << 16); }
constexpr uint32_t H_SW = (1024 >> 4) | (1u << 30), H_H = 128 >> 4, H_U = 1024 >> 4;
__device__ __forceinline__ float ex2(float x) { float r; asm("ex2.approx.ftz.f32 %0, %1;" : "=f"(r) : "f"(x)); return r; }
__device__ __forceinline__ float rsq(float x) { float r; asm("rsqrt.approx.ftz.f32 %0, %1;" : "=f"(r) : "f"(x)); return r; }
__device__ __forceinline__ float rcp(float x) { float r; asm("rcp.approx.ftz.f32 %0, %1;" : "=f"(r) : "f"(x)); return r; }

template <uint32_t HB, int TB>
__device__ __forceinline__ void wgmma_n56_rs(float (&d)[28], const uint32_t (&a)[4], uint32_t lb, int scale_d) {
    asm volatile("{\n.reg .pred p;\n.reg .b64 db;\nsetp.ne.b32 p, %33, 0;\nmov.b64 db, {%32, %34};\n"
        "wgmma.mma_async.sync.aligned.m64n56k16.f32.bf16.bf16 "
        "{%0, %1, %2, %3, %4, %5, %6, %7, %8, %9, %10, %11, %12, %13, %14, %15, %16, %17, %18, %19, %20, %21, %22, %23, %24, %25, %26, %27}, "
        "{%28, %29, %30, %31}, db, p, 1, 1, %35;\n}\n"
        : "+f"(d[0]), "+f"(d[1]), "+f"(d[2]), "+f"(d[3]), "+f"(d[4]), "+f"(d[5]), "+f"(d[6]), "+f"(d[7]), "+f"(d[8]), "+f"(d[9]), "+f"(d[10]), "+f"(d[11]), "+f"(d[12]), "+f"(d[13]), "+f"(d[14]), "+f"(d[15]), "+f"(d[16]), "+f"(d[17]), "+f"(d[18]), "+f"(d[19]), "+f"(d[20]), "+f"(d[21]), "+f"(d[22]), "+f"(d[23]), "+f"(d[24]), "+f"(d[25]), "+f"(d[26]), "+f"(d[27])
        : "r"(a[0]), "r"(a[1]), "r"(a[2]), "r"(a[3]), "r"(lb), "r"(scale_d), "n"(HB), "n"(TB));
}
template <int TA, uint32_t HA, uint32_t HB>
__device__ __forceinline__ void wgmma_n112(float (&d)[56], uint32_t la, uint32_t lb, int scale_d = 1) {
    asm volatile("{\n.reg .b64 da, db;\n.reg .pred p;\nsetp.ne.b32 p, %61, 0;\nmov.b64 da, {%56, %59};\nmov.b64 db, {%57, %60};\n"
        "wgmma.mma_async.sync.aligned.m64n112k16.f32.bf16.bf16 "
        "{%0, %1, %2, %3, %4, %5, %6, %7, %8, %9, %10, %11, %12, %13, %14, %15, %16, %17, %18, %19, %20, %21, %22, %23, %24, %25, %26, %27, %28, %29, %30, %31, %32, %33, %34, %35, %36, %37, %38, %39, %40, %41, %42, %43, %44, %45, %46, %47, %48, %49, %50, %51, %52, %53, %54, %55}, "
        "da, db, p, 1, 1, %58, 1;\n}\n"
        : "+f"(d[0]), "+f"(d[1]), "+f"(d[2]), "+f"(d[3]), "+f"(d[4]), "+f"(d[5]), "+f"(d[6]), "+f"(d[7]), "+f"(d[8]), "+f"(d[9]), "+f"(d[10]), "+f"(d[11]), "+f"(d[12]), "+f"(d[13]), "+f"(d[14]), "+f"(d[15]), "+f"(d[16]), "+f"(d[17]), "+f"(d[18]), "+f"(d[19]), "+f"(d[20]), "+f"(d[21]), "+f"(d[22]), "+f"(d[23]), "+f"(d[24]), "+f"(d[25]), "+f"(d[26]), "+f"(d[27]), "+f"(d[28]), "+f"(d[29]), "+f"(d[30]), "+f"(d[31]), "+f"(d[32]), "+f"(d[33]), "+f"(d[34]), "+f"(d[35]), "+f"(d[36]), "+f"(d[37]), "+f"(d[38]), "+f"(d[39]), "+f"(d[40]), "+f"(d[41]), "+f"(d[42]), "+f"(d[43]), "+f"(d[44]), "+f"(d[45]), "+f"(d[46]), "+f"(d[47]), "+f"(d[48]), "+f"(d[49]), "+f"(d[50]), "+f"(d[51]), "+f"(d[52]), "+f"(d[53]), "+f"(d[54]), "+f"(d[55])
        : "r"(la), "r"(lb), "n"(TA), "n"(HA), "n"(HB), "r"(scale_d));
}
template <int TA, uint32_t HA, uint32_t HB>
__device__ __forceinline__ void wgmma_n8(float (&d)[4], uint32_t la, uint32_t lb, int scale_d = 1) {
    asm volatile("{\n.reg .b64 da, db;\n.reg .pred p;\nsetp.ne.b32 p, %9, 0;\nmov.b64 da, {%4, %7};\nmov.b64 db, {%5, %8};\n"
        "wgmma.mma_async.sync.aligned.m64n8k16.f32.bf16.bf16 "
        "{%0, %1, %2, %3}, "
        "da, db, p, 1, 1, %6, 1;\n}\n"
        : "+f"(d[0]), "+f"(d[1]), "+f"(d[2]), "+f"(d[3])
        : "r"(la), "r"(lb), "n"(TA), "n"(HA), "n"(HB), "r"(scale_d));
}

__device__ __forceinline__ void send4(uint32_t rbuf, uint32_t rbar, uint32_t w0, uint32_t w1, uint32_t w2, uint32_t w3, uint32_t on) {
    asm volatile("{\n.reg .pred p;\nsetp.ne.u32 p, %6, 0;\n@p st.async.weak.shared::cluster.mbarrier::complete_tx::bytes.v4.b32 [%0], {%1,%2,%3,%4}, [%5];\n}"
                 ::"r"(rbuf), "r"(w0), "r"(w1), "r"(w2), "r"(w3), "r"(rbar), "r"(on) : "memory");
}
__device__ __forceinline__ void send_half(const float (&a)[56], uint32_t rbuf, uint32_t rbar, int t, uint32_t on) {
#pragma unroll
    for (int i = 28; i < 52; i += 8)
        send4(rbuf + (i - 28) * 256 + t * 16, rbar, pack2(a[i], a[i + 1]), pack2(a[i + 2], a[i + 3]), pack2(a[i + 4], a[i + 5]), pack2(a[i + 6], a[i + 7]), on);
    asm volatile("{\n.reg .pred p;\nsetp.ne.u32 p, %4, 0;\n@p st.async.weak.shared::cluster.mbarrier::complete_tx::bytes.v2.b32 [%0], {%1,%2}, [%3];\n}"
                 ::"r"(rbuf + 6144 + t * 8), "r"(pack2(a[52], a[53])), "r"(pack2(a[54], a[55])), "r"(rbar), "r"(on) : "memory");
}
__device__ __forceinline__ void recv_half(uint32_t (&p)[14], uint32_t buf, int t) {
#pragma unroll
    for (int i = 0; i < 3; i++)
        asm volatile("ld.shared.v4.b32 {%0,%1,%2,%3}, [%4];" : "=r"(p[4 * i]), "=r"(p[4 * i + 1]), "=r"(p[4 * i + 2]), "=r"(p[4 * i + 3]) : "r"(buf + i * 2048 + t * 16) : "memory");
    asm volatile("ld.shared.v2.b32 {%0,%1}, [%2];" : "=r"(p[12]), "=r"(p[13]) : "r"(buf + 6144 + t * 8) : "memory");
}

struct Maps { CUtensorMap xl, x, wqkv, hst, w1, w2, xn, old_, ost, wo; };

__global__ void __cluster_dims__(2, 1, 1) __launch_bounds__(512, 1)
fused_kernel(const __nv_bfloat16* __restrict__ x, const __nv_bfloat16* __restrict__ b1, const __nv_bfloat16* __restrict__ b2, uint8_t* __restrict__ scr,
             uint8_t* __restrict__ out, const __grid_constant__ Maps mp) {
    extern __shared__ __align__(1024) uint8_t smem[];
    const uint32_t sb = smem_u32(smem);
    const uint32_t bar = sb + OFF_BAR;
    const int tid = threadIdx.x, lane = tid & 31;
    const int b = blockIdx.x, z = b & 1, c = b >> 1;
    unsigned* const ctr = reinterpret_cast<unsigned*>(scr + G_CTR);
    l2_prefetch_lt(reinterpret_cast<const uint8_t*>(x) + (b * 112 + tid) * 128, tid, 112);
    const uint32_t t_in = clock32();
    TS0(0);
    TG(60);
    const int warp = __shfl_sync(0xffffffffu, tid >> 5, 0);
    const int j = c < 4 ? c : c < 36 ? (c - 4) >> 3 : ((c - 36) * 37) >> 8, q = c < 4 ? 15 : c < 36 ? (c - 4) & 7 : c - 28 - 7 * j;
    const bool g1 = q < 14;
    const int R = q < 8 ? q : (0x27654310u >> (4 * q - 32)) & 7, P = (q >> 3) * 4 + j;
    auto krow = [&](int kb) { const int k = kb + (R & 6); return (k >= 7 ? k - 7 : k) * 64; };
    auto x_load = [&](int kb) {
        mbar_expect(bar + 8 * (B_FULLQ + kb), 40960);
        tma2d(sb + OFF_A + ((XSLOT >> (4 * kb)) & 7) * 16384, &mp.x, z * D_ + krow(kb), R * 128, bar + 8 * (B_FULLQ + kb));
    };
    auto w_load = [&](int kb) {
        tma3d_mc(sb + OFF_B + ((WSLOT >> (4 * kb)) & 7) * 24576 + z * 12288, &mp.wqkv, (P * 56) & ~15, krow(kb) + z * 32, 0, bar + 8 * (B_FULLQ + kb));
    };
    if (warp == 12 && elect()) {
#pragma unroll
        for (int i = B_FULLQ; i < B_EMPTYQ; i++) mbar_init(bar + 8 * i, 1);
        mbar_expect(bar + 8 * B_LNIN, BLK);
        tma3d(sb + OFF_A, &mp.xl, 0, 16 * b, 0, bar + 8 * B_LNIN);
        x_load(0);
        TS(15);
    }
    auto bar_count = [&](int i) {
        return i < B_FULL ? (i < B_EMPTYQ + 2 ? 24 : 8) : i < B_EMPTY || i == B_FREE ? 2 : (i < B_AUX || i == B_NONE || i == B_OST) ? 8 : i == B_KV ? 12
               : (i == B_AUX || i == B_HALO) ? 4 : 1;
    };
    if (warp == 13 && elect()) {
#pragma unroll
        for (int i = B_EMPTYQ; i < B_COUNT; i++) mbar_init(bar + 8 * i, bar_count(i));
#pragma unroll
        for (int i = B_RECV1; i < B_EP; i++) mbar_expect(bar + 8 * i, i < B_RECV2 ? 7168 : 8192 - 2048 * z);
    }
    asm volatile("fence.mbarrier_init.release.cluster;" ::: "memory");
    __syncwarp();
    asm volatile("barrier.cluster.arrive.relaxed.aligned;\nbarrier.cluster.wait.aligned;" ::: "memory");
    if (warp == 12 && elect()) { w_load(0); TS(16); }
    auto slot = [](uint32_t r) { return r - 6 * ((r * 43) >> 8); };
    auto phase = [](uint32_t r) { return ((r * 43) >> 8) & 1; };
    const uint32_t r_o = g1 ? 16 : 0, r_u = r_o + 3;
    auto xslot = [&](uint32_t i) { return i == 1 ? 6 : slot(r_o + i - (i > 1)); };
    auto aoff = [](uint32_t s) { return s == 6 ? OFF_SA - OFF_A : s * 16384; };
    auto fetch_x = [&](uint32_t i, bool arm = true) {
        const uint32_t s = xslot(i), lb = bar + 8 * (B_LAND + s);
        if (arm) mbar_expect(lb, i < 4 ? 16384 : BLK);
        if (i < 4) tma2d(sb + OFF_A + aoff(s), &mp.old_, 0, (4 * z + i) * S_ + q * 128, lb);
        else bulk_load(sb + OFF_B + s * BLK, scr + G_BIMG + ((14 * z + (i < 11 ? 2 * i : 2 * i - 13)) * 4 + j) * BLK, BLK, lb);
    };
    auto epoch = [&]() { mbar_wait(bar + 8 * B_EP, 0); return *reinterpret_cast<volatile unsigned*>(smem + OFF_EP); };

    if (warp < 8) {
        const int wg = warp >> 2, w4 = warp & 3, t = tid & 127, g = lane >> 2, tq = lane & 3;
        asm volatile("setmaxnreg.inc.sync.aligned.u32 208;");
        uint32_t xa[4];
#pragma unroll
        for (int k = 0; k < 4; k++) xa[k] = sb + OFF_A + (warp * 16 + (lane & 15)) * 128 + (((2 * k + (lane >> 4)) ^ (lane & 7)) << 4);
        {
            const int rg = warp & 1, jq = warp >> 1;
            const uint32_t ex = sb + OFF_LNX + (rg * 8 + g) * 32, ew = ex + jq * 8, ls = sb + OFF_LNST + (rg * 8 + g) * 8;
            const uint32_t l0 = sb + OFF_A + rg * 1024 + g * 144;
            uint32_t r[4][4], la[4], ha[4], x0, dep = ex | ew | ls | l0;
#pragma unroll
            for (int i = 0; i < 4; i++) {
                const int cg = 14 * jq + 4 * i + ((lane >> 3) & (i < 3 ? 3 : 1));
                la[i] = sb + OFF_A + (cg >> 3) * 2048 + rg * 1024 + (lane & 7) * 128 + (((cg ^ lane) & 7) << 4);
                int pos = 4 * i + (lane >> 3) + (b >= 64 ? 7 : 0);
                if (pos >= 14) pos -= 14;
                ha[i] = sb + OFF_A + jq * 3584 + rg * 1792 + (lane & 7) * 16 + pos * 128;
                dep |= la[i] | xa[i] | ha[i];
            }
            mbar_wait(bar + 8 * B_LNIN, dep >> 31);
            asm volatile("ld.shared.b32 %0, [%1];" : "=r"(x0) : "r"(l0) : "memory");
#pragma unroll
            for (int i = 0; i < 4; i++) ldsm4(la[i], r[i]);
            float s1[4], s2[4], v[28];
            const float sh = bf_lo(x0);
#pragma unroll
            for (int n = 0; n < 14; n++) { v[2 * n] = bf_lo(r[n >> 2][n & 3]) - sh; v[2 * n + 1] = bf_hi(r[n >> 2][n & 3]) - sh; }
#pragma unroll
            for (int n = 0; n < 28; n++) {
                s1[n & 3] = n < 4 ? v[n] : s1[n & 3] + v[n];
                s2[n & 3] = n < 4 ? v[n] * v[n] : fmaf(v[n], v[n], s2[n & 3]);
            }
            float m1 = (s1[0] + s1[1]) + (s1[2] + s1[3]), m2 = (s2[0] + s2[1]) + (s2[2] + s2[3]);
#pragma unroll
            for (int o = 1; o <= 2; o <<= 1) { m1 += __shfl_xor_sync(0xffffffffu, m1, o); m2 += __shfl_xor_sync(0xffffffffu, m2, o); }
            asm volatile("st.shared.v2.f32 [%0], {%1, %2};" ::"r"(ew), "f"(m1), "f"(m2) : "memory");
            bar_sync<1, 256>();
            float4 e0, e1;
            asm volatile("ld.shared.v4.f32 {%0,%1,%2,%3}, [%4];" : "=f"(e0.x), "=f"(e0.y), "=f"(e0.z), "=f"(e0.w) : "r"(ex) : "memory");
            asm volatile("ld.shared.v4.f32 {%0,%1,%2,%3}, [%4];" : "=f"(e1.x), "=f"(e1.y), "=f"(e1.z), "=f"(e1.w) : "r"(ex + 16) : "memory");
            const float dm = ((e0.x + e0.z) + (e1.x + e1.z)) * (1.f / D_);
            const float var = fmaxf(fmaf(-dm, dm, ((e0.y + e0.w) + (e1.y + e1.w)) * (1.f / D_)), 0.f);
            const float r1 = rsq(var + 1e-5f), sc = rsq(fmaf(1e-5f, var + 1e-5f, var)), of = -dm * sc;
#pragma unroll
            for (int n = 0; n < 14; n++) r[n >> 2][n & 3] = pack2(fmaf(v[2 * n], sc, of), fmaf(v[2 * n + 1], sc, of));
#pragma unroll
            for (int i = 0; i < 3; i++) stsm4(ha[i], r[i][0], r[i][1], r[i][2], r[i][3]);
            stsm2(ha[3], r[3][0], r[3][1]);
            asm volatile("st.shared.v2.b32 [%0], {%1, %2};" ::"r"(ls), "r"(__float_as_uint(r1)), "r"(split2(-(sh + dm))) : "memory");
            TS0(24);
            asm volatile("bar.arrive 10, 288;" ::: "memory");
        }
        float a1[56];
        float rq[2], hb1[2], fb2[2];
        uint32_t qp[14], kp[14];
        const uint32_t ka = sb + OFF_K + warp * 896 + (lane & 7) * 112 + (lane >> 3) * 16;
        const uint32_t va = sb + OFF_V + (warp * 16 + (lane & 15)) * 112 + (lane >> 4) * 16;
        const uint32_t sta = sb + OFF_RSTD + warp * 64 + tq * 8;
        const uint32_t dA = desc_lo(OFF_A + wg * 8192, 16), dH = desc_lo(OFF_B, 1792), dU = desc_lo(OFF_B, 128);
        auto release = [&](uint32_t a) { mbar_arrive_if0(a, lane); };
        uint32_t rel = bar + 8 * (B_EMPTYQ + 6);
        auto g1_step = [&](uint32_t s, uint32_t acc) {
            wg_fence();
#pragma unroll
            for (int k = 0; k < 4; k++) wgmma_n112<1, H_SW, H_H>(a1, dA + s * 1024 + k * 128, dH + s * 896 + k * 224, k ? 1 : acc);
            wg_commit();
            wg_wait<1>();
            release(rel);
            rel = bar + 8 * (B_EMPTY + s);
        };
        auto g1_run = [&](uint32_t r0, uint32_t r1, bool last = false) {
#pragma unroll 1
            for (uint32_t r = g1 ? r0 : r1; r < r1; r++) {
                if (TSG1) TSD(64 + r);
                g1_step(slot(r), r);
                const bool end = last && r + 1 == r1;
                mbar_wait(bar + 8 * (end ? B_FREE : B_FULL + slot(r + 1)), !end && phase(r + 1));
            }
        };
        auto drain = [&]() { wg_wait<0>(); release(rel); rel = bar + 8 * B_NONE; };
        {
            float aq0[28], aq1[28], aq2[28];
            const uint32_t dW = desc_lo(OFF_B + (P & 1) * 16, 16);
            uint32_t xf[2][4][4];
            const uint32_t rb = mapa(bar + 8 * (B_EMPTYQ - 1), z ^ 1);
            auto fetch = [&](int kb, uint32_t (&f)[4][4]) {
                if (TSG1) TSD(178 + kb);
                mbar_wait(bar + 8 * (B_FULLQ + kb), 0);
                if (TSG1) TSD(170 + kb);
#pragma unroll
                for (int k = 0; k < 4; k++) ldsm4(xa[k] + ((XSLOT >> (4 * kb)) & 7) * 16384, f[k]);
            };
            auto mma = [&](int kb, uint32_t (&f)[4][4], int k0, int k1) {
                const uint32_t d0 = dW + ((WSLOT >> (4 * kb)) & 7) * 1536;
                wg_fence();
#pragma unroll
                for (int k = k0; k < k1; k++) {
                    const uint32_t d = d0 + (k >> 1) * 768 + (k & 1) * 128;
                    const int sc = k > 0 ? 1 : kb;
                    wgmma_n56_rs<H_SW, 1>(aq0, f[k], d, sc);
                    wgmma_n56_rs<H_SW, 1>(aq1, f[k], d + 256, sc);
                    wgmma_n56_rs<H_SW, 1>(aq2, f[k], d + 512, sc);
                }
            };
            auto retire = [&](int kb) {
                wg_commit();
                wg_wait<1>();
                mbar_arrive_if0(bar + 8 * (B_EMPTYQ + kb - 1), lane | (kb < 1));
                asm volatile("{\n.reg .pred p;\nsetp.eq.u32 p, %1, 0;\n@p mbarrier.arrive.shared::cluster.b64 _, [%0];\n}"
                             ::"r"(rb + 8 * kb), "r"(lane | ((uint32_t)(kb - 1) > 1)) : "memory");
            };
            auto stage = [&](int kb, uint32_t (&f)[4][4], uint32_t (&n)[4][4]) {
                mma(kb, f, 0, KS);
                retire(kb);
                fetch(kb + 1, n);
                mma(kb, f, KS, 4);
                wg_commit();
            };
            fetch(0, xf[0]);
#pragma unroll 1
            for (int kb = 0; kb < 6; kb += 2) {
                stage(kb, xf[0], xf[1]);
                stage(kb + 1, xf[1], xf[0]);
            }
            mma(6, xf[0], 0, KS);
            retire(6);
            TS0(2);
            mbar_wait(bar + 8 * B_AUX, 0);
            {
                uint32_t (&f)[4] = xf[1][0];
                const uint2* mt = reinterpret_cast<const uint2*>(smem + OFF_STATS) + warp * 16 + g;
                const uint2 m0 = mt[0], m1 = mt[8];
                const uint32_t sel = tq == 0 ? 0x1010 : tq == 1 ? 0x3232 : 0x4444;
                f[0] = __byte_perm(m0.y, 0, sel); f[1] = __byte_perm(m1.y, 0, sel); f[2] = f[3] = 0;
                rq[0] = __uint_as_float(m0.x); rq[1] = __uint_as_float(m1.x);
                asm volatile("" : "+r"(f[0]), "+r"(f[1]), "+r"(f[2]), "+r"(f[3])::"memory");
                const uint32_t d = desc_lo(OFF_CSB + (P & 1) * 128, 0);
                mma(6, xf[0], KS, 4);
                wgmma_n56_rs<H_H, 0>(aq1, f, d + 64, 1);
                wgmma_n56_rs<H_H, 0>(aq2, f, d + 128, 1);
                wgmma_n56_rs<H_H, 0>(aq0, f, d, 1);
                wg_commit();
            }
            mbar_wait(bar + 8 * (g1 ? B_FULL : B_LNIN), 0);
            g1_run(0, wg ? 0 : NE);
            drain();
            pin(aq0); pin(aq1); pin(aq2);
            TSW(3);
            mbar_wait(bar + 8 * (B_EMPTYQ + 5), 0);
#pragma unroll
            for (int i = 0; i < 14; i++) { kp[i] = pack2(aq1[2 * i], aq1[2 * i + 1]); qp[i] = pack2(aq2[2 * i], aq2[2 * i + 1]); }
            stsm4(ka + 896, kp[1], kp[3], kp[5], kp[7]);
            stsm4(ka + 896 + 48, kp[7], kp[9], kp[11], kp[13]);
#pragma unroll
            for (int n = 0; n < 3; n++) stsm4(va + 896 + n * 32, qp[4 * n], qp[4 * n + 1], qp[4 * n + 2], qp[4 * n + 3]);
            stsm2(va + 896 + 96, qp[12], qp[13]);
            __syncwarp();
            mbar_arrive_if0(bar + 8 * B_QKV, tid - 224);
            release(bar + 8 * B_KV);
#pragma unroll
            for (int i = 0; i < 14; i++) qp[i] = pack2(aq0[2 * i], aq0[2 * i + 1]);
            TSW(4);
        }
        g1_run(wg ? 0 : NE, wg ? PRE1 : PRE0);
        {
            uint32_t kf[2][3][4], vf[2][3][4];
            const bool up0 = 2 * tq > g, up1 = 2 * tq + 1 > g, edge = (R | warp) == 0;
            float rk[2][2], fs[2][2], rs[3][2];
            mbar_wait(bar + 8 * (warp ? B_KV : B_HALO), 0);
            const uint32_t tag = *reinterpret_cast<volatile unsigned*>(smem + OFF_EP);
#pragma unroll
            for (int i = 0; i < 2; i++)
                asm volatile("ld.shared.v2.f32 {%0,%1}, [%2];" : "=f"(hb1[i]), "=f"(fb2[i]) : "r"(sb + OFF_BIAS + (warp * 16 + g + 8 * i) * 8) : "memory");
#pragma unroll
            for (int i = 0; i < 3; i++)
                asm volatile("ld.shared.v2.f32 {%0,%1}, [%2];" : "=f"(rs[i][0]), "=f"(rs[i][1]) : "r"(sta + i * 32) : "memory");
#pragma unroll
            for (int hd = 0; hd < 2; hd++) {
                ldsm4(ka + hd * 48, kf[hd][0]);
#pragma unroll
                for (int i = 0; i < 4; i++) { kf[hd][1][i] = kp[6 * hd + 2 * i]; kf[hd][2][i] = kp[6 * hd + 2 * i + 1]; }
                ldsm4t(va + hd * 48, vf[hd][0]); ldsm4t(va + hd * 48 + 32, vf[hd][1]);
                ldsm4t(ka + (OFF_V - OFF_K) + warp * 896 + hd * 48 + 1792, vf[hd][2]);
            }
            const uint32_t q0l = tq < 2 ? qp[6] : 0, q0h = tq < 2 ? qp[7] : 0, q1l = tq < 2 ? 0 : qp[6], q1h = tq < 2 ? 0 : qp[7];
            const uint32_t mk = (up0 ? 0xFFFFu : 0u) | (up1 ? 0xFFFF0000u : 0u);
            g1_run(wg ? PRE1 : PRE0, ATT_STEP);
#pragma unroll
            for (int i = 0; i < 4; i++) {
                rk[i >> 1][i & 1] = ((i & 1) ? up1 : up0) ? rs[i >> 1][i & 1] : rs[(i >> 1) + 1][i & 1];
                fs[i >> 1][i & 1] = rk[i >> 1][i & 1] * (rq[i >> 1] * (0.18898223650461362f * 1.4426950408889634f));
                asm volatile("" : "+f"(fs[i >> 1][i & 1])::"memory");
            }
            uint32_t zr[4], oa[4], dep = q0l | q0h | q1l | q1h | mk;
#pragma unroll
            for (int i = 0; i < 4; i++) {
                zr[i] = (lane + i) * (sb >> 31);
                oa[i] = xa[i] + OFF_OST;
            }
#pragma unroll
            for (int i = 0; i < 4; i++) dep |= __float_as_uint(fs[i >> 1][i & 1]) | oa[i] | zr[i];
            after(dep & (sb >> 31));
            drain();
            bar_sync<1, 256>();
            TS0(19);
            float sc[2][3][4];
#pragma unroll
            for (int u = 0; u < 3; u++) {
#pragma unroll
                for (int i = 0; i < 8; i++) sc[i >> 2][u][i & 3] = 0.f;
                mma16816(sc[0][u], qp[0], qp[1], qp[2], qp[3], kf[0][u][0], kf[0][u][1]);
                mma16816(sc[1][u], q1l, q1h, qp[8], qp[9], kf[1][u][0], kf[1][u][1]);
            }
#pragma unroll
            for (int u = 0; u < 3; u++) {
                mma16816(sc[0][u], qp[4], qp[5], q0l, q0h, kf[0][u][2], kf[0][u][3]);
                mma16816(sc[1][u], qp[10], qp[11], qp[12], qp[13], kf[1][u][2], kf[1][u][3]);
            }
            float e[2][2][2], mx[2][2], sm[2][4];
#pragma unroll
            for (int hd = 0; hd < 2; hd++) {
                e[hd][0][0] = (up0 ? sc[hd][0][0] : sc[hd][1][0]) * fs[0][0];
                e[hd][0][1] = (up1 ? sc[hd][0][1] : sc[hd][1][1]) * fs[0][1];
                e[hd][1][0] = (up0 ? sc[hd][1][2] : sc[hd][2][2]) * fs[1][0];
                e[hd][1][1] = (up1 ? sc[hd][1][3] : sc[hd][2][3]) * fs[1][1];
                if (edge && up0) e[hd][0][0] = -1e30f;
                if (edge && up1) e[hd][0][1] = -1e30f;
                mx[hd][0] = fmaxf(e[hd][0][0], e[hd][0][1]);
                mx[hd][1] = fmaxf(e[hd][1][0], e[hd][1][1]);
            }
#pragma unroll
            for (int o = 1; o <= 2; o <<= 1)
#pragma unroll
                for (int i = 0; i < 4; i++) mx[i >> 1][i & 1] = fmaxf(mx[i >> 1][i & 1], __shfl_xor_sync(0xffffffffu, mx[i >> 1][i & 1], o));
            uint32_t pp[2][2], pu[2][2];
#pragma unroll
            for (int i = 0; i < 4; i++) {
                const float p0 = ex2(e[i >> 1][i & 1][0] - mx[i >> 1][i & 1]), p1 = ex2(e[i >> 1][i & 1][1] - mx[i >> 1][i & 1]);
                pp[i >> 1][i & 1] = pack2(p0 * rk[i & 1][0], p1 * rk[i & 1][1]);
                pu[i >> 1][i & 1] = pack2(p0, p1);
            }
            float ov[2][4][4];
#pragma unroll
            for (int hd = 0; hd < 2; hd++)
#pragma unroll
                for (int n = 0; n < 4; n++) {
                    ov[hd][n][0] = ov[hd][n][1] = ov[hd][n][2] = ov[hd][n][3] = 0.f;
                    mma16816(ov[hd][n], pp[hd][0] & mk, zr[hd], pp[hd][0] & ~mk, pp[hd][1] & mk, vf[hd][n >> 1][2 * (n & 1)], vf[hd][n >> 1][2 * (n & 1) + 1]);
                }
#pragma unroll
            for (int hd = 0; hd < 2; hd++) {
                sm[hd][0] = sm[hd][1] = sm[hd][2] = sm[hd][3] = 0.f;
                mma1688(sm[hd], pu[hd][0], pu[hd][1], 0x3F803F80u);
            }
#pragma unroll
            for (int hd = 0; hd < 2; hd++)
#pragma unroll
                for (int n = 0; n < 4; n++) mma1688(ov[hd][n], zr[2 + hd], pp[hd][1] & ~mk, vf[hd][2][n]);
            TS0(18);
            uint32_t op[16];
            op[14] = op[15] = tag & 0x3FFF;
#pragma unroll
            for (int i = 0; i < 4; i++) sm[i >> 1][i & 1] = rcp(sm[i >> 1][2 * (i & 1)]);
#pragma unroll
            for (int n = 0; n < 7; n++) {
                const bool hb = n > 3 || (n == 3 && tq >= 2);
#pragma unroll
                for (int h = 0; h < 2; h++) {
                    const float r = hb ? sm[1][h] : sm[0][h];
                    const float x0 = hb ? ov[1][n >= 3 ? n - 3 : 0][2 * h] : ov[0][n <= 3 ? n : 0][2 * h];
                    const float x1 = hb ? ov[1][n >= 3 ? n - 3 : 0][2 * h + 1] : ov[0][n <= 3 ? n : 0][2 * h + 1];
                    op[2 * n + h] = pack2(x0 * r, x1 * r);
                }
            }
#pragma unroll
            for (int n = 0; n < 4; n++) stsm4(oa[n], op[4 * n], op[4 * n + 1], op[4 * n + 2], op[4 * n + 3]);
            __syncwarp();
            release(bar + 8 * B_OST);
            mbar_wait(bar + 8 * B_OST, 0);
            TSW(5);
        }
        const uint32_t peer = z ^ 1;
        g1_run(ATT_STEP, wg ? GS : 16, true);
        gate_open(wg | !g1);
        drain();
#pragma unroll 1
        for (uint32_t r = g1 && wg ? GS : 16; r < 16; r++) {
            gate_wait(r == GS);
            g1_step(r - 12, 1);
        }
        drain();
        pin(a1);
        TSW(6);
        send_half(a1, mapa(sb + OFF_RECV1 + wg * 7168, peer), mapa(bar + 8 * (B_RECV1 + wg), peer), t, g1);
        float h[28];
#pragma unroll
        for (int i = 0; i < 28; i++) h[i] = fmaf(a1[i], 0.5f, hb1[(i >> 1) & 1]);
        pin(h);
        if (g1) {
            uint32_t p[14];
            float y[28];
            uint8_t* ub = scr + G_BIMG + ((8 + 2 * q + wg) * 4 + j) * BLK + w4 * 256 + lane * 4;
            uint8_t *u0 = ub + (q < 7 ? 7 : 13) * z * 1024, *u1 = ub + (q < 7 ? 7 : 1) * z * 1024, *u2 = u1 + (q < 7 || z ? 0 : 6144);
            mbar_wait(bar + 8 * (B_RECV1 + wg), __any_sync(0xffffffffu, ((uint64_t)u0 | (uint64_t)u1 | (uint64_t)u2) >> 63));
            TSW(8);
            recv_half(p, sb + OFF_RECV1 + wg * 7168, t);
#pragma unroll
            for (int i = 0; i < 28; i++) {
                h[i] = fmaf((i & 1) ? bf_hi(p[i >> 1]) : bf_lo(p[i >> 1]), 0.5f, h[i]);
                y[i] = h[i] * fmaf(h[i] * h[i], 8.f * 0.0356774081363f, 2.f * 0.7978845608029f);
            }
#pragma unroll
            for (int i = 0; i < 28; i++) asm volatile("tanh.approx.f32 %0, %0;" : "+f"(y[i]));
#pragma unroll
            for (int i = 0; i < 14; i++)
                stg32((i < 2 ? u0 : i < 4 ? u1 : u2) + (i >> 1) * 1024 + (i & 1) * 128, pack2(fmaf(h[2 * i], y[2 * i], h[2 * i]), fmaf(h[2 * i + 1], y[2 * i + 1], h[2 * i + 1])));
            TSW(9);
        }
        float a2[56];
#pragma unroll 1
        for (uint32_t i = 0; i < 4; i++) {
            const uint32_t s = ((g1 ? 0x0564u : 0x2160u) >> (4 * i)) & 7, da = dA + (aoff(s) >> 4), db = dU + (i == 1 ? (OFF_SB - OFF_B) >> 4 : s * 896);
            mbar_wait(bar + 8 * (B_FULL + s), g1 && i == 3);
            TSD(64 + 17 + i);
            wg_fence();
#pragma unroll
            for (int k = 0; k < 4; k++) wgmma_n112<0, H_SW, H_U>(a2, da + k * 2, db + k * 16, k ? 1 : i);
            wg_commit();
            wg_wait<1>();
            release(rel);
            rel = bar + 8 * (B_EMPTY + s);
        }
        TSW(10);
#pragma unroll 1
        for (uint32_t r = r_u; r < r_u + 14 - (wg ? NS2 : 0); r++) {
            const uint32_t s = slot(r);
            mbar_wait(bar + 8 * (B_FULL + s), phase(r));
            TSD(85 + r - r_u);
            wg_fence();
#pragma unroll
            for (int k = 0; k < 4; k++) wgmma_n112<1, H_SW, H_U>(a2, dA + s * 1024 + k * 128, dU + s * 896 + k * 16);
            wg_commit();
            wg_wait<1>();
            release(rel);
            rel = bar + 8 * (B_EMPTY + s);
        }
        uint32_t late = wg;
        asm volatile("" : "+r"(late));
        late = __shfl_sync(0xffffffffu, late, 0);
        gate_open(wg);
        mbar_wait(bar + 8 * B_UDONE, 0);
#pragma unroll 1
        for (uint32_t n = 0; n < late; n++) {
            bar_sync<4, 256>();
            wg_fence();
#pragma unroll
            for (int k = 0; k < 4 * NS2; k++) {
                const uint32_t s = g1 ? (33 - NS2 + k / 4) % 6 : (17 - NS2 + k / 4) % 6;
                wgmma_n112<1, H_SW, H_U>(a2, dA + s * 1024 + k % 4 * 128, dU + s * 896 + k % 4 * 16);
            }
            wg_commit();
        }
        {
            uint32_t ln = lane | (clock32() & (sb >> 31));
            const uint32_t un = warp * 2048 + (ln ^ ((ln >> 3) & 1)) * 16;
            const uint32_t rbuf = mapa(sb + OFF_RECV2, peer), rbar = mapa(bar + 8 * (B_RECV2 + wg), peer);
            uint32_t xr[4][4], u[4][4], sa[4];
#pragma unroll
            for (int i = 0; i < 4; i++) sa[i] = rbuf + (un ^ (i & 1) * 32) + i * 512;
            after((sa[0] | sa[1] | sa[2] | sa[3] | rbar) >> 31);
            wg_wait<0>();
            pin(a2);
            TSW(11);
            auto word = [&](int n, int h) { return pack2(a2[4 * n + 2 * h], a2[4 * n + 2 * h + 1]); };
            send4(sa[1], rbar, word(12, 0), word(13, 0), word(10, 0), word(11, 0), 1);
            send4(sa[3], rbar, word(10, 1), word(11, 1), word(12, 1), word(13, 1), 1);
            send4(sa[0], rbar, word(8, 0), word(9, 0), z ? word(0, 0) : word(8, 1), z ? word(1, 0) : word(9, 1), 1);
            send4(sa[2], rbar, word(0, 1), word(1, 1), word(8, 1), word(9, 1), z);
            const uint32_t nil = clock32() & (sb >> 31);
            const float one = __uint_as_float(0x3F800000u | nil);
#pragma unroll
            for (int i = 0; i < 32; i++) a2[i] = fmaf(a2[i], one, fb2[(i >> 1) & 1]);
#pragma unroll
            for (int i = 0; i < 4; i++) {
                const int n = i % 2 * 4 + (~i & 2), h = i / 2;
                asm volatile("st.shared.v4.b32 [%0], {%1,%2,%3,%4};" ::"r"(sb + OFF_OUT + (un ^ (i & 1) * 32) + i * 512), "r"(word(n, h)), "r"(word(n + 1, h)),
                             "r"(word(n ^ 2, h)), "r"(word(n ^ 3, h)) : "memory");
            }
            ln |= nil;
            const uint32_t la = sb + warp * 2048 + (ln & 1) * 512 + (ln & 6) * 32 + (((ln >> 3) ^ (ln >> 2 & 1) ^ (ln << 1)) & 3) * 16;
            const uint32_t lb = la - (z & ~ln) * 1024;
            const uint32_t lx = sb + OFF_A + slot(r_u + 14) * 16384 + (warp * 16 + (ln >> 3)) * 128 + (((ln ^ (ln >> 3)) & 7) << 4);
            uint8_t* o1 = out + ((q * 128 + warp * 16 + (ln >> 3)) * 896 + j * 224 + z * 96 + (ln & 7) * 16);
            uint8_t* o0 = o1 + (ln & 2 ? -32 : 32);
            auto add_x = [&]() {
#pragma unroll
                for (int i = 0; i < 16; i++) asm("add.rn.bf16x2 %0, %0, %1;" : "+r"(u[i >> 2][i & 3]) : "r"(xr[i >> 2][i & 3]));
            };
            __syncwarp();
#pragma unroll
            for (int i = 0; i < 4; i++) ldsm4(la + OFF_OUT + i / 2 * 1024 + i % 2 * 256, u[i]);
            mbar_wait(bar + 8 * B_XR, 0);
#pragma unroll
            for (int i = 0; i < 4; i++)
                asm volatile("ld.shared.v4.b32 {%0,%1,%2,%3}, [%4];" : "=r"(xr[i][0]), "=r"(xr[i][1]), "=r"(xr[i][2]), "=r"(xr[i][3])
                             : "r"((lx ^ (i % 2 * 64 + (~i & 2) * 16)) + i * 512) : "memory");
            add_x();
            mbar_wait(bar + 8 * (B_RECV2 + wg), (lb | (uint32_t)((uint64_t)o0 >> 32)) >> 31);
            TSW(12);
#pragma unroll
            for (int i = 0; i < 4; i++) ldsm4((i < 2 ? la : lb) + OFF_RECV2 + i / 2 * 1024 + i % 2 * 256, xr[i]);
            add_x();
#pragma unroll
            for (int i = 0; i < 4; i++)
                asm volatile("{\n.reg .pred p;\nsetp.ge.u32 p, %5, %6;\n@p st.global.v4.b32 [%0], {%1,%2,%3,%4};\n}"
                             ::"l"((i < 2 ? o0 : o1) + i * 3584), "r"(u[i][0]), "r"(u[i][1]), "r"(u[i][2]), "r"(u[i][3]), "r"((lane & 6) ^ (~i & 2)), "r"(z) : "memory");
        }
        TSW(13);
    } else if (warp < 12) {
        asm volatile("setmaxnreg.dec.sync.aligned.u32 64;");
        const int hw = warp - 8, t = tid & 127;
        reinterpret_cast<uint32_t*>(smem + OFF_ONES)[t] = t < 64 ? 0x3F803F80u : 0;
        fence_async_smem();
        bar_sync<12, 128>();
        while (clock32() - t_in < DLY1) {}
        uint8_t* cscell = scr + G_CS + ((P * 8 + R) * 2 + z) * 512 + (t >> 2) * 16;
        if ((lane & 3) == 0) cell_put(cscell, 0, 0, 0);
        uint8_t* cells = scr + G_HALO + ((R * 8 + P) * 2 + z) * 3584 + min(t, 111) * 16;
        cell_put(cells, 0, 0, 0);
        cell_put(cells + 1792, 0, 0, 0);
        const unsigned e1 = epoch();
        const uint32_t bv1 = ldg_u16(b1 + (g1 ? q * 128 : 0) + t), bv2 = ldg_u16(b2 + q * 128 + t);
        {
            const uint32_t da = desc_lo(OFF_B + min((R & 1) * 2 + z, 2) * 4096, 16), db = desc_lo(OFF_ONES, 128);
            float c0[4];
            mbar_wait(bar + 8 * B_FULLQ, 0);
            mbar_wait(bar + 8 * (B_FULLQ + 1), 0);
            TSH(47);
            wg_fence();
#pragma unroll
            for (int k = 0; k < 8; k++)
                wgmma_n8<1, H_SW, H_H>(c0, da + ((WSLOT >> (k & 4)) & 7) * 1536 + (k & 2) * 384 + (k & 1) * 128, db + (k >= 4 && R >= 6 ? 16 : 0), k);
            wg_commit();
            wg_wait<0>();
            pin(c0);
            if ((lane & 3) == 0) cell_put(cscell, __float_as_uint(c0[0]), __float_as_uint(c0[2]), e1);
            if (lane < 4) asm volatile("mbarrier.arrive.shared::cluster.b64 _, [%0];" ::"r"(mapa(bar + 8 * (B_EMPTYQ + (lane >> 1)), lane & 1)) : "memory");
            TSH(43);
        }
        mbar_wait(bar + 8 * (B_FULLQ + GATHER), 0);
        TSH(39);
        {
            const bool cw = hw < 3;
            const uint8_t* src = cw ? scr + G_CS + P * 8192 + t * 16 : scr + G_STATS + (z * 1024 + R * 128 + lane) * 16;
            uint32_t a[5], d[5], bad;
            do {
                bad = 0;
#pragma unroll
                for (int i = 0; i < 4; i++) bad |= cell_get(src + i * (cw ? 2048 : 512), a[i], d[i], e1);
                if (t >= 120) bad |= cell_get(src - (R ? 512 : 0), a[4], d[4], e1);
            } while (bad);
            TSH(45);
            if (cw) {
                uint4* cb = reinterpret_cast<uint4*>(smem + OFF_CSB) + (t >> 3) * 16 + (t & 7);
                const uint32_t lo = split2((__uint_as_float(a[0]) + __uint_as_float(a[1])) + (__uint_as_float(a[2]) + __uint_as_float(a[3])));
                const uint32_t hi = split2((__uint_as_float(d[0]) + __uint_as_float(d[1])) + (__uint_as_float(d[2]) + __uint_as_float(d[3])));
                cb[0] = make_uint4(lo, lo, 0, 0);
                cb[8] = make_uint4(hi, hi, 0, 0);
            } else {
                uint2* st = reinterpret_cast<uint2*>(smem + OFF_STATS) + lane;
                uint32_t* rd = reinterpret_cast<uint32_t*>(smem + OFF_RSTD) + lane;
#pragma unroll
                for (int i = 0; i < 4; i++) { st[32 * i] = make_uint2(a[i], d[i]); rd[8 + 32 * i] = a[i]; }
                if (t >= 120) rd[-24] = a[4];
            }
            fence_async_smem();
            __syncwarp();
            mbar_arrive_if0(bar + 8 * B_AUX, lane);
            TSH(41);
            reinterpret_cast<float2*>(smem + OFF_BIAS)[t] = make_float2(0.5f * bf_lo(bv1), bf_lo(bv2));
            __syncwarp();
            mbar_arrive_if0(bar + 8 * B_KV, lane);
        }
        {
            uint2* kv = reinterpret_cast<uint2*>(smem + OFF_K) + min(t, 111);
            mbar_wait(bar + 8 * B_QKV, 0);
            uint2 k2 = kv[896], v2 = kv[1792 + (OFF_V - OFF_K) / 8];
            cell_put(cells, k2.x, k2.y, e1);
            cell_put(cells + 1792, v2.x, v2.y, e1);
            k2 = v2 = make_uint2(0, 0);
            delay(DH);
            if (R > 0) while (cell_get(cells - 16 * 3584, k2.x, k2.y, e1) | cell_get(cells - 16 * 3584 + 1792, v2.x, v2.y, e1)) {}
            kv[0] = k2;
            kv[(OFF_V - OFF_K) / 8] = v2;
            mbar_wait(bar + 8 * B_KV, 0);
            __syncwarp();
            mbar_arrive_if0(bar + 8 * B_HALO, lane);
            TSH(40);
        }
        if (hw == 3) {
            mbar_wait(bar + 8 * B_OST, 0);
            if (elect()) {
                unsigned* oc = ctr + C_O + (R * 2 + (P >> 2)) * 32;
                TS(38);
                fence_async_smem();
                TS(46);
#pragma unroll
                for (int i = 0; i < 4; i++) {
                    tma2d_store(&mp.ost, sb + OFF_OST + i * 4096, z * 64, P * 1024 + R * 128 + i * 32);
                    bulk_commit();
                }
                TS(7);
                asm volatile("mbarrier.arrive.relaxed.cluster.shared::cluster.b64 _, [%0];" ::"r"(mapa(bar + 8 * B_FREE, z ^ 1)) : "memory");
                bulk_wait_read<3>();
                delay(DO);
                red_relaxed(oc, 1);
                TS(21);
                mbar_wait(bar + 8 * B_LNIN, 0);
                bulk_wait_read<0>();
                mbar_arrive(bar + 8 * B_QKV);
                TS(20);
                mbar_wait(bar + 8 * (B_EMPTY + 6), 0);
                asm volatile("mbarrier.arrive.relaxed.cluster.shared::cluster.b64 _, [%0];" ::"r"(mapa(bar + 8 * B_UDONE, z ^ 1)) : "memory");
            }
        } else {
            const uint32_t tag = e1 & 0x3FFF;
            const uint32_t ca = sb + OFF_A + lane * 128 + ((~lane & 7) << 4) + (lane >> 3) * 4, cb = sb + OFF_B + lane * 132;
            uint32_t par = 0x7F;
#pragma unroll 1
            for (uint32_t i = hw ? 3 - hw : 0; i < 18;) {
                const uint32_t s = xslot(i);
                const bool isa = i < 4;
                const uint32_t a0 = isa ? ca + aoff(s) : cb + s * BLK, a3 = a0 - (isa ? 0 : (lane & 16) * 132);
                mbar_wait(bar + 8 * (B_LAND + s), (par >> s) & 1);
                par ^= 1 << s;
                bool ok = true;
#pragma unroll
                for (int k = 0; k < 4; k++) {
                    uint32_t v;
                    asm volatile("ld.shared.b32 %0, [%1];" : "=r"(v) : "r"((k < 3 ? a0 : a3) + k * 4096) : "memory");
                    ok &= (v == (isa ? tag : ~0u)) == isa;
                }
                const uint32_t bad = __ballot_sync(0xffffffffu, !ok);
                mbar_arrive_if0(bar + 8 * (B_FULL + s), lane | bad);
                if (!bad) {
                    if (i == 0 || i == 4) TS(i ? 30 : 29);
                    i += i < 1 ? 4 : i == 1 ? 2 : 3;
                } else if (elect()) {
                    TS(31);
                    fetch_x(i);
                }
            }
        }
    } else {
        asm volatile("setmaxnreg.dec.sync.aligned.u32 32;");
        auto wait_free = [&](uint32_t r, uint32_t first) {
            const uint32_t a = r < 6 ? B_EMPTYQ + ((first >> (4 * r)) & 7) : B_EMPTY + slot(r);
            mbar_wait(bar + 8 * a, r < 6 ? 0 : phase(r) ^ 1);
        };
        if (warp == 12) {
            TS(14);
            if (elect()) {
#pragma unroll 1
                for (int kb = 1; kb < 7; kb++) {
                    if (kb == 1) while (clock32() - t_in < DLY2) {}
                    if (kb >= QDEPTH) { mbar_wait(bar + 8 * (B_FULLQ + kb - QDEPTH), 0); TS(25 + kb - QDEPTH); }
                    if (kb >= 5) mbar_wait(bar + 8 * (B_EMPTYQ + kb - 5), 0);
                    x_load(kb);
                    w_load(kb);
                }
                TS(17);
                mbar_wait(bar + 8 * B_LNFREE, 0);
                if (!g1) {
                    const int ic = (q - 14) * 8 + j * 2 + z, rot = ic >> 3;
                    mbar_wait(bar + 8 * (B_EMPTYQ + 2), 0);
                    mbar_expect(bar + 8 * B_GO, 2 * BLK);
#pragma unroll 1
                    for (int i = 0; i < 2; i++) tma4d(sb + OFF_A + i * BLK, &mp.wo, 0, 0, (z * 2 + i) * 14, ic >> 1, bar + 8 * B_GO);
                    mbar_wait(bar + 8 * B_GO, 0);
#pragma unroll 1
                    for (int i = 0; i < 2; i++) {
                        uint8_t* dst = scr + G_BIMG + (ic * 2 + i) * BLK;
                        bulk_store(dst, sb + OFF_A + i * BLK, 2048);
                        bulk_store(dst + 2048 + rot * 6144, sb + OFF_A + i * BLK + 2048, 6144);
                        bulk_store(dst + 8192 - rot * 6144, sb + OFF_A + i * BLK + 8192, 6144);
                    }
                    bulk_commit();
                    bulk_wait_all();
                    publish(ctr + C_WO);
                    TS(44);
                }
#pragma unroll 1
                for (uint32_t r = 0; r < r_o; r++) {
                    const uint32_t s = slot(r), fb = bar + 8 * (B_FULL + s);
                    wait_free(r, 0x654320u);
                    mbar_expect(fb, 16384);
                    tma3d(sb + OFF_A + s * 16384, &mp.w1, 0, z * 1024 + r * 64, 2 * q, fb);
                    TS(99 + r);
                }
                mbar_wait(bar + 8 * B_OST, 0);
                mbar_expect(bar + 8 * (B_LAND + 6), 16384);
                wait_free(r_o, 0x654320u);
                mbar_expect(bar + 8 * (B_LAND + slot(r_o)), 16384);
                poll(ctr + C_O + ((q & ~1) + z) * 32, epoch() * 8);
                TS(32);
                fetch_x(0, false);
                mbar_wait(bar + 8 * B_QKV, 1);
                fetch_x(1, false);
                TS(99 + 17);
#pragma unroll 1
                for (uint32_t i = 1; i < 3; i++) {
                    wait_free(r_o + i, 0x654320u);
                    fetch_x(i + 1);
                }
                TS(99 + 20);
#pragma unroll 1
                for (uint32_t i = 0; i < 14; i++) {
                    const uint32_t r = r_u + i, s = slot(r), fb = bar + 8 * (B_FULL + s);
                    if (g1 && i == 3) { mbar_wait(bar + 8 * (B_GO + 2), 0); delay(DW); }
                    wait_free(r, 0x654320u);
                    mbar_expect(fb, 16384);
                    tma3d(sb + OFF_A + s * 16384, &mp.w2, 0, (14 * z + (i < 7 ? 2 * i : 2 * i - 13)) * 64, 2 * q, fb);
                    TS(99 + 21 + i);
                }
                wait_free(r_u + 14, 0);
                mbar_expect(bar + 8 * B_XR, 16384);
                tma2d(sb + OFF_A + slot(r_u + 14) * 16384, &mp.xn, j * 112 + z * 48, q * 128, bar + 8 * B_XR);
            }
        } else if (warp == 13) {
            if (elect()) {
#pragma unroll 1
                for (int ph = g1 ? 0 : 1; ph < 4; ph++) {
                    const uint8_t* src = ph == 0 ? scr + G_HIMG + (64 * z + j) * BLK : scr + G_BIMG + ((ph == 1 ? 4 * z : 6 + 14 * z + ph) * 4 + j) * BLK;
                    const uint32_t r0 = ph == 0 ? 0 : r_o + (ph == 1 ? 0 : 7 * ph - 11), r1 = r_o + (ph == 0 ? 0 : 7 * ph - 4);
                    if (ph == 1) {
                        mbar_wait(bar + 8 * B_OST, 0);
                        mbar_expect(bar + 8 * (B_FULL + 6), BLK);
                        mbar_wait(bar + 8 * (B_GO + 1), 0);
                        bulk_load(sb + OFF_SB, src + 4 * BLK, BLK, bar + 8 * (B_FULL + 6));
                    }
#pragma unroll 1
                    for (uint32_t r = r0; r < r1; r++, src += r <= r_o || r == r_o + 2 ? 4 * BLK : 8 * BLK) {
                        const uint32_t s = slot(r), fb = bar + 8 * ((ph < 2 ? B_FULL : B_LAND) + s);
                        wait_free(r, 0x644332u);
                        mbar_expect(fb, BLK);
                        if (r == r0) {
                            if (ph == 0) {
                                poll(ctr + C_LN, epoch() * 128);
                                fence_async_global();
                                TS(33);
                            } else mbar_wait(bar + 8 * (B_GO + ph), 0);
                        }
                        bulk_load(sb + OFF_B + s * BLK, src, BLK, fb);
                        TS(134 + 16 + 2 * (ph > 0) + r - r_o);
                    }
                }
            }
        } else if (warp == 14) {
            uint8_t* stcell = scr + G_STATS + ((lane & 1) * 1024 + 8 * b + (lane >> 1)) * 16;
            if (lane < 16) cell_put(stcell, 0, 0, 0);
            const unsigned ev = ld_relaxed(ctr + C_LN);
            uint8_t* hb = scr + G_HIMG + (b & ~3) * BLK;
            const unsigned e1 = (ev >> 7) + 1;
            if (lane == 0) {
                *reinterpret_cast<volatile unsigned*>(smem + OFF_EP) = e1;
                mbar_arrive(bar + 8 * B_EP);
                TS(36);
            }
            bar_sync<10, 288>();
            if (elect()) {
                fence_async_smem();
                TS(42);
                tma4d_store(&mp.hst, sb + OFF_A, 0, 0, b & 3, b & ~3);
                bulk_commit();
            }
            __syncwarp();
            if (lane < 16) {
                const uint2 v = reinterpret_cast<const uint2*>(smem + OFF_LNST)[lane];
                cell_put(stcell, v.x, v.y, e1);
            }
            const uint8_t* hl = hb + ((b & 3) * 28 + min(lane, 27)) * 128;
            mbar_wait(bar + 8 * B_LNIN, (uint64_t)hl >> 63);
            bulk_wait_all();
            __syncwarp();
            mbar_arrive_if0(bar + 8 * B_LNFREE, lane);
            TS(63);
            unsigned rb = 0;
#pragma unroll
            for (int i = 0; i < 4; i++) rb |= ld_relaxed(reinterpret_cast<const unsigned*>(hl + i * BLK));
            if (elect()) {
                red_relaxed(ctr + C_LN, 1 + (rb & (sb >> 31)));
                TS(37);
#pragma unroll 1
                for (int ph = 1; ph < 4; ph++) {
                    mbar_wait(bar + 8 * (ph == 1 ? B_HALO : g1 ? B_RECV1 : B_OST), 0);
                    poll(ctr + ph * 32 + (ph >> 1) * z * 64, e1 * (ph == 1 ? 16 : 56));
                    fence_async_global();
                    mbar_arrive(bar + 8 * (B_GO + ph));
                    if (ph != 1) TS(32 + ph);
                }
            }
        } else {
            if ((sb & 0x3FFFF) != SB0) __trap();
            if (elect()) {
#pragma unroll 1
                for (int i = 3; i < 10; i++) asm volatile("prefetch.tensormap [%0];" ::"l"(reinterpret_cast<const CUtensorMap*>(&mp) + i) : "memory");
            }
            __syncwarp();
            mbar_watch(bar + 8 * B_KV, 0);
#pragma unroll 1
            for (int i = g1 ? 0 : 8; i < 8; i++) {
                uint32_t l = 56 * z + (i & 3) * 14 + min(lane >> 1, 13);
                if (q >= 7 && l >= 16) l += l < 64 ? 48 : -48;
                cell_put(scr + G_BIMG + ((8 + 2 * q + (i >> 2)) * 4 + j) * BLK + l * 128 + (l & 24) * 4 + (lane & 1) * 16, ~0u, ~0u, ~0u);
            }
            __threadfence();
            __syncwarp();
            mbar_arrive_if0(bar + 8 * B_FREE, lane);
            TS(59);
#pragma unroll 1
            for (int i = g1 ? 0 : 2; i < 2; i++) {
                mbar_watch(bar + 8 * (B_RECV1 + i), 0);
                delay(DU);
                if (lane == 0) red_relaxed(ctr + C_U + ((q >= 7 ? 2 : 0) + i) * 32, 1);
                TS(22 + i);
            }
            mbar_watch(bar + 8 * B_FREE, 0);
            mbar_watch(bar + 8 * B_RECV2, 0);
            mbar_watch(bar + 8 * (B_RECV2 + 1), 0);
        }
    }
}

typedef CUresult (*EncodeFn)(CUtensorMap*, CUtensorMapDataType, cuuint32_t, void*, const cuuint64_t*, const cuuint64_t*, const cuuint32_t*,
                             const cuuint32_t*, CUtensorMapInterleave, CUtensorMapSwizzle, CUtensorMapL2promotion, CUtensorMapFloatOOBfill);

void encode(EncodeFn fn, CUtensorMap* m, const void* p, int rank, const cuuint64_t* dims, const cuuint64_t* strides, const cuuint32_t* box, bool swz) {
    const cuuint32_t es[4] = {1, 1, 1, 1};
    fn(m, CU_TENSOR_MAP_DATA_TYPE_BFLOAT16, rank, const_cast<void*>(p), dims, strides, box, es, CU_TENSOR_MAP_INTERLEAVE_NONE,
       swz ? CU_TENSOR_MAP_SWIZZLE_128B : CU_TENSOR_MAP_SWIZZLE_NONE, CU_TENSOR_MAP_L2_PROMOTION_L2_128B, CU_TENSOR_MAP_FLOAT_OOB_FILL_NONE);
}

}

extern "C" void kernel_launch(void* const* d_in, const int* in_sizes, int n_in, void* d_out, int out_size) {
    const __nv_bfloat16* x = (const __nv_bfloat16*)d_in[0];
    const __nv_bfloat16* wqkv = (const __nv_bfloat16*)d_in[1];
    const __nv_bfloat16* wo = (const __nv_bfloat16*)d_in[2];
    const __nv_bfloat16* w1 = (const __nv_bfloat16*)d_in[4];
    const __nv_bfloat16* b1 = (const __nv_bfloat16*)d_in[5];
    const __nv_bfloat16* w2 = (const __nv_bfloat16*)d_in[6];
    const __nv_bfloat16* b2 = (const __nv_bfloat16*)d_in[7];

    void* fp = nullptr;
    cudaDriverEntryPointQueryResult qr;
    cudaGetDriverEntryPoint("cuTensorMapEncodeTiled", &fp, cudaEnableDefault, &qr);
    EncodeFn fn = (EncodeFn)fp;
    void* sp = nullptr;
    cudaGetSymbolAddress(&sp, g_scratch);
    uint8_t* scr = (uint8_t*)sp;
    void *o = scr + G_O, *himg = scr + G_HIMG;

    Maps mp;
    { cuuint64_t d[3] = {64, 2048, 7}, s[2] = {896, 128}; cuuint32_t bx[3] = {64, 16, 7}; encode(fn, &mp.xl, x, 3, d, s, bx, true); }
    { cuuint64_t d[2] = {896, 1024}, s[1] = {1792}; cuuint32_t bx[2] = {64, 128}; encode(fn, &mp.x, x, 2, d, s, bx, true); }
    { cuuint64_t d[3] = {448, 448, 3}, s[2] = {2688, 896}; cuuint32_t bx[3] = {64, 32, 3}; encode(fn, &mp.wqkv, wqkv, 3, d, s, bx, true); }
    { cuuint64_t d[3] = {64, 2048, 28}, s[2] = {3584, 128}; cuuint32_t bx[3] = {64, 64, 2}; encode(fn, &mp.w1, w1, 3, d, s, bx, true); }
    { cuuint64_t d[3] = {64, 1792, 32}, s[2] = {4096, 128}; cuuint32_t bx[3] = {64, 64, 2}; encode(fn, &mp.w2, w2, 3, d, s, bx, true); }
    { cuuint64_t d[4] = {64, 28, 4, 128}, s[3] = {128, 3584, BLK}; cuuint32_t bx[4] = {64, 28, 1, 4}; encode(fn, &mp.hst, himg, 4, d, s, bx, false); }
    { cuuint64_t d[2] = {448, 2048}, s[1] = {896}; cuuint32_t bx[2] = {64, 128}; encode(fn, &mp.xn, x, 2, d, s, bx, true); }
    { cuuint64_t d[2] = {64, 8 * 2048}, s[1] = {128}; cuuint32_t bx[2] = {64, 128}; encode(fn, &mp.old_, o, 2, d, s, bx, true); }
    { cuuint64_t d[2] = {128, 8 * 1024}, s[1] = {256}; cuuint32_t bx[2] = {64, 32}; encode(fn, &mp.ost, o, 2, d, s, bx, true); }
    { cuuint64_t d[4] = {8, 56, 56, 8}, s[3] = {896, 16, 56 * 896}; cuuint32_t bx[4] = {8, 64, 14, 1}; encode(fn, &mp.wo, wo, 4, d, s, bx, false); }

    cudaFuncSetAttribute(fused_kernel, cudaFuncAttributeMaxDynamicSharedMemorySize, SMEM_BYTES);
    fused_kernel<<<128, 512, SMEM_BYTES>>>(x, b1, b2, scr, (uint8_t*)d_out, mp);
}
```
